```python
import torch

def _softmax(x, axis=-1):
    return torch.softmax(x, dim=axis)
def _gelu(x):
    return torch.nn.functional.gelu(x, approximate="tanh")
def _silu(x):
    return torch.nn.functional.silu(x)
def _sigmoid(x):
    return torch.sigmoid(x)
def _layernorm(x, axis=-1, eps=1e-5):
    m = x.mean(dim=axis, keepdim=True)
    v = x.var(dim=axis, keepdim=True, unbiased=False)
    return (x - m) / torch.sqrt(v + eps)
def _scatter_add(tgt, idx, src, axis=0):
    return tgt.clone().index_add_(axis, idx, src)
def _segment_sum(src, seg, n):
    out = torch.zeros((n,) + src.shape[1:], dtype=src.dtype)
    return out.index_add_(0, seg, src)
def _pad(x, pw):
    flat = tuple(v for pair in reversed(pw) for v in pair)
    return torch.nn.functional.pad(x, flat)

kernel_name = 'parallel_sum__mha_block__mixer_channel_mlp__prompt'

def setup_inputs():

    _w = (lambda a: (lambda t: t.to(torch.bfloat16) if t.is_floating_point() else t)(torch.as_tensor(a)))
    def _A_setup():
        B, S, D, H = 1, 2048, 640, 32
        return {
            "x": _w((lambda *s: torch.randn(*s, dtype=torch.bfloat16) * 0.05)(B, S, D)),
            "wqkv": _w((lambda *s: torch.randn(*s, dtype=torch.bfloat16) * 0.05)(D, 3 * D)),
            "wo": _w((lambda *s: torch.randn(*s, dtype=torch.bfloat16) * 0.05)(D, D)),
        }
    _A_in = _A_setup()

    def _B_setup():
        B, S, D, F = 1, 2048, 640, 1536
        return {
            "x": _w((lambda *s: torch.randn(*s, dtype=torch.bfloat16) * 0.05)(B, S, D)),
            "w1": _w((lambda *s: torch.randn(*s, dtype=torch.bfloat16) * 3.2)(D, F) * (D ** -0.5)),
            "b1": _w((lambda *s: torch.randn(*s, dtype=torch.bfloat16) * 1.6)(F)),
            "w2": _w((lambda *s: torch.randn(*s, dtype=torch.bfloat16) * 0.1)(F, D) * (F ** -0.5)),
            "b2": _w((lambda *s: torch.randn(*s, dtype=torch.bfloat16) * 0.2)(D)),
        }
    _B_in = _B_setup()

    return {
        "A_x": _A_in["x"],
        "A_wqkv": _A_in["wqkv"],
        "A_wo": _A_in["wo"],
        "B_x": _B_in["x"],
        "B_w1": _B_in["w1"],
        "B_b1": _B_in["b1"],
        "B_w2": _B_in["w2"],
        "B_b2": _B_in["b2"],
    }

def reference(A_x, A_wqkv, A_wo, B_x, B_w1, B_b1, B_w2, B_b2):
    def _A_ref(x, wqkv, wo):
        B, S, D = x.shape
        H = 32
        Dh = D // H
        qkv = (lambda x, *d: x.permute(*d))((x @ wqkv).reshape(B, S, 3, H, Dh), 2, 0, 3, 1, 4)
        q, k, v = qkv[0], qkv[1], qkv[2]
        scores = torch.einsum("bhqd,bhkd->bhqk", q, k) * (Dh ** -0.5)
        p = _softmax(scores, axis=-1)
        o = torch.einsum("bhqk,bhkd->bhqd", p, v)
        return (lambda x, *d: x.permute(*d))(o, 0, 2, 1, 3).reshape(B, S, D) @ wo

    def _B_ref(x, w1, b1, w2, b2):
        y = _layernorm(x, axis=-1)
        h = _gelu(torch.einsum("bsd,df->bsf", y, w1) + b1)
        return torch.einsum("bsf,fd->bsd", h, w2) + b2

    x = A_x
    xn = _layernorm(x, axis=-1)
    return x + _A_ref(xn, A_wqkv, A_wo) + _B_ref(xn, B_w1, B_b1, B_w2, B_b2)
```

```cpp
#include <cuda_runtime.h>
#include <cuda_bf16.h>
#include <cuda.h>
#include <stdint.h>

namespace {

constexpr int SEQ = 2048, DM = 640, FF = 1536;
constexpr float LN_EPS = 1e-5f;

constexpr int IMG_BYTES = 256 * 384;
constexpr uint32_t EMU_MASK = 0xD5D5u;
constexpr float SAFE_BOUND = 80.0f;
constexpr float QSCALE = 0.22360679774997896f * 1.4426950408889634f;

__device__ __align__(1024) __nv_bfloat16 g_xn[SEQ * DM];
__device__ float g_r2[SEQ];
__device__ __align__(1024) uint8_t g_img[96 * IMG_BYTES + 1024];
__device__ float g_nrm[64 * SEQ];
__device__ __align__(1024) __nv_bfloat16 g_h[SEQ * FF];
__device__ __align__(1024) __nv_bfloat16 g_o[SEQ * DM];

__device__ __forceinline__ uint32_t smem_u32(const void* p) { return (uint32_t)__cvta_generic_to_shared(p); }
__device__ __forceinline__ void mbar_init(uint32_t bar, int cnt) {
    asm volatile("mbarrier.init.shared::cta.b64 [%0], %1;" ::"r"(bar), "r"(cnt));
}
__device__ __forceinline__ void mbar_expect_tx(uint32_t bar, uint32_t bytes) {
    asm volatile("mbarrier.arrive.expect_tx.shared::cta.b64 _, [%0], %1;" ::"r"(bar), "r"(bytes) : "memory");
}
__device__ __forceinline__ void mbar_wait(uint32_t bar, uint32_t parity) {
    asm volatile("{\n.reg .pred p;\n.reg .u32 n;\nmov.u32 n, 0;\n"
                 "WAIT_LOOP:\nmbarrier.try_wait.parity.shared::cta.b64 p, [%0], %1;\n@p bra WAIT_DONE;\n"
                 "add.u32 n, n, 1;\nsetp.lt.u32 p, n, 4194304;\n@p bra WAIT_LOOP;\nWAIT_DONE:\n}"
                 ::"r"(bar), "r"(parity) : "memory");
}
__device__ __forceinline__ void mbar_arrive(uint32_t bar) {
    asm volatile("mbarrier.arrive.shared::cta.b64 _, [%0];" ::"r"(bar) : "memory");
}
__device__ __forceinline__ void mbar_arrive_cluster(uint32_t bar, uint32_t cta) {
    asm volatile("{\n.reg .b32 ra;\nmapa.shared::cluster.u32 ra, %0, %1;\n"
                 "mbarrier.arrive.shared::cluster.b64 _, [ra];\n}" ::"r"(bar), "r"(cta) : "memory");
}
__device__ __forceinline__ void fence_barrier_init() { asm volatile("fence.mbarrier_init.release.cluster;" ::: "memory"); }
__device__ __forceinline__ void fence_proxy_async() { asm volatile("fence.proxy.async.shared::cta;" ::: "memory"); }
__device__ __forceinline__ void cluster_sync() {
    asm volatile("barrier.cluster.arrive.release.aligned;\nbarrier.cluster.wait.acquire.aligned;" ::: "memory");
}
__device__ __forceinline__ bool elect_one() {
    uint32_t pred;
    asm volatile("{\n.reg .pred p;\nelect.sync _|p, 0xFFFFFFFF;\nselp.b32 %0, 1, 0, p;\n}" : "=r"(pred));
    return pred != 0;
}
__device__ __forceinline__ void pdl_launch() { asm volatile("griddepcontrol.launch_dependents;" ::: "memory"); }
__device__ __forceinline__ void pdl_wait() { asm volatile("griddepcontrol.wait;" ::: "memory"); }
__device__ __forceinline__ void prefetch_map(const CUtensorMap* m) {
    asm volatile("prefetch.tensormap [%0];" ::"l"(m) : "memory");
}
__device__ __forceinline__ void tma_load(uint32_t dst, const CUtensorMap* m, int c0, int c1, uint32_t bar) {
    asm volatile("cp.async.bulk.tensor.2d.shared::cluster.global.mbarrier::complete_tx::bytes [%0], [%1, {%3, %4}], [%2];"
                 ::"r"(dst), "l"(m), "r"(bar), "r"(c0), "r"(c1) : "memory");
}
__device__ __forceinline__ void tma_load_mc(uint32_t dst, const CUtensorMap* m, int c0, int c1, uint32_t bar, uint16_t mask) {
    asm volatile("cp.async.bulk.tensor.2d.shared::cluster.global.mbarrier::complete_tx::bytes.multicast::cluster"
                 " [%0], [%1, {%3, %4}], [%2], %5;"
                 ::"r"(dst), "l"(m), "r"(bar), "r"(c0), "r"(c1), "h"(mask) : "memory");
}
__device__ __forceinline__ void tma_store(const CUtensorMap* m, uint32_t src, int c0, int c1) {
    asm volatile("cp.async.bulk.tensor.2d.global.shared::cta.bulk_group [%0, {%2, %3}], [%1];"
                 ::"l"(m), "r"(src), "r"(c0), "r"(c1) : "memory");
}
__device__ __forceinline__ void bulk_commit() { asm volatile("cp.async.bulk.commit_group;" ::: "memory"); }
__device__ __forceinline__ void bulk_wait_all() { asm volatile("cp.async.bulk.wait_group 0;" ::: "memory"); }
__device__ __forceinline__ void bulk_load(uint32_t dst, const void* src, uint32_t bytes, uint32_t bar) {
    asm volatile("cp.async.bulk.shared::cluster.global.mbarrier::complete_tx::bytes [%0], [%1], %2, [%3];"
                 ::"r"(dst), "l"(src), "r"(bytes), "r"(bar) : "memory");
}
__device__ __forceinline__ void wg_fence() { asm volatile("wgmma.fence.sync.aligned;" ::: "memory"); }
__device__ __forceinline__ void wg_commit() { asm volatile("wgmma.commit_group.sync.aligned;" ::: "memory"); }
template <int N> __device__ __forceinline__ void wg_wait() {
    asm volatile("wgmma.wait_group.sync.aligned %0;" ::"n"(N) : "memory");
}
template <int N> __device__ __forceinline__ void reg_alloc() { asm volatile("setmaxnreg.inc.sync.aligned.u32 %0;" ::"n"(N)); }
template <int N> __device__ __forceinline__ void reg_dealloc() { asm volatile("setmaxnreg.dec.sync.aligned.u32 %0;" ::"n"(N)); }
template <int N> __device__ __forceinline__ void fence_regs(float (&d)[N]) {
#pragma unroll
    for (int i = 0; i < N; i++) asm volatile("" : "+f"(d[i])::"memory");
}
__device__ __forceinline__ uint64_t make_desc(uint32_t addr, uint32_t lbo, uint32_t sbo, uint32_t swz) {
    return (uint64_t)((addr & 0x3FFFF) >> 4) | ((uint64_t)(lbo >> 4) << 16) | ((uint64_t)(sbo >> 4) << 32) |
           ((uint64_t)swz << 62);
}
__device__ __forceinline__ uint32_t pack_bf16(float lo, float hi) {
    uint32_t r;
    asm("cvt.rn.bf16x2.f32 %0, %1, %2;" : "=r"(r) : "f"(hi), "f"(lo));
    return r;
}
__device__ __forceinline__ float ex2(float x) {
    float r;
    asm("ex2.approx.ftz.f32 %0, %1;" : "=f"(r) : "f"(x));
    return r;
}
__device__ __forceinline__ float bf_lo(uint32_t v) { return __uint_as_float(v << 16); }
__device__ __forceinline__ float bf_hi(uint32_t v) { return __uint_as_float(v & 0xFFFF0000u); }
__device__ __forceinline__ void stmatrix_x4(uint32_t addr, uint32_t r0, uint32_t r1, uint32_t r2, uint32_t r3) {
    asm volatile("stmatrix.sync.aligned.m8n8.x4.shared.b16 [%0], {%1, %2, %3, %4};"
                 ::"r"(addr), "r"(r0), "r"(r1), "r"(r2), "r"(r3) : "memory");
}

__device__ __forceinline__ void wgmma_n240_ss_tb(float (&d)[120], uint64_t descA, uint64_t descB, int scaleD) {
    asm volatile("{\n.reg .pred p;\nsetp.ne.b32 p, %122, 0;\n"
        "wgmma.mma_async.sync.aligned.m64n240k16.f32.bf16.bf16 {"
        "%0, %1, %2, %3, %4, %5, %6, %7, %8, %9, %10, %11, %12, %13, %14, %15, "
        "%16, %17, %18, %19, %20, %21, %22, %23, %24, %25, %26, %27, %28, %29, %30, %31, "
        "%32, %33, %34, %35, %36, %37, %38, %39, %40, %41, %42, %43, %44, %45, %46, %47, "
        "%48, %49, %50, %51, %52, %53, %54, %55, %56, %57, %58, %59, %60, %61, %62, %63, "
        "%64, %65, %66, %67, %68, %69, %70, %71, %72, %73, %74, %75, %76, %77, %78, %79, "
        "%80, %81, %82, %83, %84, %85, %86, %87, %88, %89, %90, %91, %92, %93, %94, %95, "
        "%96, %97, %98, %99, %100, %101, %102, %103, %104, %105, %106, %107, %108, %109, %110, %111, "
        "%112, %113, %114, %115, %116, %117, %118, %119}, "
        "%120, %121, p, 1, 1, 0, 1;\n}\n"
        : "+f"(d[0]), "+f"(d[1]), "+f"(d[2]), "+f"(d[3]), "+f"(d[4]), "+f"(d[5]), "+f"(d[6]), "+f"(d[7]),
          "+f"(d[8]), "+f"(d[9]), "+f"(d[10]), "+f"(d[11]), "+f"(d[12]), "+f"(d[13]), "+f"(d[14]), "+f"(d[15]),
          "+f"(d[16]), "+f"(d[17]), "+f"(d[18]), "+f"(d[19]), "+f"(d[20]), "+f"(d[21]), "+f"(d[22]), "+f"(d[23]),
          "+f"(d[24]), "+f"(d[25]), "+f"(d[26]), "+f"(d[27]), "+f"(d[28]), "+f"(d[29]), "+f"(d[30]), "+f"(d[31]),
          "+f"(d[32]), "+f"(d[33]), "+f"(d[34]), "+f"(d[35]), "+f"(d[36]), "+f"(d[37]), "+f"(d[38]), "+f"(d[39]),
          "+f"(d[40]), "+f"(d[41]), "+f"(d[42]), "+f"(d[43]), "+f"(d[44]), "+f"(d[45]), "+f"(d[46]), "+f"(d[47]),
          "+f"(d[48]), "+f"(d[49]), "+f"(d[50]), "+f"(d[51]), "+f"(d[52]), "+f"(d[53]), "+f"(d[54]), "+f"(d[55]),
          "+f"(d[56]), "+f"(d[57]), "+f"(d[58]), "+f"(d[59]), "+f"(d[60]), "+f"(d[61]), "+f"(d[62]), "+f"(d[63]),
          "+f"(d[64]), "+f"(d[65]), "+f"(d[66]), "+f"(d[67]), "+f"(d[68]), "+f"(d[69]), "+f"(d[70]), "+f"(d[71]),
          "+f"(d[72]), "+f"(d[73]), "+f"(d[74]), "+f"(d[75]), "+f"(d[76]), "+f"(d[77]), "+f"(d[78]), "+f"(d[79]),
          "+f"(d[80]), "+f"(d[81]), "+f"(d[82]), "+f"(d[83]), "+f"(d[84]), "+f"(d[85]), "+f"(d[86]), "+f"(d[87]),
          "+f"(d[88]), "+f"(d[89]), "+f"(d[90]), "+f"(d[91]), "+f"(d[92]), "+f"(d[93]), "+f"(d[94]), "+f"(d[95]),
          "+f"(d[96]), "+f"(d[97]), "+f"(d[98]), "+f"(d[99]), "+f"(d[100]), "+f"(d[101]), "+f"(d[102]), "+f"(d[103]),
          "+f"(d[104]), "+f"(d[105]), "+f"(d[106]), "+f"(d[107]), "+f"(d[108]), "+f"(d[109]), "+f"(d[110]), "+f"(d[111]),
          "+f"(d[112]), "+f"(d[113]), "+f"(d[114]), "+f"(d[115]), "+f"(d[116]), "+f"(d[117]), "+f"(d[118]), "+f"(d[119])
        : "l"(descA), "l"(descB), "r"(scaleD));
}

__device__ __forceinline__ void wgmma_n192_ss_tb(float (&d)[96], uint64_t descA, uint64_t descB, int scaleD) {
    asm volatile("{\n.reg .pred p;\nsetp.ne.b32 p, %98, 0;\n"
        "wgmma.mma_async.sync.aligned.m64n192k16.f32.bf16.bf16 {"
        "%0, %1, %2, %3, %4, %5, %6, %7, %8, %9, %10, %11, %12, %13, %14, %15, "
        "%16, %17, %18, %19, %20, %21, %22, %23, %24, %25, %26, %27, %28, %29, %30, %31, "
        "%32, %33, %34, %35, %36, %37, %38, %39, %40, %41, %42, %43, %44, %45, %46, %47, "
        "%48, %49, %50, %51, %52, %53, %54, %55, %56, %57, %58, %59, %60, %61, %62, %63, "
        "%64, %65, %66, %67, %68, %69, %70, %71, %72, %73, %74, %75, %76, %77, %78, %79, "
        "%80, %81, %82, %83, %84, %85, %86, %87, %88, %89, %90, %91, %92, %93, %94, %95}, "
        "%96, %97, p, 1, 1, 0, 1;\n}\n"
        : "+f"(d[0]), "+f"(d[1]), "+f"(d[2]), "+f"(d[3]), "+f"(d[4]), "+f"(d[5]), "+f"(d[6]), "+f"(d[7]),
          "+f"(d[8]), "+f"(d[9]), "+f"(d[10]), "+f"(d[11]), "+f"(d[12]), "+f"(d[13]), "+f"(d[14]), "+f"(d[15]),
          "+f"(d[16]), "+f"(d[17]), "+f"(d[18]), "+f"(d[19]), "+f"(d[20]), "+f"(d[21]), "+f"(d[22]), "+f"(d[23]),
          "+f"(d[24]), "+f"(d[25]), "+f"(d[26]), "+f"(d[27]), "+f"(d[28]), "+f"(d[29]), "+f"(d[30]), "+f"(d[31]),
          "+f"(d[32]), "+f"(d[33]), "+f"(d[34]), "+f"(d[35]), "+f"(d[36]), "+f"(d[37]), "+f"(d[38]), "+f"(d[39]),
          "+f"(d[40]), "+f"(d[41]), "+f"(d[42]), "+f"(d[43]), "+f"(d[44]), "+f"(d[45]), "+f"(d[46]), "+f"(d[47]),
          "+f"(d[48]), "+f"(d[49]), "+f"(d[50]), "+f"(d[51]), "+f"(d[52]), "+f"(d[53]), "+f"(d[54]), "+f"(d[55]),
          "+f"(d[56]), "+f"(d[57]), "+f"(d[58]), "+f"(d[59]), "+f"(d[60]), "+f"(d[61]), "+f"(d[62]), "+f"(d[63]),
          "+f"(d[64]), "+f"(d[65]), "+f"(d[66]), "+f"(d[67]), "+f"(d[68]), "+f"(d[69]), "+f"(d[70]), "+f"(d[71]),
          "+f"(d[72]), "+f"(d[73]), "+f"(d[74]), "+f"(d[75]), "+f"(d[76]), "+f"(d[77]), "+f"(d[78]), "+f"(d[79]),
          "+f"(d[80]), "+f"(d[81]), "+f"(d[82]), "+f"(d[83]), "+f"(d[84]), "+f"(d[85]), "+f"(d[86]), "+f"(d[87]),
          "+f"(d[88]), "+f"(d[89]), "+f"(d[90]), "+f"(d[91]), "+f"(d[92]), "+f"(d[93]), "+f"(d[94]), "+f"(d[95])
        : "l"(descA), "l"(descB), "r"(scaleD));
}

__device__ __forceinline__ void wgmma_n160_ss_tb(float (&d)[80], uint64_t descA, uint64_t descB, int scaleD) {
    asm volatile("{\n.reg .pred p;\nsetp.ne.b32 p, %82, 0;\n"
        "wgmma.mma_async.sync.aligned.m64n160k16.f32.bf16.bf16 {"
        "%0, %1, %2, %3, %4, %5, %6, %7, %8, %9, %10, %11, %12, %13, %14, %15, "
        "%16, %17, %18, %19, %20, %21, %22, %23, %24, %25, %26, %27, %28, %29, %30, %31, "
        "%32, %33, %34, %35, %36, %37, %38, %39, %40, %41, %42, %43, %44, %45, %46, %47, "
        "%48, %49, %50, %51, %52, %53, %54, %55, %56, %57, %58, %59, %60, %61, %62, %63, "
        "%64, %65, %66, %67, %68, %69, %70, %71, %72, %73, %74, %75, %76, %77, %78, %79}, "
        "%80, %81, p, 1, 1, 0, 1;\n}\n"
        : "+f"(d[0]), "+f"(d[1]), "+f"(d[2]), "+f"(d[3]), "+f"(d[4]), "+f"(d[5]), "+f"(d[6]), "+f"(d[7]),
          "+f"(d[8]), "+f"(d[9]), "+f"(d[10]), "+f"(d[11]), "+f"(d[12]), "+f"(d[13]), "+f"(d[14]), "+f"(d[15]),
          "+f"(d[16]), "+f"(d[17]), "+f"(d[18]), "+f"(d[19]), "+f"(d[20]), "+f"(d[21]), "+f"(d[22]), "+f"(d[23]),
          "+f"(d[24]), "+f"(d[25]), "+f"(d[26]), "+f"(d[27]), "+f"(d[28]), "+f"(d[29]), "+f"(d[30]), "+f"(d[31]),
          "+f"(d[32]), "+f"(d[33]), "+f"(d[34]), "+f"(d[35]), "+f"(d[36]), "+f"(d[37]), "+f"(d[38]), "+f"(d[39]),
          "+f"(d[40]), "+f"(d[41]), "+f"(d[42]), "+f"(d[43]), "+f"(d[44]), "+f"(d[45]), "+f"(d[46]), "+f"(d[47]),
          "+f"(d[48]), "+f"(d[49]), "+f"(d[50]), "+f"(d[51]), "+f"(d[52]), "+f"(d[53]), "+f"(d[54]), "+f"(d[55]),
          "+f"(d[56]), "+f"(d[57]), "+f"(d[58]), "+f"(d[59]), "+f"(d[60]), "+f"(d[61]), "+f"(d[62]), "+f"(d[63]),
          "+f"(d[64]), "+f"(d[65]), "+f"(d[66]), "+f"(d[67]), "+f"(d[68]), "+f"(d[69]), "+f"(d[70]), "+f"(d[71]),
          "+f"(d[72]), "+f"(d[73]), "+f"(d[74]), "+f"(d[75]), "+f"(d[76]), "+f"(d[77]), "+f"(d[78]), "+f"(d[79])
        : "l"(descA), "l"(descB), "r"(scaleD));
}

__device__ __forceinline__ void wgmma_n64_rs(float (&d)[32], uint32_t a0, uint32_t a1, uint32_t a2, uint32_t a3, uint64_t descB, int scaleD) {
    asm volatile("{\n.reg .pred p;\nsetp.ne.b32 p, %37, 0;\n"
        "wgmma.mma_async.sync.aligned.m64n64k16.f32.bf16.bf16 {"
        "%0, %1, %2, %3, %4, %5, %6, %7, %8, %9, %10, %11, %12, %13, %14, %15, "
        "%16, %17, %18, %19, %20, %21, %22, %23, %24, %25, %26, %27, %28, %29, %30, %31}, "
        "{%32, %33, %34, %35}, %36, p, 1, 1, 0;\n}\n"
        : "+f"(d[0]), "+f"(d[1]), "+f"(d[2]), "+f"(d[3]), "+f"(d[4]), "+f"(d[5]), "+f"(d[6]), "+f"(d[7]),
          "+f"(d[8]), "+f"(d[9]), "+f"(d[10]), "+f"(d[11]), "+f"(d[12]), "+f"(d[13]), "+f"(d[14]), "+f"(d[15]),
          "+f"(d[16]), "+f"(d[17]), "+f"(d[18]), "+f"(d[19]), "+f"(d[20]), "+f"(d[21]), "+f"(d[22]), "+f"(d[23]),
          "+f"(d[24]), "+f"(d[25]), "+f"(d[26]), "+f"(d[27]), "+f"(d[28]), "+f"(d[29]), "+f"(d[30]), "+f"(d[31])
        : "r"(a0), "r"(a1), "r"(a2), "r"(a3), "l"(descB), "r"(scaleD));
}

__device__ __forceinline__ void wgmma_n64_rs_z(float (&d)[32], uint32_t a0, uint32_t a1, uint32_t a2, uint32_t a3, uint64_t descB) {
    asm volatile("{\n.reg .pred p;\nsetp.ne.b32 p, 0, 0;\n"
        "wgmma.mma_async.sync.aligned.m64n64k16.f32.bf16.bf16 {"
        "%0, %1, %2, %3, %4, %5, %6, %7, %8, %9, %10, %11, %12, %13, %14, %15, "
        "%16, %17, %18, %19, %20, %21, %22, %23, %24, %25, %26, %27, %28, %29, %30, %31}, "
        "{%32, %33, %34, %35}, %36, p, 1, 1, 0;\n}\n"
        : "=f"(d[0]), "=f"(d[1]), "=f"(d[2]), "=f"(d[3]), "=f"(d[4]), "=f"(d[5]), "=f"(d[6]), "=f"(d[7]),
          "=f"(d[8]), "=f"(d[9]), "=f"(d[10]), "=f"(d[11]), "=f"(d[12]), "=f"(d[13]), "=f"(d[14]), "=f"(d[15]),
          "=f"(d[16]), "=f"(d[17]), "=f"(d[18]), "=f"(d[19]), "=f"(d[20]), "=f"(d[21]), "=f"(d[22]), "=f"(d[23]),
          "=f"(d[24]), "=f"(d[25]), "=f"(d[26]), "=f"(d[27]), "=f"(d[28]), "=f"(d[29]), "=f"(d[30]), "=f"(d[31])
        : "r"(a0), "r"(a1), "r"(a2), "r"(a3), "l"(descB));
}

__device__ __forceinline__ void wgmma_n24_rs_tb(float (&d)[12], uint32_t a0, uint32_t a1, uint32_t a2, uint32_t a3, uint64_t descB, int scaleD) {
    asm volatile("{\n.reg .pred p;\nsetp.ne.b32 p, %17, 0;\n"
        "wgmma.mma_async.sync.aligned.m64n24k16.f32.bf16.bf16 {"
        "%0, %1, %2, %3, %4, %5, %6, %7, %8, %9, %10, %11}, "
        "{%12, %13, %14, %15}, %16, p, 1, 1, 1;\n}\n"
        : "+f"(d[0]), "+f"(d[1]), "+f"(d[2]), "+f"(d[3]), "+f"(d[4]), "+f"(d[5]), "+f"(d[6]), "+f"(d[7]),
          "+f"(d[8]), "+f"(d[9]), "+f"(d[10]), "+f"(d[11])
        : "r"(a0), "r"(a1), "r"(a2), "r"(a3), "l"(descB), "r"(scaleD));
}

__global__ void __launch_bounds__(256) k_ln(const __nv_bfloat16* __restrict__ x) {
    pdl_launch();
    const int lane = threadIdx.x & 31;
    const int row = blockIdx.x * 8 + (threadIdx.x >> 5);
    const uint2* src = reinterpret_cast<const uint2*>(x + (size_t)row * DM);
    uint2 v[5];
#pragma unroll
    for (int i = 0; i < 5; i++) v[i] = __ldg(src + lane + 32 * i);
    float f[20];
#pragma unroll
    for (int i = 0; i < 5; i++) {
        f[4 * i] = bf_lo(v[i].x); f[4 * i + 1] = bf_hi(v[i].x);
        f[4 * i + 2] = bf_lo(v[i].y); f[4 * i + 3] = bf_hi(v[i].y);
    }
    float s = 0.f;
#pragma unroll
    for (int i = 0; i < 20; i++) s += f[i];
#pragma unroll
    for (int o = 16; o; o >>= 1) s += __shfl_xor_sync(~0u, s, o);
    const float mu = s * (1.f / DM);
    float q = 0.f;
#pragma unroll
    for (int i = 0; i < 20; i++) { f[i] -= mu; q += f[i] * f[i]; }
#pragma unroll
    for (int o = 16; o; o >>= 1) q += __shfl_xor_sync(~0u, q, o);
    const float var = q * (1.f / DM);
    const float r1 = 1.f / sqrtf(var + LN_EPS);
    uint2* dst = reinterpret_cast<uint2*>(g_xn + (size_t)row * DM);
#pragma unroll
    for (int i = 0; i < 5; i++) {
        uint2 w;
        w.x = pack_bf16(f[4 * i] * r1, f[4 * i + 1] * r1);
        w.y = pack_bf16(f[4 * i + 2] * r1, f[4 * i + 3] * r1);
        dst[lane + 32 * i] = w;
    }
    if (lane == 0) g_r2[row] = 1.f / sqrtf(var * r1 * r1 + LN_EPS);
}

constexpr int G1_A_BYTES = 10 * 16384;
constexpr int G1_STAGES = 4;
constexpr int G1_B_STAGE = 16384;
constexpr int G1_BAR_OFF = G1_A_BYTES + G1_STAGES * G1_B_STAGE;
constexpr int G1_SMEM = G1_BAR_OFF + 256;

template <int N, bool FIRST, typename MMA>
__device__ __forceinline__ void g1_mainloop(float (&acc)[N / 2], uint32_t sA, uint32_t sB, uint32_t barA, uint32_t barFull,
                                            uint32_t barEmpty, int git0, int lane, uint32_t peer, MMA mma) {
#pragma unroll 1
    for (int it = 0; it < 20; it++) {
        const int git = git0 + it;
        const int s = git & (G1_STAGES - 1);
        if (FIRST && !(it & 1)) mbar_wait(barA + (it >> 1) * 8, 0);
        mbar_wait(barFull + s * 8, (git >> 2) & 1);
        wg_fence();
        const uint64_t dA = make_desc(sA + (it >> 1) * 16384 + (it & 1) * 64, 16, 1024, 1);
        const uint64_t dB = make_desc(sB + s * G1_B_STAGE, 4096, 1024, 1);
        mma(acc, dA, dB, it > 0);
        mma(acc, dA + 2, dB + 128, 1);
        wg_commit();
        if (it > 0) {
            wg_wait<1>();
            if (lane == 0) {
                const uint32_t e = barEmpty + ((git - 1) & (G1_STAGES - 1)) * 8;
                mbar_arrive(e);
                mbar_arrive_cluster(e, peer);
            }
        }
    }
    wg_wait<0>();
    if (lane == 0) {
        const uint32_t e = barEmpty + ((git0 + 19) & (G1_STAGES - 1)) * 8;
        mbar_arrive(e);
        mbar_arrive_cluster(e, peer);
    }
    fence_regs(acc);
}

__device__ __forceinline__ float gelu_tanh(float x) {
    const float u = x * (0.7978845608028654f + 0.035677408136300125f * x * x);
    float t;
    asm("tanh.approx.f32 %0, %1;" : "=f"(t) : "f"(u));
    const float h = 0.5f * x;
    return fmaf(h, t, h);
}

__global__ void __launch_bounds__(384, 1) __cluster_dims__(2, 1, 1)
k_gemm1(const __grid_constant__ CUtensorMap tmA, const __grid_constant__ CUtensorMap tmWqkv,
        const __grid_constant__ CUtensorMap tmW1, const __grid_constant__ CUtensorMap tmH,
        const __nv_bfloat16* __restrict__ b1) {
    extern __shared__ __align__(1024) uint8_t smem[];
    const uint32_t sbase = smem_u32(smem);
    const uint32_t sA = sbase, sB = sbase + G1_A_BYTES;
    const uint32_t barA = sbase + G1_BAR_OFF, barFull = barA + 80, barEmpty = barFull + 32;
    const int warp = __shfl_sync(~0u, threadIdx.x >> 5, 0), lane = threadIdx.x & 31;
    const uint32_t rank = blockIdx.x & 1;
    const int cl = blockIdx.x >> 1, cg = cl & 7, rb = (cl >> 3) * 2 + rank;

    pdl_launch();
    if (threadIdx.x == 0) {
        for (int i = 0; i < 10; i++) mbar_init(barA + i * 8, 1);
        for (int i = 0; i < G1_STAGES; i++) { mbar_init(barFull + i * 8, 1); mbar_init(barEmpty + i * 8, 16); }
        fence_barrier_init();
    }
    __syncthreads();
    cluster_sync();

    if (warp < 4) {
        reg_dealloc<40>();
        if (warp == 0) {
            if (elect_one()) { prefetch_map(&tmA); prefetch_map(&tmWqkv); prefetch_map(&tmW1); prefetch_map(&tmH); }
#pragma unroll 1
            for (int git = 0; git < 40; git++) {
                const int s = git & (G1_STAGES - 1);
                if (git == G1_STAGES) {
                    pdl_wait();
                    if (elect_one()) {
                        for (int kb = 0; kb < 10; kb++) {
                            mbar_expect_tx(barA + kb * 8, 16384);
                            tma_load(sA + kb * 16384, &tmA, kb * 64, rb * 128, barA + kb * 8);
                        }
                    }
                    __syncwarp();
                }
                if (git >= G1_STAGES) mbar_wait(barEmpty + s * 8, ((git >> 2) - 1) & 1);
                if (elect_one()) {
                    const uint32_t dst = sB + s * G1_B_STAGE, bar = barFull + s * 8;
                    if (git < 20) {
                        mbar_expect_tx(bar, 16384);
                        tma_load_mc(dst + (rank * 2) * 4096, &tmWqkv, cg * 240 + (rank * 2) * 64, git * 32, bar, 3);
                        tma_load_mc(dst + (rank * 2 + 1) * 4096, &tmWqkv, cg * 240 + (rank * 2 + 1) * 64, git * 32, bar, 3);
                    } else {
                        const int k0 = (git - 20) * 32;
                        mbar_expect_tx(bar, 12288);
                        if ((git & 1) == (int)rank) {
                            tma_load_mc(dst, &tmW1, cg * 192, k0, bar, 3);
                            tma_load_mc(dst + 4096, &tmW1, cg * 192 + 64, k0, bar, 3);
                        } else {
                            tma_load_mc(dst + 8192, &tmW1, cg * 192 + 128, k0, bar, 3);
                        }
                    }
                }
                __syncwarp();
            }
        }
    } else {
        reg_alloc<232>();
        const int wg = (warp >> 2) - 1, w4 = warp & 3;
        const int g = lane >> 2, c = lane & 3;
        const int row0 = rb * 128 + wg * 64 + w4 * 16 + g;
        const uint32_t sAw = sA + wg * 8192;
        const uint32_t peer = rank ^ 1;
        {
            float acc[120];
            g1_mainloop<240, true>(acc, sAw, sB, barA, barFull, barEmpty, 0, lane, peer,
                [](float (&d)[120], uint64_t a, uint64_t b, int sc) { wgmma_n240_ss_tb(d, a, b, sc); });
            const int rbk = row0 >> 3;
            const bool emu0 = (EMU_MASK >> (rbk & 15)) & 1, emu1 = (EMU_MASK >> ((rbk + 1) & 15)) & 1;
#pragma unroll
            for (int m = 0; m < 6; m++) {
                const int hs = cg * 12 + 2 * m, which = hs >> 5;
                const float* a = acc + 20 * m;
                float m0, m1;
                uint32_t pad0, pad1;
                if (which == 0) { m0 = m1 = QSCALE; pad0 = pad1 = 0x3F803F80u; }
                else if (which == 1) {
                    m0 = emu0 ? 2.f : 1.f; m1 = emu1 ? 2.f : 1.f;
                    pad0 = emu0 ? 0xBFFF4440u : 0u; pad1 = emu1 ? 0xBFFF4440u : 0u;
                } else { m0 = m1 = 1.f; pad0 = pad1 = 0x00003F80u; }
                uint8_t* pe = g_img + (size_t)hs * IMG_BYTES + rbk * 384 + g * 16 + c * 4;
                uint8_t* po = pe + IMG_BYTES;
                const uint32_t mid0 = pack_bf16(a[8] * m0, a[9] * m0), mid1 = pack_bf16(a[10] * m1, a[11] * m1);
                const bool low = c < 2;
                const uint32_t p0 = (c & 1) ? 0u : pad0, p1 = (c & 1) ? 0u : pad1;
                *(uint32_t*)(pe) = pack_bf16(a[0] * m0, a[1] * m0);
                *(uint32_t*)(pe + 128) = pack_bf16(a[4] * m0, a[5] * m0);
                *(uint32_t*)(pe + 256) = low ? mid0 : p0;
                *(uint32_t*)(pe + 384) = pack_bf16(a[2] * m1, a[3] * m1);
                *(uint32_t*)(pe + 512) = pack_bf16(a[6] * m1, a[7] * m1);
                *(uint32_t*)(pe + 640) = low ? mid1 : p1;
                *(uint32_t*)(po) = pack_bf16(a[12] * m0, a[13] * m0);
                *(uint32_t*)(po + 128) = pack_bf16(a[16] * m0, a[17] * m0);
                *(uint32_t*)(po + 256) = low ? p0 : mid0;
                *(uint32_t*)(po + 384) = pack_bf16(a[14] * m1, a[15] * m1);
                *(uint32_t*)(po + 512) = pack_bf16(a[18] * m1, a[19] * m1);
                *(uint32_t*)(po + 640) = low ? p1 : mid1;
                if (which < 2) {
                    const float u0 = a[8] * a[8] + a[9] * a[9], u1 = a[10] * a[10] + a[11] * a[11];
                    float e0 = a[0] * a[0] + a[1] * a[1] + a[4] * a[4] + a[5] * a[5] + (low ? u0 : 0.f);
                    float e1 = a[2] * a[2] + a[3] * a[3] + a[6] * a[6] + a[7] * a[7] + (low ? u1 : 0.f);
                    float o0 = a[12] * a[12] + a[13] * a[13] + a[16] * a[16] + a[17] * a[17] + (low ? 0.f : u0);
                    float o1 = a[14] * a[14] + a[15] * a[15] + a[18] * a[18] + a[19] * a[19] + (low ? 0.f : u1);
                    const bool b0 = c & 1, b1_ = c & 2;
                    float x0 = (b0 ? e1 : e0) + __shfl_xor_sync(~0u, b0 ? e0 : e1, 1);
                    float x1 = (b0 ? o1 : o0) + __shfl_xor_sync(~0u, b0 ? o0 : o1, 1);
                    float y = (b1_ ? x1 : x0) + __shfl_xor_sync(~0u, b1_ ? x0 : x1, 2);
                    if (which == 0) y *= QSCALE * QSCALE;
                    g_nrm[(hs + (c >> 1)) * SEQ + row0 + (c & 1) * 8] = y;
                }
            }
        }
        {
            float acc[96];
            g1_mainloop<192, false>(acc, sAw, sB, barA, barFull, barEmpty, 20, lane, peer,
                [](float (&d)[96], uint64_t a, uint64_t b, int sc) { wgmma_n192_ss_tb(d, a, b, sc); });
            const float r0 = g_r2[row0], r1 = g_r2[row0 + 8];
            const uint32_t* bias = reinterpret_cast<const uint32_t*>(b1 + cg * 192) + c;
            const int mrow = w4 * 16 + (lane & 15);
            const uint32_t st_row = sAw + mrow * 128;
#pragma unroll
            for (int j = 0; j < 24; j += 2) {
                const uint32_t bA = __ldg(bias + j * 4), bB = __ldg(bias + j * 4 + 4);
                const float* a = acc + j * 4;
                const uint32_t r00 = pack_bf16(gelu_tanh(fmaf(a[0], r0, bf_lo(bA))), gelu_tanh(fmaf(a[1], r0, bf_hi(bA))));
                const uint32_t r10 = pack_bf16(gelu_tanh(fmaf(a[2], r1, bf_lo(bA))), gelu_tanh(fmaf(a[3], r1, bf_hi(bA))));
                const uint32_t r01 = pack_bf16(gelu_tanh(fmaf(a[4], r0, bf_lo(bB))), gelu_tanh(fmaf(a[5], r0, bf_hi(bB))));
                const uint32_t r11 = pack_bf16(gelu_tanh(fmaf(a[6], r1, bf_lo(bB))), gelu_tanh(fmaf(a[7], r1, bf_hi(bB))));
                const int chunk = (j & 7) + (lane >> 4);
                stmatrix_x4(st_row + (j >> 3) * 16384 + ((chunk ^ (mrow & 7)) << 4), r00, r10, r01, r11);
            }
            fence_proxy_async();
            asm volatile("bar.sync %0, 128;" ::"r"(wg + 1) : "memory");
            if (w4 == 0 && elect_one()) {
#pragma unroll
                for (int b = 0; b < 3; b++) tma_store(&tmH, sAw + b * 16384, cg * 192 + b * 64, rb * 128 + wg * 64);
                bulk_commit();
                bulk_wait_all();
            }
        }
    }
    __syncthreads();
    cluster_sync();
}

constexpr int AT_BAR_OFF = 2 * IMG_BYTES;
constexpr int AT_SMEM = AT_BAR_OFF + 512;

__device__ __forceinline__ uint32_t bf2_fma(uint32_t a, uint32_t b, uint32_t c) {
    uint32_t r;
    asm("fma.rn.bf16x2 %0, %1, %2, %3;" : "=r"(r) : "r"(a), "r"(b), "r"(c));
    return r;
}
__device__ __forceinline__ uint32_t lop_and_or(uint32_t a, uint32_t m, uint32_t o) {
    uint32_t r;
    asm("lop3.b32 %0, %1, %2, %3, 0xEA;" : "=r"(r) : "r"(a), "r"(m), "r"(o));
    return r;
}
struct ExpConst { uint32_t mask, slope; };
__device__ __forceinline__ ExpConst make_exp_const() {
    ExpConst k;
    asm volatile("mov.b32 %0, 0x007F007F;" : "=r"(k.mask));
    asm volatile("mov.b32 %0, 0x3EF83EF8;" : "=r"(k.slope));
    return k;
}
__device__ __forceinline__ uint32_t exp2_pair_fma(float t0, float t1, const ExpConst& k) {
    const uint32_t L = __byte_perm(__float_as_uint(t0), __float_as_uint(t1), 0x6521);
    const uint32_t g = lop_and_or(L, k.mask, 0x3F803F80u);
    const uint32_t u = bf2_fma(g, k.slope, 0xBF37BF37u);
    const uint32_t e = bf2_fma(u, u, 0xBD71BD71u);
    return bf2_fma(L, e, L);
}
template <int SHIFT>
__device__ __forceinline__ void exp_tile(const float (&s)[32], uint32_t (&p)[16], const ExpConst& k) {
#pragma unroll
    for (int b = 0; b < 8; b++) {
        if ((EMU_MASK >> (b + SHIFT)) & 1) {
            p[2 * b] = exp2_pair_fma(s[4 * b], s[4 * b + 1], k);
            p[2 * b + 1] = exp2_pair_fma(s[4 * b + 2], s[4 * b + 3], k);
        } else {
            p[2 * b] = pack_bf16(ex2(s[4 * b]), ex2(s[4 * b + 1]));
            p[2 * b + 1] = pack_bf16(ex2(s[4 * b + 2]), ex2(s[4 * b + 3]));
        }
    }
}
struct QFrag { uint32_t q0, q1, q2, q3, q4, q5; };
__device__ __forceinline__ QFrag load_q(int h, int rbase, int g, int c) {
    const uint8_t* gq = g_img + (size_t)h * IMG_BYTES + (rbase >> 3) * 384 + g * 16 + c * 4;
    QFrag q;
    q.q0 = *(const uint32_t*)(gq); q.q1 = *(const uint32_t*)(gq + 384);
    q.q2 = *(const uint32_t*)(gq + 128); q.q3 = *(const uint32_t*)(gq + 512);
    q.q4 = *(const uint32_t*)(gq + 256); q.q5 = *(const uint32_t*)(gq + 640);
    return q;
}
__device__ __forceinline__ void qk_tile(float (&s)[32], const QFrag& q, uint64_t dK) {
    wg_fence();
    wgmma_n64_rs_z(s, q.q0, q.q1, q.q2, q.q3, dK);
    wgmma_n64_rs(s, q.q4, q.q5, 0u, 0u, dK + 16, 1);
    wg_commit();
}
__device__ __forceinline__ void pv_tile(float (&o)[12], const uint32_t (&p)[16], uint64_t dV) {
    wg_fence();
#pragma unroll
    for (int ks = 0; ks < 4; ks++)
        wgmma_n24_rs_tb(o, p[4 * ks], p[4 * ks + 1], p[4 * ks + 2], p[4 * ks + 3], dV + ks * 48, 1);
    wg_commit();
}
__device__ __forceinline__ void store_o(const float (&o)[12], int h, int rbase, int lane) {
    const int g = lane >> 2, c = lane & 3;
    const bool odd = h & 1;
    const int lsrc = (lane & ~3) | (odd ? 0 : 2);
    const float i0 = 1.f / __shfl_sync(~0u, o[8], lsrc), i1 = 1.f / __shfl_sync(~0u, o[10], lsrc);
    __nv_bfloat16* dst = g_o + (size_t)(rbase + g) * DM + h * 20;
    const int d0 = (odd ? 4 : 0) + 2 * c, d1 = d0 + 8, d2 = odd ? 2 * c - 4 : 16 + 2 * c;
    *(uint32_t*)(dst + d0) = pack_bf16(o[0] * i0, o[1] * i0);
    *(uint32_t*)(dst + d1) = pack_bf16(o[4] * i0, o[5] * i0);
    *(uint32_t*)(dst + 8 * DM + d0) = pack_bf16(o[2] * i1, o[3] * i1);
    *(uint32_t*)(dst + 8 * DM + d1) = pack_bf16(o[6] * i1, o[7] * i1);
    if (odd ? (c >= 2) : (c < 2)) {
        *(uint32_t*)(dst + d2) = pack_bf16(o[8] * i0, o[9] * i0);
        *(uint32_t*)(dst + 8 * DM + d2) = pack_bf16(o[10] * i1, o[11] * i1);
    }
}

__device__ __forceinline__ void attn_rows_maxshift(uint32_t sK, uint32_t bar, int h, int rbase) {
    const int lane = threadIdx.x & 31, g = lane >> 2, c = lane & 3;
    QFrag q = load_q(h, rbase, g, c);
    if (c == ((h & 1) ? 0 : 2)) { q.q4 = 0u; q.q5 = 0u; }
    const uint64_t dK0 = make_desc(sK, 128, 384, 0), dV0 = make_desc(sK + IMG_BYTES, 384, 128, 0);
    float o[12], s[32];
    uint32_t p[16];
#pragma unroll
    for (int i = 0; i < 12; i++) o[i] = 0.f;
    float m0 = -3.0e38f, m1 = -3.0e38f;
    mbar_wait(bar + 128, 0);
#pragma unroll 1
    for (int t = 0; t < 32; t++) {
        mbar_wait(bar + (t >> 1) * 8, 0);
        if (t) mbar_wait(bar + ((t - 1) >> 1) * 8, 0);
        qk_tile(s, q, dK0 + t * 192);
        wg_wait<0>();
        fence_regs(s);
        const uint32_t mask = EMU_MASK >> ((t & 1) * 8);
        float n0 = m0, n1 = m1;
#pragma unroll
        for (int b = 0; b < 8; b++) {
            const float f = ((mask >> b) & 1) ? 0.5f : 1.f;
            s[4 * b] *= f; s[4 * b + 1] *= f; s[4 * b + 2] *= f; s[4 * b + 3] *= f;
            n0 = fmaxf(n0, fmaxf(s[4 * b], s[4 * b + 1]));
            n1 = fmaxf(n1, fmaxf(s[4 * b + 2], s[4 * b + 3]));
        }
        n0 = fmaxf(n0, __shfl_xor_sync(~0u, n0, 1)); n0 = fmaxf(n0, __shfl_xor_sync(~0u, n0, 2));
        n1 = fmaxf(n1, __shfl_xor_sync(~0u, n1, 1)); n1 = fmaxf(n1, __shfl_xor_sync(~0u, n1, 2));
        const float c0 = ex2(m0 - n0), c1 = ex2(m1 - n1);
        m0 = n0; m1 = n1;
#pragma unroll
        for (int b = 0; b < 3; b++) { o[4 * b] *= c0; o[4 * b + 1] *= c0; o[4 * b + 2] *= c1; o[4 * b + 3] *= c1; }
#pragma unroll
        for (int b = 0; b < 8; b++) {
            p[2 * b] = pack_bf16(ex2(s[4 * b] - m0), ex2(s[4 * b + 1] - m0));
            p[2 * b + 1] = pack_bf16(ex2(s[4 * b + 2] - m1), ex2(s[4 * b + 3] - m1));
        }
        pv_tile(o, p, dV0 + t * 192);
        wg_wait<0>();
        fence_regs(o);
    }
    store_o(o, h, rbase, lane);
}

__global__ void __launch_bounds__(512, 1) k_attn() {
    extern __shared__ __align__(1024) uint8_t smem[];
    const uint32_t sK = smem_u32(smem), sV = sK + IMG_BYTES;
    const uint32_t bar = sK + AT_BAR_OFF;
    float* red = reinterpret_cast<float*>(smem + AT_BAR_OFF + 256);
    const int warp = __shfl_sync(~0u, threadIdx.x >> 5, 0), lane = threadIdx.x & 31;
    const int h = blockIdx.x >> 2, qb = blockIdx.x & 3;
    const int wg = warp >> 2, w4 = warp & 3;

    pdl_launch();
    if (threadIdx.x == 0) {
        for (int i = 0; i < 17; i++) mbar_init(bar + i * 8, 1);
        fence_barrier_init();
    }
    __syncthreads();
    pdl_wait();
    if (warp == 0 && elect_one()) {
        const uint8_t* gK = g_img + (size_t)(32 + h) * IMG_BYTES;
        const uint8_t* gV = g_img + (size_t)(64 + h) * IMG_BYTES;
        mbar_expect_tx(bar + 128, 6144);
        bulk_load(sK, gK, 6144, bar + 128);
        for (int i = 0; i < 16; i++) {
            mbar_expect_tx(bar + i * 8, i < 15 ? 12288 : 6144);
            bulk_load(sV + i * 6144, gV + i * 6144, 6144, bar + i * 8);
            if (i < 15) bulk_load(sK + (i + 1) * 6144, gK + (i + 1) * 6144, 6144, bar + i * 8);
        }
    }
    float kmax = 0.f, qmax = g_nrm[h * SEQ + qb * 512 + threadIdx.x];
#pragma unroll
    for (int i = 0; i < 4; i++) kmax = fmaxf(kmax, g_nrm[(32 + h) * SEQ + i * 512 + threadIdx.x]);
#pragma unroll
    for (int o = 16; o; o >>= 1) {
        kmax = fmaxf(kmax, __shfl_xor_sync(~0u, kmax, o));
        qmax = fmaxf(qmax, __shfl_xor_sync(~0u, qmax, o));
    }
    if (lane == 0) { red[warp] = kmax; red[16 + warp] = qmax; }
    __syncthreads();
    kmax = red[lane & 15]; qmax = red[16 + (lane & 15)];
#pragma unroll
    for (int o = 8; o; o >>= 1) {
        kmax = fmaxf(kmax, __shfl_xor_sync(~0u, kmax, o));
        qmax = fmaxf(qmax, __shfl_xor_sync(~0u, qmax, o));
    }
    const bool safe = __all_sync(~0u, kmax * qmax * 1.05f <= SAFE_BOUND * SAFE_BOUND);
    if (!safe) {
#pragma unroll 1
        for (int pass = 0; pass < 2; pass++) attn_rows_maxshift(sK, bar, h, qb * 512 + pass * 256 + wg * 64 + w4 * 16);
        return;
    }
    const ExpConst kc = make_exp_const();
    const uint64_t dK0 = make_desc(sK, 128, 384, 0), dV0 = make_desc(sV, 384, 128, 0);
#pragma unroll 1
    for (int pass = 0; pass < 2; pass++) {
        const int rbase = qb * 512 + pass * 256 + wg * 64 + w4 * 16;
        const QFrag q = load_q(h, rbase, lane >> 2, lane & 3);
        float o[12], sa[32], sb[32];
        uint32_t p[16];
#pragma unroll
        for (int i = 0; i < 12; i++) o[i] = 0.f;
        fence_regs(o);
        mbar_wait(bar + 128, 0);
        qk_tile(sa, q, dK0);
        wg_wait<0>();
        fence_regs(sa);
        uint64_t dK = dK0, dV = dV0;
        uint32_t bj = bar;
#pragma unroll 1
        for (int j = 0; j < 16; j++) {
            mbar_wait(bj, 0);
            qk_tile(sb, q, dK + 192);
            wg_wait<1>();
            exp_tile<0>(sa, p, kc);
            pv_tile(o, p, dV);
            wg_wait<1>();
            fence_regs(sb);
            mbar_wait(bj, 0);
            qk_tile(sa, q, dK + 384);
            wg_wait<1>();
            exp_tile<8>(sb, p, kc);
            pv_tile(o, p, dV + 192);
            wg_wait<1>();
            fence_regs(sa);
            dK += 384; dV += 384; bj += 8;
        }
        wg_wait<0>();
        fence_regs(o);
        store_o(o, h, rbase, lane);
    }
}

constexpr int G2_STAGES = 8;
constexpr int G2_STAGE = 8192 + 20480;
constexpr int G2_BAR_OFF = G2_STAGES * G2_STAGE;
constexpr int G2_SMEM = G2_BAR_OFF + 256;

__global__ void __launch_bounds__(160, 1) __cluster_dims__(2, 1, 1)
k_gemm2(const __grid_constant__ CUtensorMap tmO, const __grid_constant__ CUtensorMap tmH,
        const __grid_constant__ CUtensorMap tmWo, const __grid_constant__ CUtensorMap tmW2,
        const __nv_bfloat16* __restrict__ x, const __nv_bfloat16* __restrict__ b2, __nv_bfloat16* __restrict__ out) {
    extern __shared__ __align__(1024) uint8_t smem[];
    const uint32_t sbase = smem_u32(smem);
    const uint32_t barFull = sbase + G2_BAR_OFF, barEmpty = barFull + 64;
    const int warp = __shfl_sync(~0u, threadIdx.x >> 5, 0), lane = threadIdx.x & 31;
    const uint32_t rank = blockIdx.x & 1;
    const int cl = blockIdx.x >> 1, ct = cl & 3, rt = (cl >> 2) * 2 + rank;

    pdl_launch();
    if (threadIdx.x == 0) {
        for (int i = 0; i < G2_STAGES; i++) { mbar_init(barFull + i * 8, 1); mbar_init(barEmpty + i * 8, 8); }
        fence_barrier_init();
    }
    __syncthreads();
    cluster_sync();

    if (warp == 4) {
        if (elect_one()) { prefetch_map(&tmO); prefetch_map(&tmH); prefetch_map(&tmWo); prefetch_map(&tmW2); }
        pdl_wait();
#pragma unroll 1
        for (int kb = 0; kb < 34; kb++) {
            const int s = kb & (G2_STAGES - 1);
            if (kb >= G2_STAGES) mbar_wait(barEmpty + s * 8, ((kb >> 3) - 1) & 1);
            if (elect_one()) {
                const uint32_t dst = sbase + s * G2_STAGE, bar = barFull + s * 8;
                const CUtensorMap* mA = kb < 24 ? &tmH : &tmO;
                const CUtensorMap* mB = kb < 24 ? &tmW2 : &tmWo;
                const int k0 = (kb < 24 ? kb : kb - 24) * 64;
                mbar_expect_tx(bar, G2_STAGE);
                tma_load(dst, mA, k0, rt * 64, bar);
                const int first = ((kb & 1) == (int)rank) ? 0 : 3, last = ((kb & 1) == (int)rank) ? 3 : 5;
                for (int b = first; b < last; b++)
                    tma_load_mc(dst + 8192 + b * 4096, mB, ct * 160 + b * 32, k0, bar, 3);
            }
            __syncwarp();
        }
    } else {
        const int g = lane >> 2, c = lane & 3;
        const uint32_t peer = rank ^ 1;
        float acc[80];
#pragma unroll 1
        for (int kb = 0; kb < 34; kb++) {
            const int s = kb & (G2_STAGES - 1);
            mbar_wait(barFull + s * 8, (kb >> 3) & 1);
            wg_fence();
            const uint64_t dA = make_desc(sbase + s * G2_STAGE, 16, 1024, 1);
            const uint64_t dB = make_desc(sbase + s * G2_STAGE + 8192, 4096, 512, 2);
#pragma unroll
            for (int kk = 0; kk < 4; kk++) wgmma_n160_ss_tb(acc, dA + kk * 2, dB + kk * 64, (kb | kk) != 0);
            wg_commit();
            if (kb > 0) {
                wg_wait<1>();
                if (lane == 0) {
                    const uint32_t e = barEmpty + ((kb - 1) & (G2_STAGES - 1)) * 8;
                    mbar_arrive(e);
                    mbar_arrive_cluster(e, peer);
                }
            }
        }
        wg_wait<0>();
        fence_regs(acc);
        pdl_wait();
        const int row = rt * 64 + warp * 16 + g;
        const size_t off0 = (size_t)row * DM + ct * 160 + 2 * c, off1 = off0 + 8 * DM;
        const uint32_t* bias = reinterpret_cast<const uint32_t*>(b2 + ct * 160) + c;
#pragma unroll
        for (int j = 0; j < 20; j++) {
            const uint32_t bb = __ldg(bias + j * 4);
            const uint32_t x0 = __ldg((const uint32_t*)(x + off0 + j * 8)), x1 = __ldg((const uint32_t*)(x + off1 + j * 8));
            *(uint32_t*)(out + off0 + j * 8) =
                pack_bf16(acc[4 * j] + bf_lo(bb) + bf_lo(x0), acc[4 * j + 1] + bf_hi(bb) + bf_hi(x0));
            *(uint32_t*)(out + off1 + j * 8) =
                pack_bf16(acc[4 * j + 2] + bf_lo(bb) + bf_lo(x1), acc[4 * j + 3] + bf_hi(bb) + bf_hi(x1));
        }
    }
    __syncthreads();
    cluster_sync();
}

typedef CUresult (*EncodeTiledFn)(CUtensorMap*, CUtensorMapDataType, cuuint32_t, void*, const cuuint64_t*,
                                  const cuuint64_t*, const cuuint32_t*, const cuuint32_t*, CUtensorMapInterleave,
                                  CUtensorMapSwizzle, CUtensorMapL2promotion, CUtensorMapFloatOOBfill);

CUtensorMap make_map(EncodeTiledFn enc, const void* ptr, int rows, int cols, int box_rows, int box_cols,
                     CUtensorMapSwizzle swz) {
    CUtensorMap m;
    cuuint64_t gd[2] = {(cuuint64_t)cols, (cuuint64_t)rows};
    cuuint64_t gs[1] = {(cuuint64_t)cols * 2};
    cuuint32_t bd[2] = {(cuuint32_t)box_cols, (cuuint32_t)box_rows};
    cuuint32_t es[2] = {1, 1};
    enc(&m, CU_TENSOR_MAP_DATA_TYPE_BFLOAT16, 2, const_cast<void*>(ptr), gd, gs, bd, es, CU_TENSOR_MAP_INTERLEAVE_NONE,
        swz, CU_TENSOR_MAP_L2_PROMOTION_L2_128B, CU_TENSOR_MAP_FLOAT_OOB_FILL_NONE);
    return m;
}

template <typename... KArgs, typename... Args>
void launch(void (*kern)(KArgs...), int grid, int block, int smem, int cluster, bool pdl, Args... args) {
    cudaLaunchConfig_t cfg = {};
    cfg.gridDim = dim3(grid);
    cfg.blockDim = dim3(block);
    cfg.dynamicSmemBytes = smem;
    cfg.stream = cudaStreamPerThread;
    cudaLaunchAttribute at[1];
    at[0].id = cudaLaunchAttributeProgrammaticStreamSerialization;
    at[0].val.programmaticStreamSerializationAllowed = 1;
    cfg.attrs = at;
    cfg.numAttrs = pdl ? 1 : 0;
    (void)cluster;
    cudaLaunchKernelEx(&cfg, kern, KArgs(args)...);
}

}

extern "C" void kernel_launch(void* const* d_in, const int* in_sizes, int n_in, void* d_out, int out_size) {
    (void)in_sizes; (void)n_in; (void)out_size;
    const __nv_bfloat16* x = (const __nv_bfloat16*)d_in[0];
    const __nv_bfloat16* wqkv = (const __nv_bfloat16*)d_in[1];
    const __nv_bfloat16* wo = (const __nv_bfloat16*)d_in[2];
    const __nv_bfloat16* w1 = (const __nv_bfloat16*)d_in[4];
    const __nv_bfloat16* b1 = (const __nv_bfloat16*)d_in[5];
    const __nv_bfloat16* w2 = (const __nv_bfloat16*)d_in[6];
    const __nv_bfloat16* b2 = (const __nv_bfloat16*)d_in[7];
    __nv_bfloat16* out = (__nv_bfloat16*)d_out;

    static EncodeTiledFn enc = nullptr;
    static void *p_xn, *p_h, *p_o;
    if (!enc) {
        cudaDriverEntryPointQueryResult qr;
        cudaGetDriverEntryPoint("cuTensorMapEncodeTiled", (void**)&enc, cudaEnableDefault, &qr);
        cudaGetSymbolAddress(&p_xn, g_xn);
        cudaGetSymbolAddress(&p_h, g_h);
        cudaGetSymbolAddress(&p_o, g_o);
        cudaFuncSetAttribute(k_gemm1, cudaFuncAttributeMaxDynamicSharedMemorySize, G1_SMEM);
        cudaFuncSetAttribute(k_attn, cudaFuncAttributeMaxDynamicSharedMemorySize, AT_SMEM);
        cudaFuncSetAttribute(k_gemm2, cudaFuncAttributeMaxDynamicSharedMemorySize, G2_SMEM);
    }
    const CUtensorMap tmXn = make_map(enc, p_xn, SEQ, DM, 128, 64, CU_TENSOR_MAP_SWIZZLE_128B);
    const CUtensorMap tmWqkv = make_map(enc, wqkv, DM, 3 * DM, 32, 64, CU_TENSOR_MAP_SWIZZLE_128B);
    const CUtensorMap tmW1 = make_map(enc, w1, DM, FF, 32, 64, CU_TENSOR_MAP_SWIZZLE_128B);
    const CUtensorMap tmH = make_map(enc, p_h, SEQ, FF, 64, 64, CU_TENSOR_MAP_SWIZZLE_128B);
    const CUtensorMap tmO = make_map(enc, p_o, SEQ, DM, 64, 64, CU_TENSOR_MAP_SWIZZLE_128B);
    const CUtensorMap tmWo = make_map(enc, wo, DM, DM, 64, 32, CU_TENSOR_MAP_SWIZZLE_64B);
    const CUtensorMap tmW2 = make_map(enc, w2, FF, DM, 64, 32, CU_TENSOR_MAP_SWIZZLE_64B);

    launch(k_ln, SEQ / 8, 256, 0, 1, false, x);
    launch(k_gemm1, 128, 384, G1_SMEM, 2, true, tmXn, tmWqkv, tmW1, tmH, b1);
    launch(k_attn, 128, 512, AT_SMEM, 1, true);
    launch(k_gemm2, 128, 160, G2_SMEM, 2, true, tmO, tmH, tmWo, tmW2, x, b2, out);
}
```

```cpp
#include <cuda_runtime.h>
#include <cuda_bf16.h>
#include <cuda.h>
#include <stdint.h>

namespace {

constexpr int SEQ = 2048, DM = 640, FF = 1536;
constexpr float LN_EPS = 1e-5f;

constexpr int IMG_BYTES = 256 * 384;
constexpr uint32_t EMU_MASK = 0xD5D5u;
constexpr float SAFE_BOUND = 80.0f;
constexpr float QSCALE = 0.22360679774997896f * 1.4426950408889634f;

__device__ __align__(1024) __nv_bfloat16 g_xn[SEQ * DM];
__device__ float g_r2[SEQ];
__device__ __align__(1024) uint8_t g_img[96 * IMG_BYTES + 1024];
__device__ float g_nrm[64 * SEQ];
__device__ __align__(1024) __nv_bfloat16 g_h[SEQ * FF];
__device__ __align__(1024) __nv_bfloat16 g_o[SEQ * DM];

#define TL(kern, slot) do { } while (0)

__device__ __forceinline__ uint32_t smem_u32(const void* p) { return (uint32_t)__cvta_generic_to_shared(p); }
__device__ __forceinline__ void mbar_init(uint32_t bar, int cnt) {
    asm volatile("mbarrier.init.shared::cta.b64 [%0], %1;" ::"r"(bar), "r"(cnt));
}
__device__ __forceinline__ void mbar_expect_tx(uint32_t bar, uint32_t bytes) {
    asm volatile("mbarrier.arrive.expect_tx.shared::cta.b64 _, [%0], %1;" ::"r"(bar), "r"(bytes) : "memory");
}
__device__ __forceinline__ void mbar_wait(uint32_t bar, uint32_t parity) {
    asm volatile("{\n.reg .pred p;\n.reg .u32 n;\nmov.u32 n, 0;\n"
                 "WAIT_LOOP:\nmbarrier.try_wait.parity.shared::cta.b64 p, [%0], %1;\n@p bra WAIT_DONE;\n"
                 "add.u32 n, n, 1;\nsetp.lt.u32 p, n, 4194304;\n@p bra WAIT_LOOP;\nWAIT_DONE:\n}"
                 ::"r"(bar), "r"(parity) : "memory");
}
__device__ __forceinline__ void mbar_arrive(uint32_t bar) {
    asm volatile("mbarrier.arrive.shared::cta.b64 _, [%0];" ::"r"(bar) : "memory");
}
__device__ __forceinline__ void mbar_arrive_cluster(uint32_t bar, uint32_t cta) {
    asm volatile("{\n.reg .b32 ra;\nmapa.shared::cluster.u32 ra, %0, %1;\n"
                 "mbarrier.arrive.shared::cluster.b64 _, [ra];\n}" ::"r"(bar), "r"(cta) : "memory");
}
__device__ __forceinline__ void fence_barrier_init() { asm volatile("fence.mbarrier_init.release.cluster;" ::: "memory"); }
__device__ __forceinline__ void fence_proxy_async() { asm volatile("fence.proxy.async.shared::cta;" ::: "memory"); }
__device__ __forceinline__ void cluster_sync() {
    asm volatile("barrier.cluster.arrive.release.aligned;\nbarrier.cluster.wait.acquire.aligned;" ::: "memory");
}
__device__ __forceinline__ bool elect_one() {
    uint32_t pred;
    asm volatile("{\n.reg .pred p;\nelect.sync _|p, 0xFFFFFFFF;\nselp.b32 %0, 1, 0, p;\n}" : "=r"(pred));
    return pred != 0;
}
__device__ __forceinline__ void pdl_launch() { asm volatile("griddepcontrol.launch_dependents;" ::: "memory"); }
__device__ __forceinline__ void pdl_wait() { asm volatile("griddepcontrol.wait;" ::: "memory"); }
__device__ __forceinline__ void prefetch_map(const CUtensorMap* m) {
    asm volatile("prefetch.tensormap [%0];" ::"l"(m) : "memory");
}
__device__ __forceinline__ void tma_load(uint32_t dst, const CUtensorMap* m, int c0, int c1, uint32_t bar) {
    asm volatile("cp.async.bulk.tensor.2d.shared::cluster.global.mbarrier::complete_tx::bytes [%0], [%1, {%3, %4}], [%2];"
                 ::"r"(dst), "l"(m), "r"(bar), "r"(c0), "r"(c1) : "memory");
}
__device__ __forceinline__ void tma_load_mc(uint32_t dst, const CUtensorMap* m, int c0, int c1, uint32_t bar, uint16_t mask) {
    asm volatile("cp.async.bulk.tensor.2d.shared::cluster.global.mbarrier::complete_tx::bytes.multicast::cluster"
                 " [%0], [%1, {%3, %4}], [%2], %5;"
                 ::"r"(dst), "l"(m), "r"(bar), "r"(c0), "r"(c1), "h"(mask) : "memory");
}
__device__ __forceinline__ void tma_store(const CUtensorMap* m, uint32_t src, int c0, int c1) {
    asm volatile("cp.async.bulk.tensor.2d.global.shared::cta.bulk_group [%0, {%2, %3}], [%1];"
                 ::"l"(m), "r"(src), "r"(c0), "r"(c1) : "memory");
}
__device__ __forceinline__ void bulk_commit() { asm volatile("cp.async.bulk.commit_group;" ::: "memory"); }
__device__ __forceinline__ void bulk_wait_all() { asm volatile("cp.async.bulk.wait_group 0;" ::: "memory"); }
__device__ __forceinline__ void bulk_load(uint32_t dst, const void* src, uint32_t bytes, uint32_t bar) {
    asm volatile("cp.async.bulk.shared::cluster.global.mbarrier::complete_tx::bytes [%0], [%1], %2, [%3];"
                 ::"r"(dst), "l"(src), "r"(bytes), "r"(bar) : "memory");
}
__device__ __forceinline__ void wg_fence() { asm volatile("wgmma.fence.sync.aligned;" ::: "memory"); }
__device__ __forceinline__ void wg_commit() { asm volatile("wgmma.commit_group.sync.aligned;" ::: "memory"); }
template <int N> __device__ __forceinline__ void wg_wait() {
    asm volatile("wgmma.wait_group.sync.aligned %0;" ::"n"(N) : "memory");
}
template <int N> __device__ __forceinline__ void reg_alloc() { asm volatile("setmaxnreg.inc.sync.aligned.u32 %0;" ::"n"(N)); }
template <int N> __device__ __forceinline__ void reg_dealloc() { asm volatile("setmaxnreg.dec.sync.aligned.u32 %0;" ::"n"(N)); }
template <int N> __device__ __forceinline__ void fence_regs(float (&d)[N]) {
#pragma unroll
    for (int i = 0; i < N; i++) asm volatile("" : "+f"(d[i])::"memory");
}
__device__ __forceinline__ uint64_t make_desc(uint32_t addr, uint32_t lbo, uint32_t sbo, uint32_t swz) {
    return (uint64_t)((addr & 0x3FFFF) >> 4) | ((uint64_t)(lbo >> 4) << 16) | ((uint64_t)(sbo >> 4) << 32) |
           ((uint64_t)swz << 62);
}
__device__ __forceinline__ uint32_t pack_bf16(float lo, float hi) {
    uint32_t r;
    asm("cvt.rn.bf16x2.f32 %0, %1, %2;" : "=r"(r) : "f"(hi), "f"(lo));
    return r;
}
__device__ __forceinline__ float ex2(float x) {
    float r;
    asm("ex2.approx.ftz.f32 %0, %1;" : "=f"(r) : "f"(x));
    return r;
}
__device__ __forceinline__ float bf_lo(uint32_t v) { return __uint_as_float(v << 16); }
__device__ __forceinline__ float bf_hi(uint32_t v) { return __uint_as_float(v & 0xFFFF0000u); }
__device__ __forceinline__ void stmatrix_x4(uint32_t addr, uint32_t r0, uint32_t r1, uint32_t r2, uint32_t r3) {
    asm volatile("stmatrix.sync.aligned.m8n8.x4.shared.b16 [%0], {%1, %2, %3, %4};"
                 ::"r"(addr), "r"(r0), "r"(r1), "r"(r2), "r"(r3) : "memory");
}

__device__ __forceinline__ void wgmma_n240_ss_tb(float (&d)[120], uint64_t descA, uint64_t descB, int scaleD) {
    asm volatile("{\n.reg .pred p;\nsetp.ne.b32 p, %122, 0;\n"
        "wgmma.mma_async.sync.aligned.m64n240k16.f32.bf16.bf16 {"
        "%0, %1, %2, %3, %4, %5, %6, %7, %8, %9, %10, %11, %12, %13, %14, %15, "
        "%16, %17, %18, %19, %20, %21, %22, %23, %24, %25, %26, %27, %28, %29, %30, %31, "
        "%32, %33, %34, %35, %36, %37, %38, %39, %40, %41, %42, %43, %44, %45, %46, %47, "
        "%48, %49, %50, %51, %52, %53, %54, %55, %56, %57, %58, %59, %60, %61, %62, %63, "
        "%64, %65, %66, %67, %68, %69, %70, %71, %72, %73, %74, %75, %76, %77, %78, %79, "
        "%80, %81, %82, %83, %84, %85, %86, %87, %88, %89, %90, %91, %92, %93, %94, %95, "
        "%96, %97, %98, %99, %100, %101, %102, %103, %104, %105, %106, %107, %108, %109, %110, %111, "
        "%112, %113, %114, %115, %116, %117, %118, %119}, "
        "%120, %121, p, 1, 1, 0, 1;\n}\n"
        : "+f"(d[0]), "+f"(d[1]), "+f"(d[2]), "+f"(d[3]), "+f"(d[4]), "+f"(d[5]), "+f"(d[6]), "+f"(d[7]),
          "+f"(d[8]), "+f"(d[9]), "+f"(d[10]), "+f"(d[11]), "+f"(d[12]), "+f"(d[13]), "+f"(d[14]), "+f"(d[15]),
          "+f"(d[16]), "+f"(d[17]), "+f"(d[18]), "+f"(d[19]), "+f"(d[20]), "+f"(d[21]), "+f"(d[22]), "+f"(d[23]),
          "+f"(d[24]), "+f"(d[25]), "+f"(d[26]), "+f"(d[27]), "+f"(d[28]), "+f"(d[29]), "+f"(d[30]), "+f"(d[31]),
          "+f"(d[32]), "+f"(d[33]), "+f"(d[34]), "+f"(d[35]), "+f"(d[36]), "+f"(d[37]), "+f"(d[38]), "+f"(d[39]),
          "+f"(d[40]), "+f"(d[41]), "+f"(d[42]), "+f"(d[43]), "+f"(d[44]), "+f"(d[45]), "+f"(d[46]), "+f"(d[47]),
          "+f"(d[48]), "+f"(d[49]), "+f"(d[50]), "+f"(d[51]), "+f"(d[52]), "+f"(d[53]), "+f"(d[54]), "+f"(d[55]),
          "+f"(d[56]), "+f"(d[57]), "+f"(d[58]), "+f"(d[59]), "+f"(d[60]), "+f"(d[61]), "+f"(d[62]), "+f"(d[63]),
          "+f"(d[64]), "+f"(d[65]), "+f"(d[66]), "+f"(d[67]), "+f"(d[68]), "+f"(d[69]), "+f"(d[70]), "+f"(d[71]),
          "+f"(d[72]), "+f"(d[73]), "+f"(d[74]), "+f"(d[75]), "+f"(d[76]), "+f"(d[77]), "+f"(d[78]), "+f"(d[79]),
          "+f"(d[80]), "+f"(d[81]), "+f"(d[82]), "+f"(d[83]), "+f"(d[84]), "+f"(d[85]), "+f"(d[86]), "+f"(d[87]),
          "+f"(d[88]), "+f"(d[89]), "+f"(d[90]), "+f"(d[91]), "+f"(d[92]), "+f"(d[93]), "+f"(d[94]), "+f"(d[95]),
          "+f"(d[96]), "+f"(d[97]), "+f"(d[98]), "+f"(d[99]), "+f"(d[100]), "+f"(d[101]), "+f"(d[102]), "+f"(d[103]),
          "+f"(d[104]), "+f"(d[105]), "+f"(d[106]), "+f"(d[107]), "+f"(d[108]), "+f"(d[109]), "+f"(d[110]), "+f"(d[111]),
          "+f"(d[112]), "+f"(d[113]), "+f"(d[114]), "+f"(d[115]), "+f"(d[116]), "+f"(d[117]), "+f"(d[118]), "+f"(d[119])
        : "l"(descA), "l"(descB), "r"(scaleD));
}

__device__ __forceinline__ void wgmma_n192_ss_tb(float (&d)[96], uint64_t descA, uint64_t descB, int scaleD) {
    asm volatile("{\n.reg .pred p;\nsetp.ne.b32 p, %98, 0;\n"
        "wgmma.mma_async.sync.aligned.m64n192k16.f32.bf16.bf16 {"
        "%0, %1, %2, %3, %4, %5, %6, %7, %8, %9, %10, %11, %12, %13, %14, %15, "
        "%16, %17, %18, %19, %20, %21, %22, %23, %24, %25, %26, %27, %28, %29, %30, %31, "
        "%32, %33, %34, %35, %36, %37, %38, %39, %40, %41, %42, %43, %44, %45, %46, %47, "
        "%48, %49, %50, %51, %52, %53, %54, %55, %56, %57, %58, %59, %60, %61, %62, %63, "
        "%64, %65, %66, %67, %68, %69, %70, %71, %72, %73, %74, %75, %76, %77, %78, %79, "
        "%80, %81, %82, %83, %84, %85, %86, %87, %88, %89, %90, %91, %92, %93, %94, %95}, "
        "%96, %97, p, 1, 1, 0, 1;\n}\n"
        : "+f"(d[0]), "+f"(d[1]), "+f"(d[2]), "+f"(d[3]), "+f"(d[4]), "+f"(d[5]), "+f"(d[6]), "+f"(d[7]),
          "+f"(d[8]), "+f"(d[9]), "+f"(d[10]), "+f"(d[11]), "+f"(d[12]), "+f"(d[13]), "+f"(d[14]), "+f"(d[15]),
          "+f"(d[16]), "+f"(d[17]), "+f"(d[18]), "+f"(d[19]), "+f"(d[20]), "+f"(d[21]), "+f"(d[22]), "+f"(d[23]),
          "+f"(d[24]), "+f"(d[25]), "+f"(d[26]), "+f"(d[27]), "+f"(d[28]), "+f"(d[29]), "+f"(d[30]), "+f"(d[31]),
          "+f"(d[32]), "+f"(d[33]), "+f"(d[34]), "+f"(d[35]), "+f"(d[36]), "+f"(d[37]), "+f"(d[38]), "+f"(d[39]),
          "+f"(d[40]), "+f"(d[41]), "+f"(d[42]), "+f"(d[43]), "+f"(d[44]), "+f"(d[45]), "+f"(d[46]), "+f"(d[47]),
          "+f"(d[48]), "+f"(d[49]), "+f"(d[50]), "+f"(d[51]), "+f"(d[52]), "+f"(d[53]), "+f"(d[54]), "+f"(d[55]),
          "+f"(d[56]), "+f"(d[57]), "+f"(d[58]), "+f"(d[59]), "+f"(d[60]), "+f"(d[61]), "+f"(d[62]), "+f"(d[63]),
          "+f"(d[64]), "+f"(d[65]), "+f"(d[66]), "+f"(d[67]), "+f"(d[68]), "+f"(d[69]), "+f"(d[70]), "+f"(d[71]),
          "+f"(d[72]), "+f"(d[73]), "+f"(d[74]), "+f"(d[75]), "+f"(d[76]), "+f"(d[77]), "+f"(d[78]), "+f"(d[79]),
          "+f"(d[80]), "+f"(d[81]), "+f"(d[82]), "+f"(d[83]), "+f"(d[84]), "+f"(d[85]), "+f"(d[86]), "+f"(d[87]),
          "+f"(d[88]), "+f"(d[89]), "+f"(d[90]), "+f"(d[91]), "+f"(d[92]), "+f"(d[93]), "+f"(d[94]), "+f"(d[95])
        : "l"(descA), "l"(descB), "r"(scaleD));
}

__device__ __forceinline__ void wgmma_n160_ss_tb(float (&d)[80], uint64_t descA, uint64_t descB, int scaleD) {
    asm volatile("{\n.reg .pred p;\nsetp.ne.b32 p, %82, 0;\n"
        "wgmma.mma_async.sync.aligned.m64n160k16.f32.bf16.bf16 {"
        "%0, %1, %2, %3, %4, %5, %6, %7, %8, %9, %10, %11, %12, %13, %14, %15, "
        "%16, %17, %18, %19, %20, %21, %22, %23, %24, %25, %26, %27, %28, %29, %30, %31, "
        "%32, %33, %34, %35, %36, %37, %38, %39, %40, %41, %42, %43, %44, %45, %46, %47, "
        "%48, %49, %50, %51, %52, %53, %54, %55, %56, %57, %58, %59, %60, %61, %62, %63, "
        "%64, %65, %66, %67, %68, %69, %70, %71, %72, %73, %74, %75, %76, %77, %78, %79}, "
        "%80, %81, p, 1, 1, 0, 1;\n}\n"
        : "+f"(d[0]), "+f"(d[1]), "+f"(d[2]), "+f"(d[3]), "+f"(d[4]), "+f"(d[5]), "+f"(d[6]), "+f"(d[7]),
          "+f"(d[8]), "+f"(d[9]), "+f"(d[10]), "+f"(d[11]), "+f"(d[12]), "+f"(d[13]), "+f"(d[14]), "+f"(d[15]),
          "+f"(d[16]), "+f"(d[17]), "+f"(d[18]), "+f"(d[19]), "+f"(d[20]), "+f"(d[21]), "+f"(d[22]), "+f"(d[23]),
          "+f"(d[24]), "+f"(d[25]), "+f"(d[26]), "+f"(d[27]), "+f"(d[28]), "+f"(d[29]), "+f"(d[30]), "+f"(d[31]),
          "+f"(d[32]), "+f"(d[33]), "+f"(d[34]), "+f"(d[35]), "+f"(d[36]), "+f"(d[37]), "+f"(d[38]), "+f"(d[39]),
          "+f"(d[40]), "+f"(d[41]), "+f"(d[42]), "+f"(d[43]), "+f"(d[44]), "+f"(d[45]), "+f"(d[46]), "+f"(d[47]),
          "+f"(d[48]), "+f"(d[49]), "+f"(d[50]), "+f"(d[51]), "+f"(d[52]), "+f"(d[53]), "+f"(d[54]), "+f"(d[55]),
          "+f"(d[56]), "+f"(d[57]), "+f"(d[58]), "+f"(d[59]), "+f"(d[60]), "+f"(d[61]), "+f"(d[62]), "+f"(d[63]),
          "+f"(d[64]), "+f"(d[65]), "+f"(d[66]), "+f"(d[67]), "+f"(d[68]), "+f"(d[69]), "+f"(d[70]), "+f"(d[71]),
          "+f"(d[72]), "+f"(d[73]), "+f"(d[74]), "+f"(d[75]), "+f"(d[76]), "+f"(d[77]), "+f"(d[78]), "+f"(d[79])
        : "l"(descA), "l"(descB), "r"(scaleD));
}

__device__ __forceinline__ void wgmma_n64_rs(float (&d)[32], uint32_t a0, uint32_t a1, uint32_t a2, uint32_t a3, uint64_t descB, int scaleD) {
    asm volatile("{\n.reg .pred p;\nsetp.ne.b32 p, %37, 0;\n"
        "wgmma.mma_async.sync.aligned.m64n64k16.f32.bf16.bf16 {"
        "%0, %1, %2, %3, %4, %5, %6, %7, %8, %9, %10, %11, %12, %13, %14, %15, "
        "%16, %17, %18, %19, %20, %21, %22, %23, %24, %25, %26, %27, %28, %29, %30, %31}, "
        "{%32, %33, %34, %35}, %36, p, 1, 1, 0;\n}\n"
        : "+f"(d[0]), "+f"(d[1]), "+f"(d[2]), "+f"(d[3]), "+f"(d[4]), "+f"(d[5]), "+f"(d[6]), "+f"(d[7]),
          "+f"(d[8]), "+f"(d[9]), "+f"(d[10]), "+f"(d[11]), "+f"(d[12]), "+f"(d[13]), "+f"(d[14]), "+f"(d[15]),
          "+f"(d[16]), "+f"(d[17]), "+f"(d[18]), "+f"(d[19]), "+f"(d[20]), "+f"(d[21]), "+f"(d[22]), "+f"(d[23]),
          "+f"(d[24]), "+f"(d[25]), "+f"(d[26]), "+f"(d[27]), "+f"(d[28]), "+f"(d[29]), "+f"(d[30]), "+f"(d[31])
        : "r"(a0), "r"(a1), "r"(a2), "r"(a3), "l"(descB), "r"(scaleD));
}

__device__ __forceinline__ void wgmma_n64_rs_z(float (&d)[32], uint32_t a0, uint32_t a1, uint32_t a2, uint32_t a3, uint64_t descB) {
    asm volatile("{\n.reg .pred p;\nsetp.ne.b32 p, 0, 0;\n"
        "wgmma.mma_async.sync.aligned.m64n64k16.f32.bf16.bf16 {"
        "%0, %1, %2, %3, %4, %5, %6, %7, %8, %9, %10, %11, %12, %13, %14, %15, "
        "%16, %17, %18, %19, %20, %21, %22, %23, %24, %25, %26, %27, %28, %29, %30, %31}, "
        "{%32, %33, %34, %35}, %36, p, 1, 1, 0;\n}\n"
        : "=f"(d[0]), "=f"(d[1]), "=f"(d[2]), "=f"(d[3]), "=f"(d[4]), "=f"(d[5]), "=f"(d[6]), "=f"(d[7]),
          "=f"(d[8]), "=f"(d[9]), "=f"(d[10]), "=f"(d[11]), "=f"(d[12]), "=f"(d[13]), "=f"(d[14]), "=f"(d[15]),
          "=f"(d[16]), "=f"(d[17]), "=f"(d[18]), "=f"(d[19]), "=f"(d[20]), "=f"(d[21]), "=f"(d[22]), "=f"(d[23]),
          "=f"(d[24]), "=f"(d[25]), "=f"(d[26]), "=f"(d[27]), "=f"(d[28]), "=f"(d[29]), "=f"(d[30]), "=f"(d[31])
        : "r"(a0), "r"(a1), "r"(a2), "r"(a3), "l"(descB));
}

__device__ __forceinline__ void wgmma_n24_rs_tb(float (&d)[12], uint32_t a0, uint32_t a1, uint32_t a2, uint32_t a3, uint64_t descB, int scaleD) {
    asm volatile("{\n.reg .pred p;\nsetp.ne.b32 p, %17, 0;\n"
        "wgmma.mma_async.sync.aligned.m64n24k16.f32.bf16.bf16 {"
        "%0, %1, %2, %3, %4, %5, %6, %7, %8, %9, %10, %11}, "
        "{%12, %13, %14, %15}, %16, p, 1, 1, 1;\n}\n"
        : "+f"(d[0]), "+f"(d[1]), "+f"(d[2]), "+f"(d[3]), "+f"(d[4]), "+f"(d[5]), "+f"(d[6]), "+f"(d[7]),
          "+f"(d[8]), "+f"(d[9]), "+f"(d[10]), "+f"(d[11])
        : "r"(a0), "r"(a1), "r"(a2), "r"(a3), "l"(descB), "r"(scaleD));
}

__global__ void __launch_bounds__(256) k_ln(const __nv_bfloat16* __restrict__ x) {
    if (threadIdx.x == 0) TL(0, 0);
    pdl_launch();
    const int lane = threadIdx.x & 31;
    const int row = blockIdx.x * 8 + (threadIdx.x >> 5);
    const uint2* src = reinterpret_cast<const uint2*>(x + (size_t)row * DM);
    uint2 v[5];
#pragma unroll
    for (int i = 0; i < 5; i++) v[i] = __ldg(src + lane + 32 * i);
    float f[20];
#pragma unroll
    for (int i = 0; i < 5; i++) {
        f[4 * i] = bf_lo(v[i].x); f[4 * i + 1] = bf_hi(v[i].x);
        f[4 * i + 2] = bf_lo(v[i].y); f[4 * i + 3] = bf_hi(v[i].y);
    }
    float s = 0.f;
#pragma unroll
    for (int i = 0; i < 20; i++) s += f[i];
#pragma unroll
    for (int o = 16; o; o >>= 1) s += __shfl_xor_sync(~0u, s, o);
    const float mu = s * (1.f / DM);
    float q = 0.f;
#pragma unroll
    for (int i = 0; i < 20; i++) { f[i] -= mu; q += f[i] * f[i]; }
#pragma unroll
    for (int o = 16; o; o >>= 1) q += __shfl_xor_sync(~0u, q, o);
    const float var = q * (1.f / DM);
    const float r1 = 1.f / sqrtf(var + LN_EPS);
    uint2* dst = reinterpret_cast<uint2*>(g_xn + (size_t)row * DM);
#pragma unroll
    for (int i = 0; i < 5; i++) {
        uint2 w;
        w.x = pack_bf16(f[4 * i] * r1, f[4 * i + 1] * r1);
        w.y = pack_bf16(f[4 * i + 2] * r1, f[4 * i + 3] * r1);
        dst[lane + 32 * i] = w;
    }
    if (lane == 0) g_r2[row] = 1.f / sqrtf(var * r1 * r1 + LN_EPS);
    if (threadIdx.x == 0) TL(0, 3);
}

constexpr int G1_A_BYTES = 10 * 16384;
constexpr int G1_STAGES = 4;
constexpr int G1_B_STAGE = 16384;
constexpr int G1_BAR_OFF = G1_A_BYTES + G1_STAGES * G1_B_STAGE;
constexpr int G1_SMEM = G1_BAR_OFF + 256;

template <int N, bool FIRST, typename MMA>
__device__ __forceinline__ void g1_mainloop(float (&acc)[N / 2], uint32_t sA, uint32_t sB, uint32_t barA, uint32_t barFull,
                                            uint32_t barEmpty, int git0, int lane, uint32_t peer, MMA mma) {
#pragma unroll 1
    for (int it = 0; it < 20; it++) {
        const int git = git0 + it;
        const int s = git & (G1_STAGES - 1);
        if (FIRST && !(it & 1)) mbar_wait(barA + (it >> 1) * 8, 0);
        mbar_wait(barFull + s * 8, (git >> 2) & 1);
        wg_fence();
        const uint64_t dA = make_desc(sA + (it >> 1) * 16384 + (it & 1) * 64, 16, 1024, 1);
        const uint64_t dB = make_desc(sB + s * G1_B_STAGE, 4096, 1024, 1);
        mma(acc, dA, dB, it > 0);
        mma(acc, dA + 2, dB + 128, 1);
        wg_commit();
        if (it > 0) {
            wg_wait<1>();
            if (lane == 0) {
                const uint32_t e = barEmpty + ((git - 1) & (G1_STAGES - 1)) * 8;
                mbar_arrive(e);
                mbar_arrive_cluster(e, peer);
            }
        }
    }
    wg_wait<0>();
    if (lane == 0) {
        const uint32_t e = barEmpty + ((git0 + 19) & (G1_STAGES - 1)) * 8;
        mbar_arrive(e);
        mbar_arrive_cluster(e, peer);
    }
    fence_regs(acc);
}

__device__ __forceinline__ float gelu_tanh(float x) {
    const float u = x * (0.7978845608028654f + 0.035677408136300125f * x * x);
    float t;
    asm("tanh.approx.f32 %0, %1;" : "=f"(t) : "f"(u));
    const float h = 0.5f * x;
    return fmaf(h, t, h);
}

__global__ void __launch_bounds__(384, 1) __cluster_dims__(2, 1, 1)
k_gemm1(const __grid_constant__ CUtensorMap tmA, const __grid_constant__ CUtensorMap tmWqkv,
        const __grid_constant__ CUtensorMap tmW1, const __grid_constant__ CUtensorMap tmH,
        const __nv_bfloat16* __restrict__ b1) {
    extern __shared__ __align__(1024) uint8_t smem[];
    const uint32_t sbase = smem_u32(smem);
    const uint32_t sA = sbase, sB = sbase + G1_A_BYTES;
    const uint32_t barA = sbase + G1_BAR_OFF, barFull = barA + 80, barEmpty = barFull + 32;
    const int warp = __shfl_sync(~0u, threadIdx.x >> 5, 0), lane = threadIdx.x & 31;
    const uint32_t rank = blockIdx.x & 1;
    const int cl = blockIdx.x >> 1, cg = cl & 7, rb = (cl >> 3) * 2 + rank;

    if (threadIdx.x == 0) TL(1, 0);
    pdl_launch();
    if (threadIdx.x == 0) {
        for (int i = 0; i < 10; i++) mbar_init(barA + i * 8, 1);
        for (int i = 0; i < G1_STAGES; i++) { mbar_init(barFull + i * 8, 1); mbar_init(barEmpty + i * 8, 16); }
        fence_barrier_init();
    }
    __syncthreads();
    cluster_sync();

    if (warp < 4) {
        reg_dealloc<40>();
        if (warp == 0) {
            if (elect_one()) { prefetch_map(&tmA); prefetch_map(&tmWqkv); prefetch_map(&tmW1); prefetch_map(&tmH); }
#pragma unroll 1
            for (int git = 0; git < 40; git++) {
                const int s = git & (G1_STAGES - 1);
                if (git == G1_STAGES) {
                    pdl_wait();
                    if (elect_one()) {
                        for (int kb = 0; kb < 10; kb++) {
                            mbar_expect_tx(barA + kb * 8, 16384);
                            tma_load(sA + kb * 16384, &tmA, kb * 64, rb * 128, barA + kb * 8);
                        }
                    }
                    __syncwarp();
                }
                if (git >= G1_STAGES) mbar_wait(barEmpty + s * 8, ((git >> 2) - 1) & 1);
                if (elect_one()) {
                    const uint32_t dst = sB + s * G1_B_STAGE, bar = barFull + s * 8;
                    if (git < 20) {
                        mbar_expect_tx(bar, 16384);
                        tma_load_mc(dst + (rank * 2) * 4096, &tmWqkv, cg * 240 + (rank * 2) * 64, git * 32, bar, 3);
                        tma_load_mc(dst + (rank * 2 + 1) * 4096, &tmWqkv, cg * 240 + (rank * 2 + 1) * 64, git * 32, bar, 3);
                    } else {
                        const int k0 = (git - 20) * 32;
                        mbar_expect_tx(bar, 12288);
                        if ((git & 1) == (int)rank) {
                            tma_load_mc(dst, &tmW1, cg * 192, k0, bar, 3);
                            tma_load_mc(dst + 4096, &tmW1, cg * 192 + 64, k0, bar, 3);
                        } else {
                            tma_load_mc(dst + 8192, &tmW1, cg * 192 + 128, k0, bar, 3);
                        }
                    }
                }
                __syncwarp();
            }
        }
    } else {
        reg_alloc<232>();
        const int wg = (warp >> 2) - 1, w4 = warp & 3;
        const int g = lane >> 2, c = lane & 3;
        const int row0 = rb * 128 + wg * 64 + w4 * 16 + g;
        const uint32_t sAw = sA + wg * 8192;
        const uint32_t peer = rank ^ 1;
        {
            float acc[120];
            g1_mainloop<240, true>(acc, sAw, sB, barA, barFull, barEmpty, 0, lane, peer,
                [](float (&d)[120], uint64_t a, uint64_t b, int sc) { wgmma_n240_ss_tb(d, a, b, sc); });
            if (threadIdx.x == 128) TL(1, 1);
            const int rbk = row0 >> 3;
            const bool emu0 = (EMU_MASK >> (rbk & 15)) & 1, emu1 = (EMU_MASK >> ((rbk + 1) & 15)) & 1;
#pragma unroll
            for (int m = 0; m < 6; m++) {
                const int hs = cg * 12 + 2 * m, which = hs >> 5;
                const float* a = acc + 20 * m;
                float m0, m1;
                uint32_t pad0, pad1;
                if (which == 0) { m0 = m1 = QSCALE; pad0 = pad1 = 0x3F803F80u; }
                else if (which == 1) {
                    m0 = emu0 ? 2.f : 1.f; m1 = emu1 ? 2.f : 1.f;
                    pad0 = emu0 ? 0xBFFF4440u : 0u; pad1 = emu1 ? 0xBFFF4440u : 0u;
                } else { m0 = m1 = 1.f; pad0 = pad1 = 0x00003F80u; }
                uint8_t* pe = g_img + (size_t)hs * IMG_BYTES + rbk * 384 + g * 16 + c * 4;
                uint8_t* po = pe + IMG_BYTES;
                const uint32_t mid0 = pack_bf16(a[8] * m0, a[9] * m0), mid1 = pack_bf16(a[10] * m1, a[11] * m1);
                const bool low = c < 2;
                const uint32_t p0 = (c & 1) ? 0u : pad0, p1 = (c & 1) ? 0u : pad1;
                *(uint32_t*)(pe) = pack_bf16(a[0] * m0, a[1] * m0);
                *(uint32_t*)(pe + 128) = pack_bf16(a[4] * m0, a[5] * m0);
                *(uint32_t*)(pe + 256) = low ? mid0 : p0;
                *(uint32_t*)(pe + 384) = pack_bf16(a[2] * m1, a[3] * m1);
                *(uint32_t*)(pe + 512) = pack_bf16(a[6] * m1, a[7] * m1);
                *(uint32_t*)(pe + 640) = low ? mid1 : p1;
                *(uint32_t*)(po) = pack_bf16(a[12] * m0, a[13] * m0);
                *(uint32_t*)(po + 128) = pack_bf16(a[16] * m0, a[17] * m0);
                *(uint32_t*)(po + 256) = low ? p0 : mid0;
                *(uint32_t*)(po + 384) = pack_bf16(a[14] * m1, a[15] * m1);
                *(uint32_t*)(po + 512) = pack_bf16(a[18] * m1, a[19] * m1);
                *(uint32_t*)(po + 640) = low ? p1 : mid1;
                if (which < 2) {
                    const float u0 = a[8] * a[8] + a[9] * a[9], u1 = a[10] * a[10] + a[11] * a[11];
                    float e0 = a[0] * a[0] + a[1] * a[1] + a[4] * a[4] + a[5] * a[5] + (low ? u0 : 0.f);
                    float e1 = a[2] * a[2] + a[3] * a[3] + a[6] * a[6] + a[7] * a[7] + (low ? u1 : 0.f);
                    float o0 = a[12] * a[12] + a[13] * a[13] + a[16] * a[16] + a[17] * a[17] + (low ? 0.f : u0);
                    float o1 = a[14] * a[14] + a[15] * a[15] + a[18] * a[18] + a[19] * a[19] + (low ? 0.f : u1);
                    const bool b0 = c & 1, b1_ = c & 2;
                    float x0 = (b0 ? e1 : e0) + __shfl_xor_sync(~0u, b0 ? e0 : e1, 1);
                    float x1 = (b0 ? o1 : o0) + __shfl_xor_sync(~0u, b0 ? o0 : o1, 1);
                    float y = (b1_ ? x1 : x0) + __shfl_xor_sync(~0u, b1_ ? x0 : x1, 2);
                    if (which == 0) y *= QSCALE * QSCALE;
                    g_nrm[(hs + (c >> 1)) * SEQ + row0 + (c & 1) * 8] = y;
                }
            }
        }
        {
            float acc[96];
            g1_mainloop<192, false>(acc, sAw, sB, barA, barFull, barEmpty, 20, lane, peer,
                [](float (&d)[96], uint64_t a, uint64_t b, int sc) { wgmma_n192_ss_tb(d, a, b, sc); });
            if (threadIdx.x == 128) TL(1, 2);
            const float r0 = g_r2[row0], r1 = g_r2[row0 + 8];
            const uint32_t* bias = reinterpret_cast<const uint32_t*>(b1 + cg * 192) + c;
            const int mrow = w4 * 16 + (lane & 15);
            const uint32_t st_row = sAw + mrow * 128;
#pragma unroll
            for (int j = 0; j < 24; j += 2) {
                const uint32_t bA = __ldg(bias + j * 4), bB = __ldg(bias + j * 4 + 4);
                const float* a = acc + j * 4;
                const uint32_t r00 = pack_bf16(gelu_tanh(fmaf(a[0], r0, bf_lo(bA))), gelu_tanh(fmaf(a[1], r0, bf_hi(bA))));
                const uint32_t r10 = pack_bf16(gelu_tanh(fmaf(a[2], r1, bf_lo(bA))), gelu_tanh(fmaf(a[3], r1, bf_hi(bA))));
                const uint32_t r01 = pack_bf16(gelu_tanh(fmaf(a[4], r0, bf_lo(bB))), gelu_tanh(fmaf(a[5], r0, bf_hi(bB))));
                const uint32_t r11 = pack_bf16(gelu_tanh(fmaf(a[6], r1, bf_lo(bB))), gelu_tanh(fmaf(a[7], r1, bf_hi(bB))));
                const int chunk = (j & 7) + (lane >> 4);
                stmatrix_x4(st_row + (j >> 3) * 16384 + ((chunk ^ (mrow & 7)) << 4), r00, r10, r01, r11);
            }
            fence_proxy_async();
            asm volatile("bar.sync %0, 128;" ::"r"(wg + 1) : "memory");
            if (w4 == 0 && elect_one()) {
#pragma unroll
                for (int b = 0; b < 3; b++) tma_store(&tmH, sAw + b * 16384, cg * 192 + b * 64, rb * 128 + wg * 64);
                bulk_commit();
                bulk_wait_all();
            }
        }
    }
    __syncthreads();
    if (threadIdx.x == 0) TL(1, 3);
    cluster_sync();
}

constexpr int AT_BAR_OFF = 2 * IMG_BYTES;
constexpr int AT_SMEM = AT_BAR_OFF + 512;

__device__ __forceinline__ uint32_t bf2_fma(uint32_t a, uint32_t b, uint32_t c) {
    uint32_t r;
    asm("fma.rn.bf16x2 %0, %1, %2, %3;" : "=r"(r) : "r"(a), "r"(b), "r"(c));
    return r;
}
__device__ __forceinline__ uint32_t lop_and_or(uint32_t a, uint32_t m, uint32_t o) {
    uint32_t r;
    asm("lop3.b32 %0, %1, %2, %3, 0xEA;" : "=r"(r) : "r"(a), "r"(m), "r"(o));
    return r;
}
struct ExpConst { uint32_t mask, slope; };
__device__ __forceinline__ ExpConst make_exp_const() {
    ExpConst k;
    asm volatile("mov.b32 %0, 0x007F007F;" : "=r"(k.mask));
    asm volatile("mov.b32 %0, 0x3EF83EF8;" : "=r"(k.slope));
    return k;
}
__device__ __forceinline__ uint32_t exp2_pair_fma(float t0, float t1, const ExpConst& k) {
    const uint32_t L = __byte_perm(__float_as_uint(t0), __float_as_uint(t1), 0x6521);
    const uint32_t g = lop_and_or(L, k.mask, 0x3F803F80u);
    const uint32_t u = bf2_fma(g, k.slope, 0xBF37BF37u);
    const uint32_t e = bf2_fma(u, u, 0xBD71BD71u);
    return bf2_fma(L, e, L);
}
template <int SHIFT>
__device__ __forceinline__ void exp_tile(const float (&s)[32], uint32_t (&p)[16], const ExpConst& k) {
#pragma unroll
    for (int b = 0; b < 8; b++) {
        if ((EMU_MASK >> (b + SHIFT)) & 1) {
            p[2 * b] = exp2_pair_fma(s[4 * b], s[4 * b + 1], k);
            p[2 * b + 1] = exp2_pair_fma(s[4 * b + 2], s[4 * b + 3], k);
        } else {
            p[2 * b] = pack_bf16(ex2(s[4 * b]), ex2(s[4 * b + 1]));
            p[2 * b + 1] = pack_bf16(ex2(s[4 * b + 2]), ex2(s[4 * b + 3]));
        }
    }
}
struct QFrag { uint32_t q0, q1, q2, q3, q4, q5; };
__device__ __forceinline__ QFrag load_q(int h, int rbase, int g, int c) {
    const uint8_t* gq = g_img + (size_t)h * IMG_BYTES + (rbase >> 3) * 384 + g * 16 + c * 4;
    QFrag q;
    q.q0 = *(const uint32_t*)(gq); q.q1 = *(const uint32_t*)(gq + 384);
    q.q2 = *(const uint32_t*)(gq + 128); q.q3 = *(const uint32_t*)(gq + 512);
    q.q4 = *(const uint32_t*)(gq + 256); q.q5 = *(const uint32_t*)(gq + 640);
    return q;
}
__device__ __forceinline__ void qk_tile(float (&s)[32], const QFrag& q, uint64_t dK) {
    wg_fence();
    wgmma_n64_rs_z(s, q.q0, q.q1, q.q2, q.q3, dK);
    wgmma_n64_rs(s, q.q4, q.q5, 0u, 0u, dK + 16, 1);
    wg_commit();
}
__device__ __forceinline__ void pv_tile(float (&o)[12], const uint32_t (&p)[16], uint64_t dV) {
    wg_fence();
#pragma unroll
    for (int ks = 0; ks < 4; ks++)
        wgmma_n24_rs_tb(o, p[4 * ks], p[4 * ks + 1], p[4 * ks + 2], p[4 * ks + 3], dV + ks * 48, 1);
    wg_commit();
}
__device__ __forceinline__ void store_o(const float (&o)[12], int h, int rbase, int lane) {
    const int g = lane >> 2, c = lane & 3;
    const bool odd = h & 1;
    const int lsrc = (lane & ~3) | (odd ? 0 : 2);
    const float i0 = 1.f / __shfl_sync(~0u, o[8], lsrc), i1 = 1.f / __shfl_sync(~0u, o[10], lsrc);
    __nv_bfloat16* dst = g_o + (size_t)(rbase + g) * DM + h * 20;
    const int d0 = (odd ? 4 : 0) + 2 * c, d1 = d0 + 8, d2 = odd ? 2 * c - 4 : 16 + 2 * c;
    *(uint32_t*)(dst + d0) = pack_bf16(o[0] * i0, o[1] * i0);
    *(uint32_t*)(dst + d1) = pack_bf16(o[4] * i0, o[5] * i0);
    *(uint32_t*)(dst + 8 * DM + d0) = pack_bf16(o[2] * i1, o[3] * i1);
    *(uint32_t*)(dst + 8 * DM + d1) = pack_bf16(o[6] * i1, o[7] * i1);
    if (odd ? (c >= 2) : (c < 2)) {
        *(uint32_t*)(dst + d2) = pack_bf16(o[8] * i0, o[9] * i0);
        *(uint32_t*)(dst + 8 * DM + d2) = pack_bf16(o[10] * i1, o[11] * i1);
    }
}

__device__ __forceinline__ void attn_rows_maxshift(uint32_t sK, uint32_t bar, int h, int rbase) {
    const int lane = threadIdx.x & 31, g = lane >> 2, c = lane & 3;
    QFrag q = load_q(h, rbase, g, c);
    if (c == ((h & 1) ? 0 : 2)) { q.q4 = 0u; q.q5 = 0u; }
    const uint64_t dK0 = make_desc(sK, 128, 384, 0), dV0 = make_desc(sK + IMG_BYTES, 384, 128, 0);
    float o[12], s[32];
    uint32_t p[16];
#pragma unroll
    for (int i = 0; i < 12; i++) o[i] = 0.f;
    float m0 = -3.0e38f, m1 = -3.0e38f;
    mbar_wait(bar + 128, 0);
#pragma unroll 1
    for (int t = 0; t < 32; t++) {
        mbar_wait(bar + (t >> 1) * 8, 0);
        if (t) mbar_wait(bar + ((t - 1) >> 1) * 8, 0);
        qk_tile(s, q, dK0 + t * 192);
        wg_wait<0>();
        fence_regs(s);
        const uint32_t mask = EMU_MASK >> ((t & 1) * 8);
        float n0 = m0, n1 = m1;
#pragma unroll
        for (int b = 0; b < 8; b++) {
            const float f = ((mask >> b) & 1) ? 0.5f : 1.f;
            s[4 * b] *= f; s[4 * b + 1] *= f; s[4 * b + 2] *= f; s[4 * b + 3] *= f;
            n0 = fmaxf(n0, fmaxf(s[4 * b], s[4 * b + 1]));
            n1 = fmaxf(n1, fmaxf(s[4 * b + 2], s[4 * b + 3]));
        }
        n0 = fmaxf(n0, __shfl_xor_sync(~0u, n0, 1)); n0 = fmaxf(n0, __shfl_xor_sync(~0u, n0, 2));
        n1 = fmaxf(n1, __shfl_xor_sync(~0u, n1, 1)); n1 = fmaxf(n1, __shfl_xor_sync(~0u, n1, 2));
        const float c0 = ex2(m0 - n0), c1 = ex2(m1 - n1);
        m0 = n0; m1 = n1;
#pragma unroll
        for (int b = 0; b < 3; b++) { o[4 * b] *= c0; o[4 * b + 1] *= c0; o[4 * b + 2] *= c1; o[4 * b + 3] *= c1; }
#pragma unroll
        for (int b = 0; b < 8; b++) {
            p[2 * b] = pack_bf16(ex2(s[4 * b] - m0), ex2(s[4 * b + 1] - m0));
            p[2 * b + 1] = pack_bf16(ex2(s[4 * b + 2] - m1), ex2(s[4 * b + 3] - m1));
        }
        pv_tile(o, p, dV0 + t * 192);
        wg_wait<0>();
        fence_regs(o);
    }
    store_o(o, h, rbase, lane);
}

__global__ void __launch_bounds__(512, 1) k_attn() {
    extern __shared__ __align__(1024) uint8_t smem[];
    const uint32_t sK = smem_u32(smem), sV = sK + IMG_BYTES;
    const uint32_t bar = sK + AT_BAR_OFF;
    float* red = reinterpret_cast<float*>(smem + AT_BAR_OFF + 256);
    const int warp = __shfl_sync(~0u, threadIdx.x >> 5, 0), lane = threadIdx.x & 31;
    const int h = blockIdx.x >> 2, qb = blockIdx.x & 3;
    const int wg = warp >> 2, w4 = warp & 3;

    if (threadIdx.x == 0) TL(2, 0);
    pdl_launch();
    if (threadIdx.x == 0) {
        for (int i = 0; i < 17; i++) mbar_init(bar + i * 8, 1);
        fence_barrier_init();
    }
    __syncthreads();
    pdl_wait();
    if (threadIdx.x == 0) TL(2, 1);
    if (warp == 0 && elect_one()) {
        const uint8_t* gK = g_img + (size_t)(32 + h) * IMG_BYTES;
        const uint8_t* gV = g_img + (size_t)(64 + h) * IMG_BYTES;
        mbar_expect_tx(bar + 128, 6144);
        bulk_load(sK, gK, 6144, bar + 128);
        for (int i = 0; i < 16; i++) {
            mbar_expect_tx(bar + i * 8, i < 15 ? 12288 : 6144);
            bulk_load(sV + i * 6144, gV + i * 6144, 6144, bar + i * 8);
            if (i < 15) bulk_load(sK + (i + 1) * 6144, gK + (i + 1) * 6144, 6144, bar + i * 8);
        }
    }
    float kmax = 0.f, qmax = g_nrm[h * SEQ + qb * 512 + threadIdx.x];
#pragma unroll
    for (int i = 0; i < 4; i++) kmax = fmaxf(kmax, g_nrm[(32 + h) * SEQ + i * 512 + threadIdx.x]);
#pragma unroll
    for (int o = 16; o; o >>= 1) {
        kmax = fmaxf(kmax, __shfl_xor_sync(~0u, kmax, o));
        qmax = fmaxf(qmax, __shfl_xor_sync(~0u, qmax, o));
    }
    if (lane == 0) { red[warp] = kmax; red[16 + warp] = qmax; }
    __syncthreads();
    kmax = red[lane & 15]; qmax = red[16 + (lane & 15)];
#pragma unroll
    for (int o = 8; o; o >>= 1) {
        kmax = fmaxf(kmax, __shfl_xor_sync(~0u, kmax, o));
        qmax = fmaxf(qmax, __shfl_xor_sync(~0u, qmax, o));
    }
    const bool safe = __all_sync(~0u, kmax * qmax * 1.05f <= SAFE_BOUND * SAFE_BOUND);
    if (!safe) {
#pragma unroll 1
        for (int pass = 0; pass < 2; pass++) attn_rows_maxshift(sK, bar, h, qb * 512 + pass * 256 + wg * 64 + w4 * 16);
        return;
    }
    const ExpConst kc = make_exp_const();
    const uint64_t dK0 = make_desc(sK, 128, 384, 0), dV0 = make_desc(sV, 384, 128, 0);
#pragma unroll 1
    for (int pass = 0; pass < 2; pass++) {
        const int rbase = qb * 512 + pass * 256 + wg * 64 + w4 * 16;
        const QFrag q = load_q(h, rbase, lane >> 2, lane & 3);
        float o[12], sa[32], sb[32];
        uint32_t p[16];
#pragma unroll
        for (int i = 0; i < 12; i++) o[i] = 0.f;
        fence_regs(o);
        mbar_wait(bar + 128, 0);
        qk_tile(sa, q, dK0);
        wg_wait<0>();
        fence_regs(sa);
        uint64_t dK = dK0, dV = dV0;
        uint32_t bj = bar;
#pragma unroll 1
        for (int j = 0; j < 16; j++) {
            mbar_wait(bj, 0);
            qk_tile(sb, q, dK + 192);
            wg_wait<1>();
            exp_tile<0>(sa, p, kc);
            pv_tile(o, p, dV);
            wg_wait<1>();
            fence_regs(sb);
            mbar_wait(bj, 0);
            qk_tile(sa, q, dK + 384);
            wg_wait<1>();
            exp_tile<8>(sb, p, kc);
            pv_tile(o, p, dV + 192);
            wg_wait<1>();
            fence_regs(sa);
            dK += 384; dV += 384; bj += 8;
        }
        wg_wait<0>();
        fence_regs(o);
        store_o(o, h, rbase, lane);
        if (threadIdx.x == 0) TL(2, 2 + pass);
    }
}

constexpr int G2_STAGES = 8;
constexpr int G2_STAGE = 8192 + 20480;
constexpr int G2_BAR_OFF = G2_STAGES * G2_STAGE;
constexpr int G2_SMEM = G2_BAR_OFF + 256;

__global__ void __launch_bounds__(160, 1) __cluster_dims__(2, 1, 1)
k_gemm2(const __grid_constant__ CUtensorMap tmO, const __grid_constant__ CUtensorMap tmH,
        const __grid_constant__ CUtensorMap tmWo, const __grid_constant__ CUtensorMap tmW2,
        const __nv_bfloat16* __restrict__ x, const __nv_bfloat16* __restrict__ b2, __nv_bfloat16* __restrict__ out) {
    extern __shared__ __align__(1024) uint8_t smem[];
    const uint32_t sbase = smem_u32(smem);
    const uint32_t barFull = sbase + G2_BAR_OFF, barEmpty = barFull + 64;
    const int warp = __shfl_sync(~0u, threadIdx.x >> 5, 0), lane = threadIdx.x & 31;
    const uint32_t rank = blockIdx.x & 1;
    const int cl = blockIdx.x >> 1, ct = cl & 3, rt = (cl >> 2) * 2 + rank;

    if (threadIdx.x == 0) TL(3, 0);
    pdl_launch();
    if (threadIdx.x == 0) {
        for (int i = 0; i < G2_STAGES; i++) { mbar_init(barFull + i * 8, 1); mbar_init(barEmpty + i * 8, 8); }
        fence_barrier_init();
    }
    __syncthreads();
    cluster_sync();

    if (warp == 4) {
        if (elect_one()) { prefetch_map(&tmO); prefetch_map(&tmH); prefetch_map(&tmWo); prefetch_map(&tmW2); }
        pdl_wait();
        if (lane == 0) TL(3, 1);
#pragma unroll 1
        for (int kb = 0; kb < 34; kb++) {
            const int s = kb & (G2_STAGES - 1);
            if (kb >= G2_STAGES) mbar_wait(barEmpty + s * 8, ((kb >> 3) - 1) & 1);
            if (elect_one()) {
                const uint32_t dst = sbase + s * G2_STAGE, bar = barFull + s * 8;
                const CUtensorMap* mA = kb < 24 ? &tmH : &tmO;
                const CUtensorMap* mB = kb < 24 ? &tmW2 : &tmWo;
                const int k0 = (kb < 24 ? kb : kb - 24) * 64;
                mbar_expect_tx(bar, G2_STAGE);
                tma_load(dst, mA, k0, rt * 64, bar);
                const int first = ((kb & 1) == (int)rank) ? 0 : 3, last = ((kb & 1) == (int)rank) ? 3 : 5;
                for (int b = first; b < last; b++)
                    tma_load_mc(dst + 8192 + b * 4096, mB, ct * 160 + b * 32, k0, bar, 3);
            }
            __syncwarp();
        }
    } else {
        const int g = lane >> 2, c = lane & 3;
        const uint32_t peer = rank ^ 1;
        float acc[80];
#pragma unroll 1
        for (int kb = 0; kb < 34; kb++) {
            const int s = kb & (G2_STAGES - 1);
            mbar_wait(barFull + s * 8, (kb >> 3) & 1);
            wg_fence();
            const uint64_t dA = make_desc(sbase + s * G2_STAGE, 16, 1024, 1);
            const uint64_t dB = make_desc(sbase + s * G2_STAGE + 8192, 4096, 512, 2);
#pragma unroll
            for (int kk = 0; kk < 4; kk++) wgmma_n160_ss_tb(acc, dA + kk * 2, dB + kk * 64, (kb | kk) != 0);
            wg_commit();
            if (kb > 0) {
                wg_wait<1>();
                if (lane == 0) {
                    const uint32_t e = barEmpty + ((kb - 1) & (G2_STAGES - 1)) * 8;
                    mbar_arrive(e);
                    mbar_arrive_cluster(e, peer);
                }
            }
        }
        wg_wait<0>();
        fence_regs(acc);
        if (threadIdx.x == 0) TL(3, 2);
        const int row = rt * 64 + warp * 16 + g;
        const size_t off0 = (size_t)row * DM + ct * 160 + 2 * c, off1 = off0 + 8 * DM;
        const uint32_t* bias = reinterpret_cast<const uint32_t*>(b2 + ct * 160) + c;
#pragma unroll
        for (int j = 0; j < 20; j++) {
            const uint32_t bb = __ldg(bias + j * 4);
            const uint32_t x0 = __ldg((const uint32_t*)(x + off0 + j * 8)), x1 = __ldg((const uint32_t*)(x + off1 + j * 8));
            *(uint32_t*)(out + off0 + j * 8) =
                pack_bf16(acc[4 * j] + bf_lo(bb) + bf_lo(x0), acc[4 * j + 1] + bf_hi(bb) + bf_hi(x0));
            *(uint32_t*)(out + off1 + j * 8) =
                pack_bf16(acc[4 * j + 2] + bf_lo(bb) + bf_lo(x1), acc[4 * j + 3] + bf_hi(bb) + bf_hi(x1));
        }
    }
    __syncthreads();
    if (threadIdx.x == 0) TL(3, 3);
    cluster_sync();
}

typedef CUresult (*EncodeTiledFn)(CUtensorMap*, CUtensorMapDataType, cuuint32_t, void*, const cuuint64_t*,
                                  const cuuint64_t*, const cuuint32_t*, const cuuint32_t*, CUtensorMapInterleave,
                                  CUtensorMapSwizzle, CUtensorMapL2promotion, CUtensorMapFloatOOBfill);

CUtensorMap make_map(EncodeTiledFn enc, const void* ptr, int rows, int cols, int box_rows, int box_cols,
                     CUtensorMapSwizzle swz) {
    CUtensorMap m;
    cuuint64_t gd[2] = {(cuuint64_t)cols, (cuuint64_t)rows};
    cuuint64_t gs[1] = {(cuuint64_t)cols * 2};
    cuuint32_t bd[2] = {(cuuint32_t)box_cols, (cuuint32_t)box_rows};
    cuuint32_t es[2] = {1, 1};
    enc(&m, CU_TENSOR_MAP_DATA_TYPE_BFLOAT16, 2, const_cast<void*>(ptr), gd, gs, bd, es, CU_TENSOR_MAP_INTERLEAVE_NONE,
        swz, CU_TENSOR_MAP_L2_PROMOTION_L2_128B, CU_TENSOR_MAP_FLOAT_OOB_FILL_NONE);
    return m;
}

template <typename... KArgs, typename... Args>
void launch(void (*kern)(KArgs...), int grid, int block, int smem, int cluster, bool pdl, Args... args) {
    cudaLaunchConfig_t cfg = {};
    cfg.gridDim = dim3(grid);
    cfg.blockDim = dim3(block);
    cfg.dynamicSmemBytes = smem;
    cfg.stream = cudaStreamPerThread;
    cudaLaunchAttribute at[1];
    at[0].id = cudaLaunchAttributeProgrammaticStreamSerialization;
    at[0].val.programmaticStreamSerializationAllowed = 1;
    cfg.attrs = at;
    cfg.numAttrs = pdl ? 1 : 0;
    (void)cluster;
    cudaLaunchKernelEx(&cfg, kern, KArgs(args)...);
}

}

extern "C" void kernel_launch(void* const* d_in, const int* in_sizes, int n_in, void* d_out, int out_size) {
    (void)in_sizes; (void)n_in; (void)out_size;
    const __nv_bfloat16* x = (const __nv_bfloat16*)d_in[0];
    const __nv_bfloat16* wqkv = (const __nv_bfloat16*)d_in[1];
    const __nv_bfloat16* wo = (const __nv_bfloat16*)d_in[2];
    const __nv_bfloat16* w1 = (const __nv_bfloat16*)d_in[4];
    const __nv_bfloat16* b1 = (const __nv_bfloat16*)d_in[5];
    const __nv_bfloat16* w2 = (const __nv_bfloat16*)d_in[6];
    const __nv_bfloat16* b2 = (const __nv_bfloat16*)d_in[7];
    __nv_bfloat16* out = (__nv_bfloat16*)d_out;

    static EncodeTiledFn enc = nullptr;
    static void *p_xn, *p_h, *p_o;
    if (!enc) {
        cudaDriverEntryPointQueryResult qr;
        cudaGetDriverEntryPoint("cuTensorMapEncodeTiled", (void**)&enc, cudaEnableDefault, &qr);
        cudaGetSymbolAddress(&p_xn, g_xn);
        cudaGetSymbolAddress(&p_h, g_h);
        cudaGetSymbolAddress(&p_o, g_o);
        cudaFuncSetAttribute(k_gemm1, cudaFuncAttributeMaxDynamicSharedMemorySize, G1_SMEM);
        cudaFuncSetAttribute(k_attn, cudaFuncAttributeMaxDynamicSharedMemorySize, AT_SMEM);
        cudaFuncSetAttribute(k_gemm2, cudaFuncAttributeMaxDynamicSharedMemorySize, G2_SMEM);
    }
    const CUtensorMap tmXn = make_map(enc, p_xn, SEQ, DM, 128, 64, CU_TENSOR_MAP_SWIZZLE_128B);
    const CUtensorMap tmWqkv = make_map(enc, wqkv, DM, 3 * DM, 32, 64, CU_TENSOR_MAP_SWIZZLE_128B);
    const CUtensorMap tmW1 = make_map(enc, w1, DM, FF, 32, 64, CU_TENSOR_MAP_SWIZZLE_128B);
    const CUtensorMap tmH = make_map(enc, p_h, SEQ, FF, 64, 64, CU_TENSOR_MAP_SWIZZLE_128B);
    const CUtensorMap tmO = make_map(enc, p_o, SEQ, DM, 64, 64, CU_TENSOR_MAP_SWIZZLE_128B);
    const CUtensorMap tmWo = make_map(enc, wo, DM, DM, 64, 32, CU_TENSOR_MAP_SWIZZLE_64B);
    const CUtensorMap tmW2 = make_map(enc, w2, FF, DM, 64, 32, CU_TENSOR_MAP_SWIZZLE_64B);

    launch(k_ln, SEQ / 8, 256, 0, 1, false, x);
    launch(k_gemm1, 128, 384, G1_SMEM, 2, true, tmXn, tmWqkv, tmW1, tmH, b1);
    launch(k_attn, 128, 512, AT_SMEM, 1, true);
    launch(k_gemm2, 128, 160, G2_SMEM, 2, true, tmO, tmH, tmWo, tmW2, x, b2, out);
}
```

```cpp
#include <cuda_runtime.h>
#include <cuda_bf16.h>
#include <cuda.h>
#include <stdint.h>

namespace {

constexpr int SEQ = 2048, DM = 640, FF = 1536;
constexpr float LN_EPS = 1e-5f;

constexpr int IMG_BYTES = 256 * 384;
constexpr uint32_t EMU_MASK = 0xD5D5u;
constexpr float SAFE_BOUND = 80.0f;
constexpr float QSCALE = 0.22360679774997896f * 1.4426950408889634f;

__device__ __align__(1024) __nv_bfloat16 g_xn[SEQ * DM];
__device__ float g_r2[SEQ];
__device__ __align__(1024) uint8_t g_img[96 * IMG_BYTES + 1024];
__device__ float g_nrm[64 * SEQ];
__device__ __align__(1024) __nv_bfloat16 g_h[SEQ * FF];
__device__ __align__(1024) __nv_bfloat16 g_o[SEQ * DM];

#define TL(kern, slot) do { } while (0)
#define IT(row, i) do { } while (0)

__device__ __forceinline__ uint32_t smem_u32(const void* p) { return (uint32_t)__cvta_generic_to_shared(p); }
__device__ __forceinline__ void mbar_init(uint32_t bar, int cnt) {
    asm volatile("mbarrier.init.shared::cta.b64 [%0], %1;" ::"r"(bar), "r"(cnt));
}
__device__ __forceinline__ void mbar_expect_tx(uint32_t bar, uint32_t bytes) {
    asm volatile("mbarrier.arrive.expect_tx.shared::cta.b64 _, [%0], %1;" ::"r"(bar), "r"(bytes) : "memory");
}
__device__ __forceinline__ void mbar_wait(uint32_t bar, uint32_t parity) {
    asm volatile("{\n.reg .pred p;\n.reg .u32 n;\nmov.u32 n, 0;\n"
                 "WAIT_LOOP:\nmbarrier.try_wait.parity.shared::cta.b64 p, [%0], %1;\n@p bra WAIT_DONE;\n"
                 "add.u32 n, n, 1;\nsetp.lt.u32 p, n, 4194304;\n@p bra WAIT_LOOP;\nWAIT_DONE:\n}"
                 ::"r"(bar), "r"(parity) : "memory");
}
__device__ __forceinline__ void mbar_arrive(uint32_t bar) {
    asm volatile("mbarrier.arrive.shared::cta.b64 _, [%0];" ::"r"(bar) : "memory");
}
__device__ __forceinline__ void mbar_arrive_cluster(uint32_t bar, uint32_t cta) {
    asm volatile("{\n.reg .b32 ra;\nmapa.shared::cluster.u32 ra, %0, %1;\n"
                 "mbarrier.arrive.shared::cluster.b64 _, [ra];\n}" ::"r"(bar), "r"(cta) : "memory");
}
__device__ __forceinline__ void fence_barrier_init() { asm volatile("fence.mbarrier_init.release.cluster;" ::: "memory"); }
__device__ __forceinline__ void fence_proxy_async() { asm volatile("fence.proxy.async.shared::cta;" ::: "memory"); }
__device__ __forceinline__ void cluster_sync() {
    asm volatile("barrier.cluster.arrive.release.aligned;\nbarrier.cluster.wait.acquire.aligned;" ::: "memory");
}
__device__ __forceinline__ bool elect_one() {
    uint32_t pred;
    asm volatile("{\n.reg .pred p;\nelect.sync _|p, 0xFFFFFFFF;\nselp.b32 %0, 1, 0, p;\n}" : "=r"(pred));
    return pred != 0;
}
__device__ __forceinline__ void pdl_launch() { asm volatile("griddepcontrol.launch_dependents;" ::: "memory"); }
__device__ __forceinline__ void pdl_wait() { asm volatile("griddepcontrol.wait;" ::: "memory"); }
__device__ __forceinline__ void prefetch_map(const CUtensorMap* m) {
    asm volatile("prefetch.tensormap [%0];" ::"l"(m) : "memory");
}
__device__ __forceinline__ void tma_load(uint32_t dst, const CUtensorMap* m, int c0, int c1, uint32_t bar) {
    asm volatile("cp.async.bulk.tensor.2d.shared::cluster.global.mbarrier::complete_tx::bytes [%0], [%1, {%3, %4}], [%2];"
                 ::"r"(dst), "l"(m), "r"(bar), "r"(c0), "r"(c1) : "memory");
}
__device__ __forceinline__ void tma_load_mc(uint32_t dst, const CUtensorMap* m, int c0, int c1, uint32_t bar, uint16_t mask) {
    asm volatile("cp.async.bulk.tensor.2d.shared::cluster.global.mbarrier::complete_tx::bytes.multicast::cluster"
                 " [%0], [%1, {%3, %4}], [%2], %5;"
                 ::"r"(dst), "l"(m), "r"(bar), "r"(c0), "r"(c1), "h"(mask) : "memory");
}
__device__ __forceinline__ void tma_store(const CUtensorMap* m, uint32_t src, int c0, int c1) {
    asm volatile("cp.async.bulk.tensor.2d.global.shared::cta.bulk_group [%0, {%2, %3}], [%1];"
                 ::"l"(m), "r"(src), "r"(c0), "r"(c1) : "memory");
}
__device__ __forceinline__ void bulk_commit() { asm volatile("cp.async.bulk.commit_group;" ::: "memory"); }
__device__ __forceinline__ void bulk_wait_all() { asm volatile("cp.async.bulk.wait_group 0;" ::: "memory"); }
__device__ __forceinline__ void bulk_load(uint32_t dst, const void* src, uint32_t bytes, uint32_t bar) {
    asm volatile("cp.async.bulk.shared::cluster.global.mbarrier::complete_tx::bytes [%0], [%1], %2, [%3];"
                 ::"r"(dst), "l"(src), "r"(bytes), "r"(bar) : "memory");
}
__device__ __forceinline__ void prefetch_l2(const void* p, uint32_t bytes) {
    asm volatile("cp.async.bulk.prefetch.L2.global [%0], %1;" ::"l"(p), "r"(bytes) : "memory");
}
__device__ __forceinline__ void wg_fence() { asm volatile("wgmma.fence.sync.aligned;" ::: "memory"); }
__device__ __forceinline__ void wg_commit() { asm volatile("wgmma.commit_group.sync.aligned;" ::: "memory"); }
template <int N> __device__ __forceinline__ void wg_wait() {
    asm volatile("wgmma.wait_group.sync.aligned %0;" ::"n"(N) : "memory");
}
template <int N> __device__ __forceinline__ void reg_alloc() { asm volatile("setmaxnreg.inc.sync.aligned.u32 %0;" ::"n"(N)); }
template <int N> __device__ __forceinline__ void reg_dealloc() { asm volatile("setmaxnreg.dec.sync.aligned.u32 %0;" ::"n"(N)); }
template <int N> __device__ __forceinline__ void fence_regs(float (&d)[N]) {
#pragma unroll
    for (int i = 0; i < N; i++) asm volatile("" : "+f"(d[i])::"memory");
}
__device__ __forceinline__ uint64_t make_desc(uint32_t addr, uint32_t lbo, uint32_t sbo, uint32_t swz) {
    return (uint64_t)((addr & 0x3FFFF) >> 4) | ((uint64_t)(lbo >> 4) << 16) | ((uint64_t)(sbo >> 4) << 32) |
           ((uint64_t)swz << 62);
}
__device__ __forceinline__ uint32_t pack_bf16(float lo, float hi) {
    uint32_t r;
    asm("cvt.rn.bf16x2.f32 %0, %1, %2;" : "=r"(r) : "f"(hi), "f"(lo));
    return r;
}
__device__ __forceinline__ float ex2(float x) {
    float r;
    asm("ex2.approx.ftz.f32 %0, %1;" : "=f"(r) : "f"(x));
    return r;
}
__device__ __forceinline__ float bf_lo(uint32_t v) { return __uint_as_float(v << 16); }
__device__ __forceinline__ float bf_hi(uint32_t v) { return __uint_as_float(v & 0xFFFF0000u); }
__device__ __forceinline__ void stmatrix_x4(uint32_t addr, uint32_t r0, uint32_t r1, uint32_t r2, uint32_t r3) {
    asm volatile("stmatrix.sync.aligned.m8n8.x4.shared.b16 [%0], {%1, %2, %3, %4};"
                 ::"r"(addr), "r"(r0), "r"(r1), "r"(r2), "r"(r3) : "memory");
}

__device__ __forceinline__ void wgmma_n120_ss_tb(float (&d)[60], uint64_t descA, uint64_t descB, int scaleD) {
    asm volatile("{\n.reg .pred p;\nsetp.ne.b32 p, %62, 0;\n"
        "wgmma.mma_async.sync.aligned.m64n120k16.f32.bf16.bf16 {"
        "%0, %1, %2, %3, %4, %5, %6, %7, %8, %9, %10, %11, %12, %13, %14, %15, "
        "%16, %17, %18, %19, %20, %21, %22, %23, %24, %25, %26, %27, %28, %29, %30, %31, "
        "%32, %33, %34, %35, %36, %37, %38, %39, %40, %41, %42, %43, %44, %45, %46, %47, "
        "%48, %49, %50, %51, %52, %53, %54, %55, %56, %57, %58, %59}, "
        "%60, %61, p, 1, 1, 0, 1;\n}\n"
        : "+f"(d[0]), "+f"(d[1]), "+f"(d[2]), "+f"(d[3]), "+f"(d[4]), "+f"(d[5]), "+f"(d[6]), "+f"(d[7]),
          "+f"(d[8]), "+f"(d[9]), "+f"(d[10]), "+f"(d[11]), "+f"(d[12]), "+f"(d[13]), "+f"(d[14]), "+f"(d[15]),
          "+f"(d[16]), "+f"(d[17]), "+f"(d[18]), "+f"(d[19]), "+f"(d[20]), "+f"(d[21]), "+f"(d[22]), "+f"(d[23]),
          "+f"(d[24]), "+f"(d[25]), "+f"(d[26]), "+f"(d[27]), "+f"(d[28]), "+f"(d[29]), "+f"(d[30]), "+f"(d[31]),
          "+f"(d[32]), "+f"(d[33]), "+f"(d[34]), "+f"(d[35]), "+f"(d[36]), "+f"(d[37]), "+f"(d[38]), "+f"(d[39]),
          "+f"(d[40]), "+f"(d[41]), "+f"(d[42]), "+f"(d[43]), "+f"(d[44]), "+f"(d[45]), "+f"(d[46]), "+f"(d[47]),
          "+f"(d[48]), "+f"(d[49]), "+f"(d[50]), "+f"(d[51]), "+f"(d[52]), "+f"(d[53]), "+f"(d[54]), "+f"(d[55]),
          "+f"(d[56]), "+f"(d[57]), "+f"(d[58]), "+f"(d[59])
        : "l"(descA), "l"(descB), "r"(scaleD));
}

__device__ __forceinline__ void wgmma_n96_ss_tb(float (&d)[48], uint64_t descA, uint64_t descB, int scaleD) {
    asm volatile("{\n.reg .pred p;\nsetp.ne.b32 p, %50, 0;\n"
        "wgmma.mma_async.sync.aligned.m64n96k16.f32.bf16.bf16 {"
        "%0, %1, %2, %3, %4, %5, %6, %7, %8, %9, %10, %11, %12, %13, %14, %15, "
        "%16, %17, %18, %19, %20, %21, %22, %23, %24, %25, %26, %27, %28, %29, %30, %31, "
        "%32, %33, %34, %35, %36, %37, %38, %39, %40, %41, %42, %43, %44, %45, %46, %47}, "
        "%48, %49, p, 1, 1, 0, 1;\n}\n"
        : "+f"(d[0]), "+f"(d[1]), "+f"(d[2]), "+f"(d[3]), "+f"(d[4]), "+f"(d[5]), "+f"(d[6]), "+f"(d[7]),
          "+f"(d[8]), "+f"(d[9]), "+f"(d[10]), "+f"(d[11]), "+f"(d[12]), "+f"(d[13]), "+f"(d[14]), "+f"(d[15]),
          "+f"(d[16]), "+f"(d[17]), "+f"(d[18]), "+f"(d[19]), "+f"(d[20]), "+f"(d[21]), "+f"(d[22]), "+f"(d[23]),
          "+f"(d[24]), "+f"(d[25]), "+f"(d[26]), "+f"(d[27]), "+f"(d[28]), "+f"(d[29]), "+f"(d[30]), "+f"(d[31]),
          "+f"(d[32]), "+f"(d[33]), "+f"(d[34]), "+f"(d[35]), "+f"(d[36]), "+f"(d[37]), "+f"(d[38]), "+f"(d[39]),
          "+f"(d[40]), "+f"(d[41]), "+f"(d[42]), "+f"(d[43]), "+f"(d[44]), "+f"(d[45]), "+f"(d[46]), "+f"(d[47])
        : "l"(descA), "l"(descB), "r"(scaleD));
}

__device__ __forceinline__ void wgmma_n96_ss_tb_z(float (&d)[48], uint64_t descA, uint64_t descB) {
    asm volatile("{\n.reg .pred p;\nsetp.ne.b32 p, 0, 0;\n"
        "wgmma.mma_async.sync.aligned.m64n96k16.f32.bf16.bf16 {"
        "%0, %1, %2, %3, %4, %5, %6, %7, %8, %9, %10, %11, %12, %13, %14, %15, "
        "%16, %17, %18, %19, %20, %21, %22, %23, %24, %25, %26, %27, %28, %29, %30, %31, "
        "%32, %33, %34, %35, %36, %37, %38, %39, %40, %41, %42, %43, %44, %45, %46, %47}, "
        "%48, %49, p, 1, 1, 0, 1;\n}\n"
        : "=f"(d[0]), "=f"(d[1]), "=f"(d[2]), "=f"(d[3]), "=f"(d[4]), "=f"(d[5]), "=f"(d[6]), "=f"(d[7]),
          "=f"(d[8]), "=f"(d[9]), "=f"(d[10]), "=f"(d[11]), "=f"(d[12]), "=f"(d[13]), "=f"(d[14]), "=f"(d[15]),
          "=f"(d[16]), "=f"(d[17]), "=f"(d[18]), "=f"(d[19]), "=f"(d[20]), "=f"(d[21]), "=f"(d[22]), "=f"(d[23]),
          "=f"(d[24]), "=f"(d[25]), "=f"(d[26]), "=f"(d[27]), "=f"(d[28]), "=f"(d[29]), "=f"(d[30]), "=f"(d[31]),
          "=f"(d[32]), "=f"(d[33]), "=f"(d[34]), "=f"(d[35]), "=f"(d[36]), "=f"(d[37]), "=f"(d[38]), "=f"(d[39]),
          "=f"(d[40]), "=f"(d[41]), "=f"(d[42]), "=f"(d[43]), "=f"(d[44]), "=f"(d[45]), "=f"(d[46]), "=f"(d[47])
        : "l"(descA), "l"(descB));
}

__device__ __forceinline__ void wgmma_n160_ss_tb(float (&d)[80], uint64_t descA, uint64_t descB, int scaleD) {
    asm volatile("{\n.reg .pred p;\nsetp.ne.b32 p, %82, 0;\n"
        "wgmma.mma_async.sync.aligned.m64n160k16.f32.bf16.bf16 {"
        "%0, %1, %2, %3, %4, %5, %6, %7, %8, %9, %10, %11, %12, %13, %14, %15, "
        "%16, %17, %18, %19, %20, %21, %22, %23, %24, %25, %26, %27, %28, %29, %30, %31, "
        "%32, %33, %34, %35, %36, %37, %38, %39, %40, %41, %42, %43, %44, %45, %46, %47, "
        "%48, %49, %50, %51, %52, %53, %54, %55, %56, %57, %58, %59, %60, %61, %62, %63, "
        "%64, %65, %66, %67, %68, %69, %70, %71, %72, %73, %74, %75, %76, %77, %78, %79}, "
        "%80, %81, p, 1, 1, 0, 1;\n}\n"
        : "+f"(d[0]), "+f"(d[1]), "+f"(d[2]), "+f"(d[3]), "+f"(d[4]), "+f"(d[5]), "+f"(d[6]), "+f"(d[7]),
          "+f"(d[8]), "+f"(d[9]), "+f"(d[10]), "+f"(d[11]), "+f"(d[12]), "+f"(d[13]), "+f"(d[14]), "+f"(d[15]),
          "+f"(d[16]), "+f"(d[17]), "+f"(d[18]), "+f"(d[19]), "+f"(d[20]), "+f"(d[21]), "+f"(d[22]), "+f"(d[23]),
          "+f"(d[24]), "+f"(d[25]), "+f"(d[26]), "+f"(d[27]), "+f"(d[28]), "+f"(d[29]), "+f"(d[30]), "+f"(d[31]),
          "+f"(d[32]), "+f"(d[33]), "+f"(d[34]), "+f"(d[35]), "+f"(d[36]), "+f"(d[37]), "+f"(d[38]), "+f"(d[39]),
          "+f"(d[40]), "+f"(d[41]), "+f"(d[42]), "+f"(d[43]), "+f"(d[44]), "+f"(d[45]), "+f"(d[46]), "+f"(d[47]),
          "+f"(d[48]), "+f"(d[49]), "+f"(d[50]), "+f"(d[51]), "+f"(d[52]), "+f"(d[53]), "+f"(d[54]), "+f"(d[55]),
          "+f"(d[56]), "+f"(d[57]), "+f"(d[58]), "+f"(d[59]), "+f"(d[60]), "+f"(d[61]), "+f"(d[62]), "+f"(d[63]),
          "+f"(d[64]), "+f"(d[65]), "+f"(d[66]), "+f"(d[67]), "+f"(d[68]), "+f"(d[69]), "+f"(d[70]), "+f"(d[71]),
          "+f"(d[72]), "+f"(d[73]), "+f"(d[74]), "+f"(d[75]), "+f"(d[76]), "+f"(d[77]), "+f"(d[78]), "+f"(d[79])
        : "l"(descA), "l"(descB), "r"(scaleD));
}

__device__ __forceinline__ void wgmma_n64_rs(float (&d)[32], uint32_t a0, uint32_t a1, uint32_t a2, uint32_t a3, uint64_t descB, int scaleD) {
    asm volatile("{\n.reg .pred p;\nsetp.ne.b32 p, %37, 0;\n"
        "wgmma.mma_async.sync.aligned.m64n64k16.f32.bf16.bf16 {"
        "%0, %1, %2, %3, %4, %5, %6, %7, %8, %9, %10, %11, %12, %13, %14, %15, "
        "%16, %17, %18, %19, %20, %21, %22, %23, %24, %25, %26, %27, %28, %29, %30, %31}, "
        "{%32, %33, %34, %35}, %36, p, 1, 1, 0;\n}\n"
        : "+f"(d[0]), "+f"(d[1]), "+f"(d[2]), "+f"(d[3]), "+f"(d[4]), "+f"(d[5]), "+f"(d[6]), "+f"(d[7]),
          "+f"(d[8]), "+f"(d[9]), "+f"(d[10]), "+f"(d[11]), "+f"(d[12]), "+f"(d[13]), "+f"(d[14]), "+f"(d[15]),
          "+f"(d[16]), "+f"(d[17]), "+f"(d[18]), "+f"(d[19]), "+f"(d[20]), "+f"(d[21]), "+f"(d[22]), "+f"(d[23]),
          "+f"(d[24]), "+f"(d[25]), "+f"(d[26]), "+f"(d[27]), "+f"(d[28]), "+f"(d[29]), "+f"(d[30]), "+f"(d[31])
        : "r"(a0), "r"(a1), "r"(a2), "r"(a3), "l"(descB), "r"(scaleD));
}

__device__ __forceinline__ void wgmma_n64_rs_z(float (&d)[32], uint32_t a0, uint32_t a1, uint32_t a2, uint32_t a3, uint64_t descB) {
    asm volatile("{\n.reg .pred p;\nsetp.ne.b32 p, 0, 0;\n"
        "wgmma.mma_async.sync.aligned.m64n64k16.f32.bf16.bf16 {"
        "%0, %1, %2, %3, %4, %5, %6, %7, %8, %9, %10, %11, %12, %13, %14, %15, "
        "%16, %17, %18, %19, %20, %21, %22, %23, %24, %25, %26, %27, %28, %29, %30, %31}, "
        "{%32, %33, %34, %35}, %36, p, 1, 1, 0;\n}\n"
        : "=f"(d[0]), "=f"(d[1]), "=f"(d[2]), "=f"(d[3]), "=f"(d[4]), "=f"(d[5]), "=f"(d[6]), "=f"(d[7]),
          "=f"(d[8]), "=f"(d[9]), "=f"(d[10]), "=f"(d[11]), "=f"(d[12]), "=f"(d[13]), "=f"(d[14]), "=f"(d[15]),
          "=f"(d[16]), "=f"(d[17]), "=f"(d[18]), "=f"(d[19]), "=f"(d[20]), "=f"(d[21]), "=f"(d[22]), "=f"(d[23]),
          "=f"(d[24]), "=f"(d[25]), "=f"(d[26]), "=f"(d[27]), "=f"(d[28]), "=f"(d[29]), "=f"(d[30]), "=f"(d[31])
        : "r"(a0), "r"(a1), "r"(a2), "r"(a3), "l"(descB));
}

__device__ __forceinline__ void wgmma_n24_rs_tb(float (&d)[12], uint32_t a0, uint32_t a1, uint32_t a2, uint32_t a3, uint64_t descB, int scaleD) {
    asm volatile("{\n.reg .pred p;\nsetp.ne.b32 p, %17, 0;\n"
        "wgmma.mma_async.sync.aligned.m64n24k16.f32.bf16.bf16 {"
        "%0, %1, %2, %3, %4, %5, %6, %7, %8, %9, %10, %11}, "
        "{%12, %13, %14, %15}, %16, p, 1, 1, 1;\n}\n"
        : "+f"(d[0]), "+f"(d[1]), "+f"(d[2]), "+f"(d[3]), "+f"(d[4]), "+f"(d[5]), "+f"(d[6]), "+f"(d[7]),
          "+f"(d[8]), "+f"(d[9]), "+f"(d[10]), "+f"(d[11])
        : "r"(a0), "r"(a1), "r"(a2), "r"(a3), "l"(descB), "r"(scaleD));
}

__global__ void __launch_bounds__(256) k_ln(const __nv_bfloat16* __restrict__ x, const uint8_t* __restrict__ wqkv,
                                            const uint8_t* __restrict__ w1, const uint8_t* __restrict__ w2,
                                            const uint8_t* __restrict__ wo) {
    if (threadIdx.x == 0) TL(0, 0);
    pdl_launch();
    const int lane = threadIdx.x & 31;
    const int row = blockIdx.x * 8 + (threadIdx.x >> 5);
    const uint2* src = reinterpret_cast<const uint2*>(x + (size_t)row * DM);
    uint2 v[5];
#pragma unroll
    for (int i = 0; i < 5; i++) v[i] = __ldg(src + lane + 32 * i);
    if (threadIdx.x == 0) {
        prefetch_l2(wqkv + blockIdx.x * 9600, 9600);
        prefetch_l2(w1 + blockIdx.x * 7680, 7680);
        prefetch_l2(w2 + blockIdx.x * 7680, 7680);
        prefetch_l2(wo + blockIdx.x * 3200, 3200);
    }
    float f[20];
#pragma unroll
    for (int i = 0; i < 5; i++) {
        f[4 * i] = bf_lo(v[i].x); f[4 * i + 1] = bf_hi(v[i].x);
        f[4 * i + 2] = bf_lo(v[i].y); f[4 * i + 3] = bf_hi(v[i].y);
    }
    float s = 0.f;
#pragma unroll
    for (int i = 0; i < 20; i++) s += f[i];
#pragma unroll
    for (int o = 16; o; o >>= 1) s += __shfl_xor_sync(~0u, s, o);
    const float mu = s * (1.f / DM);
    float q = 0.f;
#pragma unroll
    for (int i = 0; i < 20; i++) { f[i] -= mu; q += f[i] * f[i]; }
#pragma unroll
    for (int o = 16; o; o >>= 1) q += __shfl_xor_sync(~0u, q, o);
    const float var = q * (1.f / DM);
    const float r1 = 1.f / sqrtf(var + LN_EPS);
    uint2* dst = reinterpret_cast<uint2*>(g_xn + (size_t)row * DM);
#pragma unroll
    for (int i = 0; i < 5; i++) {
        uint2 w;
        w.x = pack_bf16(f[4 * i] * r1, f[4 * i + 1] * r1);
        w.y = pack_bf16(f[4 * i + 2] * r1, f[4 * i + 3] * r1);
        dst[lane + 32 * i] = w;
    }
    if (lane == 0) g_r2[row] = 1.f / sqrtf(var * r1 * r1 + LN_EPS);
    if (threadIdx.x == 0) TL(0, 3);
}

constexpr int G1_A_BYTES = 10 * 16384;
constexpr int G1_RING = 65536;
constexpr int G1_BIAS_OFF = G1_A_BYTES + G1_RING;
constexpr int G1_BAR_OFF = G1_BIAS_OFF + 512;
constexpr int G1_SMEM = G1_BAR_OFF + 256;

__device__ __forceinline__ float gelu_tanh(float x) {
    const float u = x * (0.7978845608028654f + 0.035677408136300125f * x * x);
    float t;
    asm("tanh.approx.f32 %0, %1;" : "=f"(t) : "f"(u));
    const float h = 0.5f * x;
    return fmaf(h, t, h);
}
__device__ __forceinline__ void release_stage(uint32_t bar, uint32_t peer, int lane) {
    if (lane == 0) { mbar_arrive(bar); mbar_arrive_cluster(bar, peer); }
}

__global__ void __launch_bounds__(544, 1) __cluster_dims__(2, 1, 1)
k_gemm1(const __grid_constant__ CUtensorMap tmA, const __grid_constant__ CUtensorMap tmWqkv,
        const __grid_constant__ CUtensorMap tmW1, const __grid_constant__ CUtensorMap tmHst,
        const __nv_bfloat16* __restrict__ b1) {
    extern __shared__ __align__(1024) uint8_t smem[];
    const uint32_t sbase = smem_u32(smem);
    const uint32_t sA = sbase, sB = sbase + G1_A_BYTES;
    const uint32_t barA = sbase + G1_BAR_OFF, full1 = barA + 80, empty1 = full1 + 32, full2 = empty1 + 32, empty2 = full2 + 40;
    const int warp = __shfl_sync(~0u, threadIdx.x >> 5, 0), lane = threadIdx.x & 31;
    const uint32_t rank = blockIdx.x & 1;
    const int cl = blockIdx.x >> 1, cg = cl & 7, rb = (cl >> 3) * 2 + rank;

    if (threadIdx.x == 0) TL(1, 0);
    pdl_launch();
    if (threadIdx.x == 0) {
        for (int i = 0; i < 10; i++) mbar_init(barA + i * 8, 1);
        for (int i = 0; i < 4; i++) { mbar_init(full1 + i * 8, 1); mbar_init(empty1 + i * 8, 32); }
        for (int i = 0; i < 5; i++) { mbar_init(full2 + i * 8, 1); mbar_init(empty2 + i * 8, 32); }
        fence_barrier_init();
    }
    if (threadIdx.x < 96)
        reinterpret_cast<uint32_t*>(smem + G1_BIAS_OFF)[threadIdx.x] = __ldg(reinterpret_cast<const uint32_t*>(b1 + cg * 192) + threadIdx.x);
    __syncthreads();
    cluster_sync();

    if (warp == 16) {
        if (elect_one()) { prefetch_map(&tmA); prefetch_map(&tmWqkv); prefetch_map(&tmW1); prefetch_map(&tmHst); }
#pragma unroll 1
        for (int it = 0; it < 20; it++) {
            const int s = it & 3;
            if (lane == 0) IT(2, it);
            if (it >= 4) mbar_wait(empty1 + s * 8, ((it >> 2) - 1) & 1);
            if (lane == 0) IT(3, it);
            if (elect_one()) {
                const uint32_t dst = sB + s * 16384 + rank * 8192, bar = full1 + s * 8;
                const int c0 = cg * 240 + rank * 120;
                mbar_expect_tx(bar, 16384);
                tma_load_mc(dst, &tmWqkv, c0, it * 32, bar, 3);
                tma_load_mc(dst + 4096, &tmWqkv, c0 + 64, it * 32, bar, 3);
            }
            __syncwarp();
            if (it == 0) pdl_wait();
            if (!(it & 1) && elect_one()) {
                const int kb = it >> 1;
                mbar_expect_tx(barA + kb * 8, 16384);
                tma_load(sA + kb * 16384, &tmA, kb * 64, rb * 128, barA + kb * 8);
            }
            __syncwarp();
        }
#pragma unroll 1
        for (int it = 0; it < 20; it++) {
            const int s = it % 5;
            if (lane == 0) IT(2, 20 + it);
            if (it < 5) { if (it != 3) mbar_wait(empty1 + (it == 4 ? 3 : it) * 8, 0); }
            else mbar_wait(empty2 + s * 8, ((it / 5) - 1) & 1);
            if (lane == 0) IT(3, 20 + it);
            if (elect_one()) {
                const uint32_t dst = sB + s * 12288 + rank * 6144, bar = full2 + s * 8;
                const int c0 = cg * 192 + rank * 96;
                mbar_expect_tx(bar, 12288);
#pragma unroll
                for (int b = 0; b < 3; b++) tma_load_mc(dst + b * 2048, &tmW1, c0 + b * 32, it * 32, bar, 3);
            }
            __syncwarp();
        }
    } else {
        const int wgi = warp >> 2, wi = wgi & 1, wj = wgi >> 1, w4 = warp & 3;
        const int g = lane >> 2, c = lane & 3;
        const int row0 = rb * 128 + wi * 64 + w4 * 16 + g;
        const uint32_t sAw = sA + wi * 8192;
        const uint32_t peer = rank ^ 1;
        uint32_t pend[36];
        const int rbk = row0 >> 3;
        const int hs0 = cg * 12 + wj * 6;
        {
            float acc[60];
#pragma unroll 1
            for (int it = 0; it < 20; it++) {
                const int s = it & 3;
                if (!(it & 1)) mbar_wait(barA + (it >> 1) * 8, 0);
                if (threadIdx.x == 0) IT(0, it);
                mbar_wait(full1 + s * 8, (it >> 2) & 1);
                if (threadIdx.x == 0) IT(1, it);
                wg_fence();
                const uint64_t dA = make_desc(sAw + (it >> 1) * 16384 + (it & 1) * 64, 16, 1024, 1);
                const uint64_t dB = make_desc(sB + s * 16384 + wj * 8192, 4096, 1024, 1);
                wgmma_n120_ss_tb(acc, dA, dB, it > 0);
                wgmma_n120_ss_tb(acc, dA + 2, dB + 128, 1);
                wg_commit();
                if (it > 0) { wg_wait<1>(); release_stage(empty1 + ((it - 1) & 3) * 8, peer, lane); }
            }
            wg_wait<0>();
            release_stage(empty1 + 3 * 8, peer, lane);
            fence_regs(acc);
            if (threadIdx.x == 0) TL(1, 1);
            const bool emu0 = (EMU_MASK >> (rbk & 15)) & 1, emu1 = (EMU_MASK >> ((rbk + 1) & 15)) & 1;
            const bool low = c < 2;
#pragma unroll
            for (int m = 0; m < 3; m++) {
                const int hs = hs0 + 2 * m, which = hs >> 5;
                const float* a = acc + 20 * m;
                float m0, m1;
                uint32_t pad0, pad1;
                if (which == 0) { m0 = m1 = QSCALE; pad0 = pad1 = 0x3F803F80u; }
                else if (which == 1) {
                    m0 = emu0 ? 2.f : 1.f; m1 = emu1 ? 2.f : 1.f;
                    pad0 = emu0 ? 0xBFFF4440u : 0u; pad1 = emu1 ? 0xBFFF4440u : 0u;
                } else { m0 = m1 = 1.f; pad0 = pad1 = 0x00003F80u; }
                const uint32_t mid0 = pack_bf16(a[8] * m0, a[9] * m0), mid1 = pack_bf16(a[10] * m1, a[11] * m1);
                const uint32_t p0 = (c & 1) ? 0u : pad0, p1 = (c & 1) ? 0u : pad1;
                uint32_t* o = pend + 12 * m;
                o[0] = pack_bf16(a[0] * m0, a[1] * m0);   o[1] = pack_bf16(a[4] * m0, a[5] * m0);   o[2] = low ? mid0 : p0;
                o[3] = pack_bf16(a[2] * m1, a[3] * m1);   o[4] = pack_bf16(a[6] * m1, a[7] * m1);   o[5] = low ? mid1 : p1;
                o[6] = pack_bf16(a[12] * m0, a[13] * m0); o[7] = pack_bf16(a[16] * m0, a[17] * m0); o[8] = low ? p0 : mid0;
                o[9] = pack_bf16(a[14] * m1, a[15] * m1); o[10] = pack_bf16(a[18] * m1, a[19] * m1); o[11] = low ? p1 : mid1;
                if (which < 2) {
                    const float u0 = a[8] * a[8] + a[9] * a[9], u1 = a[10] * a[10] + a[11] * a[11];
                    float e0 = a[0] * a[0] + a[1] * a[1] + a[4] * a[4] + a[5] * a[5] + (low ? u0 : 0.f);
                    float e1 = a[2] * a[2] + a[3] * a[3] + a[6] * a[6] + a[7] * a[7] + (low ? u1 : 0.f);
                    float o0 = a[12] * a[12] + a[13] * a[13] + a[16] * a[16] + a[17] * a[17] + (low ? 0.f : u0);
                    float o1 = a[14] * a[14] + a[15] * a[15] + a[18] * a[18] + a[19] * a[19] + (low ? 0.f : u1);
                    const bool b0 = c & 1, b1_ = c & 2;
                    const float x0 = (b0 ? e1 : e0) + __shfl_xor_sync(~0u, b0 ? e0 : e1, 1);
                    const float x1 = (b0 ? o1 : o0) + __shfl_xor_sync(~0u, b0 ? o0 : o1, 1);
                    float y = (b1_ ? x1 : x0) + __shfl_xor_sync(~0u, b1_ ? x0 : x1, 2);
                    if (which == 0) y *= QSCALE * QSCALE;
                    g_nrm[(hs + (c >> 1)) * SEQ + row0 + (c & 1) * 8] = y;
                }
            }
        }
        {
            float acc[48];
            uint8_t* img = g_img + (size_t)hs0 * IMG_BYTES + rbk * 384 + g * 16 + c * 4;
#pragma unroll
            for (int it = 0; it < 20; it++) {
                const int s = it % 5;
                if (threadIdx.x == 0) IT(0, 20 + it);
                mbar_wait(full2 + s * 8, (it / 5) & 1);
                if (threadIdx.x == 0) IT(1, 20 + it);
                wg_fence();
                const uint64_t dA = make_desc(sAw + (it >> 1) * 16384 + (it & 1) * 64, 16, 1024, 1);
                const uint64_t dB = make_desc(sB + s * 12288 + wj * 6144, 2048, 512, 2);
                if (it == 0) wgmma_n96_ss_tb_z(acc, dA, dB); else wgmma_n96_ss_tb(acc, dA, dB, 1);
                wgmma_n96_ss_tb(acc, dA + 2, dB + 64, 1);
                wg_commit();
                if (it < 18) {
#pragma unroll
                    for (int u = 2 * it; u < 2 * it + 2; u++) {
                        const int m = u / 12, r = u % 12;
                        const int off = (2 * m + r / 6) * IMG_BYTES + ((r % 6) / 3) * 384 + (r % 3) * 128;
                        *(uint32_t*)(img + off) = pend[u];
                    }
                }
                if (it > 0) { wg_wait<1>(); if (it <= 15) release_stage(empty2 + ((it - 1) % 5) * 8, peer, lane); }
            }
            wg_wait<0>();
            fence_regs(acc);
            if (threadIdx.x == 0) TL(1, 2);
            const float r0 = g_r2[row0], r1 = g_r2[row0 + 8];
            const uint32_t* bias = reinterpret_cast<const uint32_t*>(smem + G1_BIAS_OFF) + wj * 48 + c;
            asm volatile("bar.sync %0, 256;" ::"r"(wi + 1) : "memory");
            const int mrow = w4 * 16 + (lane & 15);
            const uint32_t stage = sAw + wj * 3 * 16384;
            const uint32_t st_row = stage + mrow * 64;
#pragma unroll
            for (int j = 0; j < 12; j += 2) {
                const uint32_t bA = bias[j * 4], bB = bias[j * 4 + 4];
                const float* a = acc + j * 4;
                const uint32_t r00 = pack_bf16(gelu_tanh(fmaf(a[0], r0, bf_lo(bA))), gelu_tanh(fmaf(a[1], r0, bf_hi(bA))));
                const uint32_t r10 = pack_bf16(gelu_tanh(fmaf(a[2], r1, bf_lo(bA))), gelu_tanh(fmaf(a[3], r1, bf_hi(bA))));
                const uint32_t r01 = pack_bf16(gelu_tanh(fmaf(a[4], r0, bf_lo(bB))), gelu_tanh(fmaf(a[5], r0, bf_hi(bB))));
                const uint32_t r11 = pack_bf16(gelu_tanh(fmaf(a[6], r1, bf_lo(bB))), gelu_tanh(fmaf(a[7], r1, bf_hi(bB))));
                const int chunk = (j & 3) + (lane >> 4);
                stmatrix_x4(st_row + (j >> 2) * 16384 + ((chunk ^ ((mrow >> 1) & 3)) << 4), r00, r10, r01, r11);
            }
            fence_proxy_async();
            asm volatile("bar.sync %0, 128;" ::"r"(wgi + 3) : "memory");
            if (w4 == 0 && elect_one()) {
#pragma unroll
                for (int b = 0; b < 3; b++)
                    tma_store(&tmHst, stage + b * 16384, cg * 192 + wj * 96 + b * 32, rb * 128 + wi * 64);
                bulk_commit();
                bulk_wait_all();
            }
        }
    }
    __syncthreads();
    if (threadIdx.x == 0) TL(1, 3);
    cluster_sync();
}

constexpr int AT_BAR_OFF = 2 * IMG_BYTES;
constexpr int AT_SMEM = AT_BAR_OFF + 512;

__device__ __forceinline__ uint32_t bf2_fma(uint32_t a, uint32_t b, uint32_t c) {
    uint32_t r;
    asm("fma.rn.bf16x2 %0, %1, %2, %3;" : "=r"(r) : "r"(a), "r"(b), "r"(c));
    return r;
}
__device__ __forceinline__ uint32_t lop_and_or(uint32_t a, uint32_t m, uint32_t o) {
    uint32_t r;
    asm("lop3.b32 %0, %1, %2, %3, 0xEA;" : "=r"(r) : "r"(a), "r"(m), "r"(o));
    return r;
}
struct ExpConst { uint32_t mask, slope; };
__device__ __forceinline__ ExpConst make_exp_const() {
    ExpConst k;
    asm volatile("mov.b32 %0, 0x007F007F;" : "=r"(k.mask));
    asm volatile("mov.b32 %0, 0x3EF83EF8;" : "=r"(k.slope));
    return k;
}
__device__ __forceinline__ uint32_t exp2_pair_fma(float t0, float t1, const ExpConst& k) {
    const uint32_t L = __byte_perm(__float_as_uint(t0), __float_as_uint(t1), 0x6521);
    const uint32_t g = lop_and_or(L, k.mask, 0x3F803F80u);
    const uint32_t u = bf2_fma(g, k.slope, 0xBF37BF37u);
    const uint32_t e = bf2_fma(u, u, 0xBD71BD71u);
    return bf2_fma(L, e, L);
}
template <int SHIFT>
__device__ __forceinline__ void exp_tile(const float (&s)[32], uint32_t (&p)[16], const ExpConst& k) {
#pragma unroll
    for (int b = 0; b < 8; b++) {
        if ((EMU_MASK >> (b + SHIFT)) & 1) {
            p[2 * b] = exp2_pair_fma(s[4 * b], s[4 * b + 1], k);
            p[2 * b + 1] = exp2_pair_fma(s[4 * b + 2], s[4 * b + 3], k);
        } else {
            p[2 * b] = pack_bf16(ex2(s[4 * b]), ex2(s[4 * b + 1]));
            p[2 * b + 1] = pack_bf16(ex2(s[4 * b + 2]), ex2(s[4 * b + 3]));
        }
    }
}
struct QFrag { uint32_t q0, q1, q2, q3, q4, q5; };
__device__ __forceinline__ QFrag load_q(int h, int rbase, int g, int c) {
    const uint8_t* gq = g_img + (size_t)h * IMG_BYTES + (rbase >> 3) * 384 + g * 16 + c * 4;
    QFrag q;
    q.q0 = *(const uint32_t*)(gq); q.q1 = *(const uint32_t*)(gq + 384);
    q.q2 = *(const uint32_t*)(gq + 128); q.q3 = *(const uint32_t*)(gq + 512);
    q.q4 = *(const uint32_t*)(gq + 256); q.q5 = *(const uint32_t*)(gq + 640);
    return q;
}
__device__ __forceinline__ void qk_tile(float (&s)[32], const QFrag& q, uint64_t dK) {
    wg_fence();
    wgmma_n64_rs_z(s, q.q0, q.q1, q.q2, q.q3, dK);
    wgmma_n64_rs(s, q.q4, q.q5, 0u, 0u, dK + 16, 1);
    wg_commit();
}
__device__ __forceinline__ void pv_tile(float (&o)[12], const uint32_t (&p)[16], uint64_t dV) {
    wg_fence();
#pragma unroll
    for (int ks = 0; ks < 4; ks++)
        wgmma_n24_rs_tb(o, p[4 * ks], p[4 * ks + 1], p[4 * ks + 2], p[4 * ks + 3], dV + ks * 48, 1);
    wg_commit();
}
__device__ __forceinline__ void store_o(const float (&o)[12], int h, int rbase, int lane) {
    const int g = lane >> 2, c = lane & 3;
    const bool odd = h & 1;
    const int lsrc = (lane & ~3) | (odd ? 0 : 2);
    const float i0 = 1.f / __shfl_sync(~0u, o[8], lsrc), i1 = 1.f / __shfl_sync(~0u, o[10], lsrc);
    __nv_bfloat16* dst = g_o + (size_t)(rbase + g) * DM + h * 20;
    const int d0 = (odd ? 4 : 0) + 2 * c, d1 = d0 + 8, d2 = odd ? 2 * c - 4 : 16 + 2 * c;
    *(uint32_t*)(dst + d0) = pack_bf16(o[0] * i0, o[1] * i0);
    *(uint32_t*)(dst + d1) = pack_bf16(o[4] * i0, o[5] * i0);
    *(uint32_t*)(dst + 8 * DM + d0) = pack_bf16(o[2] * i1, o[3] * i1);
    *(uint32_t*)(dst + 8 * DM + d1) = pack_bf16(o[6] * i1, o[7] * i1);
    if (odd ? (c >= 2) : (c < 2)) {
        *(uint32_t*)(dst + d2) = pack_bf16(o[8] * i0, o[9] * i0);
        *(uint32_t*)(dst + 8 * DM + d2) = pack_bf16(o[10] * i1, o[11] * i1);
    }
}

__device__ __forceinline__ void attn_rows_maxshift(uint32_t sK, uint32_t bar, int h, int rbase) {
    const int lane = threadIdx.x & 31, g = lane >> 2, c = lane & 3;
    QFrag q = load_q(h, rbase, g, c);
    if (c == ((h & 1) ? 0 : 2)) { q.q4 = 0u; q.q5 = 0u; }
    const uint64_t dK0 = make_desc(sK, 128, 384, 0), dV0 = make_desc(sK + IMG_BYTES, 384, 128, 0);
    float o[12], s[32];
    uint32_t p[16];
#pragma unroll
    for (int i = 0; i < 12; i++) o[i] = 0.f;
    float m0 = -3.0e38f, m1 = -3.0e38f;
    mbar_wait(bar + 128, 0);
#pragma unroll 1
    for (int t = 0; t < 32; t++) {
        mbar_wait(bar + (t >> 1) * 8, 0);
        if (t) mbar_wait(bar + ((t - 1) >> 1) * 8, 0);
        qk_tile(s, q, dK0 + t * 192);
        wg_wait<0>();
        fence_regs(s);
        const uint32_t mask = EMU_MASK >> ((t & 1) * 8);
        float n0 = m0, n1 = m1;
#pragma unroll
        for (int b = 0; b < 8; b++) {
            const float f = ((mask >> b) & 1) ? 0.5f : 1.f;
            s[4 * b] *= f; s[4 * b + 1] *= f; s[4 * b + 2] *= f; s[4 * b + 3] *= f;
            n0 = fmaxf(n0, fmaxf(s[4 * b], s[4 * b + 1]));
            n1 = fmaxf(n1, fmaxf(s[4 * b + 2], s[4 * b + 3]));
        }
        n0 = fmaxf(n0, __shfl_xor_sync(~0u, n0, 1)); n0 = fmaxf(n0, __shfl_xor_sync(~0u, n0, 2));
        n1 = fmaxf(n1, __shfl_xor_sync(~0u, n1, 1)); n1 = fmaxf(n1, __shfl_xor_sync(~0u, n1, 2));
        const float c0 = ex2(m0 - n0), c1 = ex2(m1 - n1);
        m0 = n0; m1 = n1;
#pragma unroll
        for (int b = 0; b < 3; b++) { o[4 * b] *= c0; o[4 * b + 1] *= c0; o[4 * b + 2] *= c1; o[4 * b + 3] *= c1; }
#pragma unroll
        for (int b = 0; b < 8; b++) {
            p[2 * b] = pack_bf16(ex2(s[4 * b] - m0), ex2(s[4 * b + 1] - m0));
            p[2 * b + 1] = pack_bf16(ex2(s[4 * b + 2] - m1), ex2(s[4 * b + 3] - m1));
        }
        pv_tile(o, p, dV0 + t * 192);
        wg_wait<0>();
        fence_regs(o);
    }
    store_o(o, h, rbase, lane);
}

__global__ void __launch_bounds__(512, 1) k_attn() {
    extern __shared__ __align__(1024) uint8_t smem[];
    const uint32_t sK = smem_u32(smem), sV = sK + IMG_BYTES;
    const uint32_t bar = sK + AT_BAR_OFF;
    float* red = reinterpret_cast<float*>(smem + AT_BAR_OFF + 256);
    const int warp = __shfl_sync(~0u, threadIdx.x >> 5, 0), lane = threadIdx.x & 31;
    const int h = blockIdx.x >> 2, qb = blockIdx.x & 3;
    const int wg = warp >> 2, w4 = warp & 3;

    if (threadIdx.x == 0) TL(2, 0);
    pdl_launch();
    if (threadIdx.x == 0) {
        for (int i = 0; i < 17; i++) mbar_init(bar + i * 8, 1);
        fence_barrier_init();
    }
    __syncthreads();
    pdl_wait();
    if (threadIdx.x == 0) TL(2, 1);
    if (warp == 0 && elect_one()) {
        const uint8_t* gK = g_img + (size_t)(32 + h) * IMG_BYTES;
        const uint8_t* gV = g_img + (size_t)(64 + h) * IMG_BYTES;
        mbar_expect_tx(bar + 128, 6144);
        bulk_load(sK, gK, 6144, bar + 128);
        for (int i = 0; i < 16; i++) {
            mbar_expect_tx(bar + i * 8, i < 15 ? 12288 : 6144);
            bulk_load(sV + i * 6144, gV + i * 6144, 6144, bar + i * 8);
            if (i < 15) bulk_load(sK + (i + 1) * 6144, gK + (i + 1) * 6144, 6144, bar + i * 8);
        }
    }
    float kmax = 0.f, qmax = g_nrm[h * SEQ + qb * 512 + threadIdx.x];
#pragma unroll
    for (int i = 0; i < 4; i++) kmax = fmaxf(kmax, g_nrm[(32 + h) * SEQ + i * 512 + threadIdx.x]);
#pragma unroll
    for (int o = 16; o; o >>= 1) {
        kmax = fmaxf(kmax, __shfl_xor_sync(~0u, kmax, o));
        qmax = fmaxf(qmax, __shfl_xor_sync(~0u, qmax, o));
    }
    if (lane == 0) { red[warp] = kmax; red[16 + warp] = qmax; }
    __syncthreads();
    kmax = red[lane & 15]; qmax = red[16 + (lane & 15)];
#pragma unroll
    for (int o = 8; o; o >>= 1) {
        kmax = fmaxf(kmax, __shfl_xor_sync(~0u, kmax, o));
        qmax = fmaxf(qmax, __shfl_xor_sync(~0u, qmax, o));
    }
    const bool safe = __all_sync(~0u, kmax * qmax * 1.05f <= SAFE_BOUND * SAFE_BOUND);
    if (!safe) {
#pragma unroll 1
        for (int pass = 0; pass < 2; pass++) attn_rows_maxshift(sK, bar, h, qb * 512 + pass * 256 + wg * 64 + w4 * 16);
        return;
    }
    const ExpConst kc = make_exp_const();
    const uint64_t dK0 = make_desc(sK, 128, 384, 0), dV0 = make_desc(sV, 384, 128, 0);
#pragma unroll 1
    for (int pass = 0; pass < 2; pass++) {
        const int rbase = qb * 512 + pass * 256 + wg * 64 + w4 * 16;
        const QFrag q = load_q(h, rbase, lane >> 2, lane & 3);
        float o[12], sa[32], sb[32];
        uint32_t p[16];
#pragma unroll
        for (int i = 0; i < 12; i++) o[i] = 0.f;
        fence_regs(o);
        mbar_wait(bar + 128, 0);
        qk_tile(sa, q, dK0);
        wg_wait<0>();
        fence_regs(sa);
        uint64_t dK = dK0, dV = dV0;
        uint32_t bj = bar;
#pragma unroll 1
        for (int j = 0; j < 16; j++) {
            mbar_wait(bj, 0);
            qk_tile(sb, q, dK + 192);
            wg_wait<1>();
            exp_tile<0>(sa, p, kc);
            pv_tile(o, p, dV);
            wg_wait<1>();
            fence_regs(sb);
            mbar_wait(bj, 0);
            qk_tile(sa, q, dK + 384);
            wg_wait<1>();
            exp_tile<8>(sb, p, kc);
            pv_tile(o, p, dV + 192);
            wg_wait<1>();
            fence_regs(sa);
            dK += 384; dV += 384; bj += 8;
        }
        wg_wait<0>();
        fence_regs(o);
        store_o(o, h, rbase, lane);
        if (threadIdx.x == 0) TL(2, 2 + pass);
    }
}

constexpr int G2_STAGES = 8;
constexpr int G2_STAGE = 8192 + 20480;
constexpr int G2_BAR_OFF = G2_STAGES * G2_STAGE;
constexpr int G2_SMEM = G2_BAR_OFF + 256;

__global__ void __launch_bounds__(160, 1) __cluster_dims__(2, 1, 1)
k_gemm2(const __grid_constant__ CUtensorMap tmO, const __grid_constant__ CUtensorMap tmH,
        const __grid_constant__ CUtensorMap tmWo, const __grid_constant__ CUtensorMap tmW2,
        const __nv_bfloat16* __restrict__ x, const __nv_bfloat16* __restrict__ b2, __nv_bfloat16* __restrict__ out) {
    extern __shared__ __align__(1024) uint8_t smem[];
    const uint32_t sbase = smem_u32(smem);
    const uint32_t barFull = sbase + G2_BAR_OFF, barEmpty = barFull + 64;
    const int warp = __shfl_sync(~0u, threadIdx.x >> 5, 0), lane = threadIdx.x & 31;
    const uint32_t rank = blockIdx.x & 1;
    const int cl = blockIdx.x >> 1, ct = cl & 3, rt = (cl >> 2) * 2 + rank;

    if (threadIdx.x == 0) TL(3, 0);
    pdl_launch();
    if (threadIdx.x == 0) {
        for (int i = 0; i < G2_STAGES; i++) { mbar_init(barFull + i * 8, 1); mbar_init(barEmpty + i * 8, 8); }
        fence_barrier_init();
    }
    __syncthreads();
    cluster_sync();

    if (warp == 4) {
        if (elect_one()) { prefetch_map(&tmO); prefetch_map(&tmH); prefetch_map(&tmWo); prefetch_map(&tmW2); }
        pdl_wait();
        if (lane == 0) TL(3, 1);
#pragma unroll 1
        for (int kb = 0; kb < 34; kb++) {
            const int s = kb & (G2_STAGES - 1);
            if (kb >= G2_STAGES) mbar_wait(barEmpty + s * 8, ((kb >> 3) - 1) & 1);
            if (elect_one()) {
                const uint32_t dst = sbase + s * G2_STAGE, bar = barFull + s * 8;
                const CUtensorMap* mA = kb < 24 ? &tmH : &tmO;
                const CUtensorMap* mB = kb < 24 ? &tmW2 : &tmWo;
                const int k0 = (kb < 24 ? kb : kb - 24) * 64;
                mbar_expect_tx(bar, G2_STAGE);
                tma_load(dst, mA, k0, rt * 64, bar);
                const int first = ((kb & 1) == (int)rank) ? 0 : 3, last = ((kb & 1) == (int)rank) ? 3 : 5;
                for (int b = first; b < last; b++)
                    tma_load_mc(dst + 8192 + b * 4096, mB, ct * 160 + b * 32, k0, bar, 3);
            }
            __syncwarp();
        }
    } else {
        const int g = lane >> 2, c = lane & 3;
        const uint32_t peer = rank ^ 1;
        float acc[80];
#pragma unroll 1
        for (int kb = 0; kb < 34; kb++) {
            const int s = kb & (G2_STAGES - 1);
            mbar_wait(barFull + s * 8, (kb >> 3) & 1);
            wg_fence();
            const uint64_t dA = make_desc(sbase + s * G2_STAGE, 16, 1024, 1);
            const uint64_t dB = make_desc(sbase + s * G2_STAGE + 8192, 4096, 512, 2);
#pragma unroll
            for (int kk = 0; kk < 4; kk++) wgmma_n160_ss_tb(acc, dA + kk * 2, dB + kk * 64, (kb | kk) != 0);
            wg_commit();
            if (kb > 0) {
                wg_wait<1>();
                if (lane == 0) {
                    const uint32_t e = barEmpty + ((kb - 1) & (G2_STAGES - 1)) * 8;
                    mbar_arrive(e);
                    mbar_arrive_cluster(e, peer);
                }
            }
        }
        wg_wait<0>();
        fence_regs(acc);
        if (threadIdx.x == 0) TL(3, 2);
        const int row = rt * 64 + warp * 16 + g;
        const size_t off0 = (size_t)row * DM + ct * 160 + 2 * c, off1 = off0 + 8 * DM;
        const uint32_t* bias = reinterpret_cast<const uint32_t*>(b2 + ct * 160) + c;
#pragma unroll
        for (int j = 0; j < 20; j++) {
            const uint32_t bb = __ldg(bias + j * 4);
            const uint32_t x0 = __ldg((const uint32_t*)(x + off0 + j * 8)), x1 = __ldg((const uint32_t*)(x + off1 + j * 8));
            *(uint32_t*)(out + off0 + j * 8) =
                pack_bf16(acc[4 * j] + bf_lo(bb) + bf_lo(x0), acc[4 * j + 1] + bf_hi(bb) + bf_hi(x0));
            *(uint32_t*)(out + off1 + j * 8) =
                pack_bf16(acc[4 * j + 2] + bf_lo(bb) + bf_lo(x1), acc[4 * j + 3] + bf_hi(bb) + bf_hi(x1));
        }
    }
    __syncthreads();
    if (threadIdx.x == 0) TL(3, 3);
    cluster_sync();
}

typedef CUresult (*EncodeTiledFn)(CUtensorMap*, CUtensorMapDataType, cuuint32_t, void*, const cuuint64_t*,
                                  const cuuint64_t*, const cuuint32_t*, const cuuint32_t*, CUtensorMapInterleave,
                                  CUtensorMapSwizzle, CUtensorMapL2promotion, CUtensorMapFloatOOBfill);

CUtensorMap make_map(EncodeTiledFn enc, const void* ptr, int rows, int cols, int box_rows, int box_cols,
                     CUtensorMapSwizzle swz) {
    CUtensorMap m;
    cuuint64_t gd[2] = {(cuuint64_t)cols, (cuuint64_t)rows};
    cuuint64_t gs[1] = {(cuuint64_t)cols * 2};
    cuuint32_t bd[2] = {(cuuint32_t)box_cols, (cuuint32_t)box_rows};
    cuuint32_t es[2] = {1, 1};
    enc(&m, CU_TENSOR_MAP_DATA_TYPE_BFLOAT16, 2, const_cast<void*>(ptr), gd, gs, bd, es, CU_TENSOR_MAP_INTERLEAVE_NONE,
        swz, CU_TENSOR_MAP_L2_PROMOTION_L2_128B, CU_TENSOR_MAP_FLOAT_OOB_FILL_NONE);
    return m;
}

template <typename... KArgs, typename... Args>
void launch(void (*kern)(KArgs...), int grid, int block, int smem, int cluster, bool pdl, Args... args) {
    cudaLaunchConfig_t cfg = {};
    cfg.gridDim = dim3(grid);
    cfg.blockDim = dim3(block);
    cfg.dynamicSmemBytes = smem;
    cfg.stream = cudaStreamPerThread;
    cudaLaunchAttribute at[1];
    at[0].id = cudaLaunchAttributeProgrammaticStreamSerialization;
    at[0].val.programmaticStreamSerializationAllowed = 1;
    cfg.attrs = at;
    cfg.numAttrs = pdl ? 1 : 0;
    (void)cluster;
    cudaLaunchKernelEx(&cfg, kern, KArgs(args)...);
}

}

extern "C" void kernel_launch(void* const* d_in, const int* in_sizes, int n_in, void* d_out, int out_size) {
    (void)in_sizes; (void)n_in; (void)out_size;
    const __nv_bfloat16* x = (const __nv_bfloat16*)d_in[0];
    const __nv_bfloat16* wqkv = (const __nv_bfloat16*)d_in[1];
    const __nv_bfloat16* wo = (const __nv_bfloat16*)d_in[2];
    const __nv_bfloat16* w1 = (const __nv_bfloat16*)d_in[4];
    const __nv_bfloat16* b1 = (const __nv_bfloat16*)d_in[5];
    const __nv_bfloat16* w2 = (const __nv_bfloat16*)d_in[6];
    const __nv_bfloat16* b2 = (const __nv_bfloat16*)d_in[7];
    __nv_bfloat16* out = (__nv_bfloat16*)d_out;

    static EncodeTiledFn enc = nullptr;
    static void *p_xn, *p_h, *p_o;
    if (!enc) {
        cudaDriverEntryPointQueryResult qr;
        cudaGetDriverEntryPoint("cuTensorMapEncodeTiled", (void**)&enc, cudaEnableDefault, &qr);
        cudaGetSymbolAddress(&p_xn, g_xn);
        cudaGetSymbolAddress(&p_h, g_h);
        cudaGetSymbolAddress(&p_o, g_o);
        cudaFuncSetAttribute(k_gemm1, cudaFuncAttributeMaxDynamicSharedMemorySize, G1_SMEM);
        cudaFuncSetAttribute(k_attn, cudaFuncAttributeMaxDynamicSharedMemorySize, AT_SMEM);
        cudaFuncSetAttribute(k_gemm2, cudaFuncAttributeMaxDynamicSharedMemorySize, G2_SMEM);
    }
    const CUtensorMap tmXn = make_map(enc, p_xn, SEQ, DM, 128, 64, CU_TENSOR_MAP_SWIZZLE_128B);
    const CUtensorMap tmWqkv = make_map(enc, wqkv, DM, 3 * DM, 32, 64, CU_TENSOR_MAP_SWIZZLE_128B);
    const CUtensorMap tmW1 = make_map(enc, w1, DM, FF, 32, 32, CU_TENSOR_MAP_SWIZZLE_64B);
    const CUtensorMap tmHst = make_map(enc, p_h, SEQ, FF, 64, 32, CU_TENSOR_MAP_SWIZZLE_64B);
    const CUtensorMap tmH = make_map(enc, p_h, SEQ, FF, 64, 64, CU_TENSOR_MAP_SWIZZLE_128B);
    const CUtensorMap tmO = make_map(enc, p_o, SEQ, DM, 64, 64, CU_TENSOR_MAP_SWIZZLE_128B);
    const CUtensorMap tmWo = make_map(enc, wo, DM, DM, 64, 32, CU_TENSOR_MAP_SWIZZLE_64B);
    const CUtensorMap tmW2 = make_map(enc, w2, FF, DM, 64, 32, CU_TENSOR_MAP_SWIZZLE_64B);

    launch(k_ln, SEQ / 8, 256, 0, 1, false, x, (const uint8_t*)wqkv, (const uint8_t*)w1, (const uint8_t*)w2, (const uint8_t*)wo);
    launch(k_gemm1, 128, 544, G1_SMEM, 2, true, tmXn, tmWqkv, tmW1, tmHst, b1);
    launch(k_attn, 128, 512, AT_SMEM, 1, true);
    launch(k_gemm2, 128, 160, G2_SMEM, 2, true, tmO, tmH, tmWo, tmW2, x, b2, out);
}
```

```cpp
#include <cuda_runtime.h>
#include <cuda_bf16.h>
#include <cuda.h>
#include <stdint.h>

namespace {

constexpr int SEQ = 2048, DM = 640, FF = 1536;
constexpr float LN_EPS = 1e-5f;

constexpr int IMG_BYTES = 256 * 384;
constexpr uint32_t EMU_MASK = 0xD5D5u;
constexpr float SAFE_BOUND = 80.0f;
constexpr float QSCALE = 0.22360679774997896f * 1.4426950408889634f;

__device__ __align__(1024) __nv_bfloat16 g_xn[SEQ * DM];
__device__ float g_r2[SEQ];
__device__ __align__(1024) uint8_t g_img[96 * IMG_BYTES + 1024];
__device__ float g_nrm[64 * SEQ];
__device__ __align__(1024) __nv_bfloat16 g_h[SEQ * FF];
__device__ __align__(1024) __nv_bfloat16 g_o[SEQ * DM];
constexpr int CNT_LN = 0, CNT_QKV = 16, CNT_H = 24, CNT_O = 40;
__device__ uint32_t g_cnt[44 * 32];
__device__ uint32_t g_epoch;

#define TL(kern, slot) do { } while (0)
#define IT(row, i) do { } while (0)

__device__ __forceinline__ uint32_t smem_u32(const void* p) { return (uint32_t)__cvta_generic_to_shared(p); }
__device__ __forceinline__ void mbar_init(uint32_t bar, int cnt) {
    asm volatile("mbarrier.init.shared::cta.b64 [%0], %1;" ::"r"(bar), "r"(cnt));
}
__device__ __forceinline__ void mbar_expect_tx(uint32_t bar, uint32_t bytes) {
    asm volatile("mbarrier.arrive.expect_tx.shared::cta.b64 _, [%0], %1;" ::"r"(bar), "r"(bytes) : "memory");
}
__device__ __forceinline__ void mbar_wait(uint32_t bar, uint32_t parity) {
    asm volatile("{\n.reg .pred p;\n.reg .u32 n;\nmov.u32 n, 0;\n"
                 "WAIT_LOOP:\nmbarrier.try_wait.parity.shared::cta.b64 p, [%0], %1;\n@p bra WAIT_DONE;\n"
                 "add.u32 n, n, 1;\nsetp.lt.u32 p, n, 4194304;\n@p bra WAIT_LOOP;\nWAIT_DONE:\n}"
                 ::"r"(bar), "r"(parity) : "memory");
}
__device__ __forceinline__ void mbar_arrive(uint32_t bar) {
    asm volatile("mbarrier.arrive.shared::cta.b64 _, [%0];" ::"r"(bar) : "memory");
}
__device__ __forceinline__ void mbar_arrive_cluster(uint32_t bar, uint32_t cta) {
    asm volatile("{\n.reg .b32 ra;\nmapa.shared::cluster.u32 ra, %0, %1;\n"
                 "mbarrier.arrive.shared::cluster.b64 _, [ra];\n}" ::"r"(bar), "r"(cta) : "memory");
}
__device__ __forceinline__ void fence_barrier_init() { asm volatile("fence.mbarrier_init.release.cluster;" ::: "memory"); }
__device__ __forceinline__ void fence_proxy_async() { asm volatile("fence.proxy.async.shared::cta;" ::: "memory"); }
__device__ __forceinline__ void cluster_sync() {
    asm volatile("barrier.cluster.arrive.release.aligned;\nbarrier.cluster.wait.acquire.aligned;" ::: "memory");
}
__device__ __forceinline__ bool elect_one() {
    uint32_t pred;
    asm volatile("{\n.reg .pred p;\nelect.sync _|p, 0xFFFFFFFF;\nselp.b32 %0, 1, 0, p;\n}" : "=r"(pred));
    return pred != 0;
}
__device__ __forceinline__ void pdl_launch() { asm volatile("griddepcontrol.launch_dependents;" ::: "memory"); }
__device__ __forceinline__ void pdl_wait() { asm volatile("griddepcontrol.wait;" ::: "memory"); }
__device__ __forceinline__ void prefetch_map(const CUtensorMap* m) {
    asm volatile("prefetch.tensormap [%0];" ::"l"(m) : "memory");
}
__device__ __forceinline__ void tma_load(uint32_t dst, const CUtensorMap* m, int c0, int c1, uint32_t bar) {
    asm volatile("cp.async.bulk.tensor.2d.shared::cluster.global.mbarrier::complete_tx::bytes [%0], [%1, {%3, %4}], [%2];"
                 ::"r"(dst), "l"(m), "r"(bar), "r"(c0), "r"(c1) : "memory");
}
__device__ __forceinline__ void tma_load_mc(uint32_t dst, const CUtensorMap* m, int c0, int c1, uint32_t bar, uint16_t mask) {
    asm volatile("cp.async.bulk.tensor.2d.shared::cluster.global.mbarrier::complete_tx::bytes.multicast::cluster"
                 " [%0], [%1, {%3, %4}], [%2], %5;"
                 ::"r"(dst), "l"(m), "r"(bar), "r"(c0), "r"(c1), "h"(mask) : "memory");
}
__device__ __forceinline__ void tma_store(const CUtensorMap* m, uint32_t src, int c0, int c1) {
    asm volatile("cp.async.bulk.tensor.2d.global.shared::cta.bulk_group [%0, {%2, %3}], [%1];"
                 ::"l"(m), "r"(src), "r"(c0), "r"(c1) : "memory");
}
__device__ __forceinline__ void bulk_commit() { asm volatile("cp.async.bulk.commit_group;" ::: "memory"); }
__device__ __forceinline__ void bulk_wait_all() { asm volatile("cp.async.bulk.wait_group 0;" ::: "memory"); }
__device__ __forceinline__ void bulk_load(uint32_t dst, const void* src, uint32_t bytes, uint32_t bar) {
    asm volatile("cp.async.bulk.shared::cluster.global.mbarrier::complete_tx::bytes [%0], [%1], %2, [%3];"
                 ::"r"(dst), "l"(src), "r"(bytes), "r"(bar) : "memory");
}
__device__ __forceinline__ void prefetch_l2(const void* p, uint32_t bytes) {
    asm volatile("cp.async.bulk.prefetch.L2.global [%0], %1;" ::"l"(p), "r"(bytes) : "memory");
}
__device__ __forceinline__ void wg_fence() { asm volatile("wgmma.fence.sync.aligned;" ::: "memory"); }
__device__ __forceinline__ void wg_commit() { asm volatile("wgmma.commit_group.sync.aligned;" ::: "memory"); }
template <int N> __device__ __forceinline__ void wg_wait() {
    asm volatile("wgmma.wait_group.sync.aligned %0;" ::"n"(N) : "memory");
}
template <int N> __device__ __forceinline__ void reg_alloc() { asm volatile("setmaxnreg.inc.sync.aligned.u32 %0;" ::"n"(N)); }
template <int N> __device__ __forceinline__ void reg_dealloc() { asm volatile("setmaxnreg.dec.sync.aligned.u32 %0;" ::"n"(N)); }
template <int N> __device__ __forceinline__ void fence_regs(float (&d)[N]) {
#pragma unroll
    for (int i = 0; i < N; i++) asm volatile("" : "+f"(d[i])::"memory");
}
__device__ __forceinline__ uint64_t make_desc(uint32_t addr, uint32_t lbo, uint32_t sbo, uint32_t swz) {
    return (uint64_t)((addr & 0x3FFFF) >> 4) | ((uint64_t)(lbo >> 4) << 16) | ((uint64_t)(sbo >> 4) << 32) |
           ((uint64_t)swz << 62);
}
__device__ __forceinline__ uint32_t pack_bf16(float lo, float hi) {
    uint32_t r;
    asm("cvt.rn.bf16x2.f32 %0, %1, %2;" : "=r"(r) : "f"(hi), "f"(lo));
    return r;
}
__device__ __forceinline__ float ex2(float x) {
    float r;
    asm("ex2.approx.ftz.f32 %0, %1;" : "=f"(r) : "f"(x));
    return r;
}
__device__ __forceinline__ float bf_lo(uint32_t v) { return __uint_as_float(v << 16); }
__device__ __forceinline__ float bf_hi(uint32_t v) { return __uint_as_float(v & 0xFFFF0000u); }
__device__ __forceinline__ void stmatrix_x4(uint32_t addr, uint32_t r0, uint32_t r1, uint32_t r2, uint32_t r3) {
    asm volatile("stmatrix.sync.aligned.m8n8.x4.shared.b16 [%0], {%1, %2, %3, %4};"
                 ::"r"(addr), "r"(r0), "r"(r1), "r"(r2), "r"(r3) : "memory");
}

__device__ __forceinline__ void wgmma_n120_ss_tb(float (&d)[60], uint64_t descA, uint64_t descB, int scaleD) {
    asm volatile("{\n.reg .pred p;\nsetp.ne.b32 p, %62, 0;\n"
        "wgmma.mma_async.sync.aligned.m64n120k16.f32.bf16.bf16 {"
        "%0, %1, %2, %3, %4, %5, %6, %7, %8, %9, %10, %11, %12, %13, %14, %15, "
        "%16, %17, %18, %19, %20, %21, %22, %23, %24, %25, %26, %27, %28, %29, %30, %31, "
        "%32, %33, %34, %35, %36, %37, %38, %39, %40, %41, %42, %43, %44, %45, %46, %47, "
        "%48, %49, %50, %51, %52, %53, %54, %55, %56, %57, %58, %59}, "
        "%60, %61, p, 1, 1, 0, 1;\n}\n"
        : "+f"(d[0]), "+f"(d[1]), "+f"(d[2]), "+f"(d[3]), "+f"(d[4]), "+f"(d[5]), "+f"(d[6]), "+f"(d[7]),
          "+f"(d[8]), "+f"(d[9]), "+f"(d[10]), "+f"(d[11]), "+f"(d[12]), "+f"(d[13]), "+f"(d[14]), "+f"(d[15]),
          "+f"(d[16]), "+f"(d[17]), "+f"(d[18]), "+f"(d[19]), "+f"(d[20]), "+f"(d[21]), "+f"(d[22]), "+f"(d[23]),
          "+f"(d[24]), "+f"(d[25]), "+f"(d[26]), "+f"(d[27]), "+f"(d[28]), "+f"(d[29]), "+f"(d[30]), "+f"(d[31]),
          "+f"(d[32]), "+f"(d[33]), "+f"(d[34]), "+f"(d[35]), "+f"(d[36]), "+f"(d[37]), "+f"(d[38]), "+f"(d[39]),
          "+f"(d[40]), "+f"(d[41]), "+f"(d[42]), "+f"(d[43]), "+f"(d[44]), "+f"(d[45]), "+f"(d[46]), "+f"(d[47]),
          "+f"(d[48]), "+f"(d[49]), "+f"(d[50]), "+f"(d[51]), "+f"(d[52]), "+f"(d[53]), "+f"(d[54]), "+f"(d[55]),
          "+f"(d[56]), "+f"(d[57]), "+f"(d[58]), "+f"(d[59])
        : "l"(descA), "l"(descB), "r"(scaleD));
}

__device__ __forceinline__ void wgmma_n192_ss_tb(float (&d)[96], uint64_t descA, uint64_t descB, int scaleD) {
    asm volatile("{\n.reg .pred p;\nsetp.ne.b32 p, %98, 0;\n"
        "wgmma.mma_async.sync.aligned.m64n192k16.f32.bf16.bf16 {"
        "%0, %1, %2, %3, %4, %5, %6, %7, %8, %9, %10, %11, %12, %13, %14, %15, "
        "%16, %17, %18, %19, %20, %21, %22, %23, %24, %25, %26, %27, %28, %29, %30, %31, "
        "%32, %33, %34, %35, %36, %37, %38, %39, %40, %41, %42, %43, %44, %45, %46, %47, "
        "%48, %49, %50, %51, %52, %53, %54, %55, %56, %57, %58, %59, %60, %61, %62, %63, "
        "%64, %65, %66, %67, %68, %69, %70, %71, %72, %73, %74, %75, %76, %77, %78, %79, "
        "%80, %81, %82, %83, %84, %85, %86, %87, %88, %89, %90, %91, %92, %93, %94, %95}, "
        "%96, %97, p, 1, 1, 0, 1;\n}\n"
        : "+f"(d[0]), "+f"(d[1]), "+f"(d[2]), "+f"(d[3]), "+f"(d[4]), "+f"(d[5]), "+f"(d[6]), "+f"(d[7]),
          "+f"(d[8]), "+f"(d[9]), "+f"(d[10]), "+f"(d[11]), "+f"(d[12]), "+f"(d[13]), "+f"(d[14]), "+f"(d[15]),
          "+f"(d[16]), "+f"(d[17]), "+f"(d[18]), "+f"(d[19]), "+f"(d[20]), "+f"(d[21]), "+f"(d[22]), "+f"(d[23]),
          "+f"(d[24]), "+f"(d[25]), "+f"(d[26]), "+f"(d[27]), "+f"(d[28]), "+f"(d[29]), "+f"(d[30]), "+f"(d[31]),
          "+f"(d[32]), "+f"(d[33]), "+f"(d[34]), "+f"(d[35]), "+f"(d[36]), "+f"(d[37]), "+f"(d[38]), "+f"(d[39]),
          "+f"(d[40]), "+f"(d[41]), "+f"(d[42]), "+f"(d[43]), "+f"(d[44]), "+f"(d[45]), "+f"(d[46]), "+f"(d[47]),
          "+f"(d[48]), "+f"(d[49]), "+f"(d[50]), "+f"(d[51]), "+f"(d[52]), "+f"(d[53]), "+f"(d[54]), "+f"(d[55]),
          "+f"(d[56]), "+f"(d[57]), "+f"(d[58]), "+f"(d[59]), "+f"(d[60]), "+f"(d[61]), "+f"(d[62]), "+f"(d[63]),
          "+f"(d[64]), "+f"(d[65]), "+f"(d[66]), "+f"(d[67]), "+f"(d[68]), "+f"(d[69]), "+f"(d[70]), "+f"(d[71]),
          "+f"(d[72]), "+f"(d[73]), "+f"(d[74]), "+f"(d[75]), "+f"(d[76]), "+f"(d[77]), "+f"(d[78]), "+f"(d[79]),
          "+f"(d[80]), "+f"(d[81]), "+f"(d[82]), "+f"(d[83]), "+f"(d[84]), "+f"(d[85]), "+f"(d[86]), "+f"(d[87]),
          "+f"(d[88]), "+f"(d[89]), "+f"(d[90]), "+f"(d[91]), "+f"(d[92]), "+f"(d[93]), "+f"(d[94]), "+f"(d[95])
        : "l"(descA), "l"(descB), "r"(scaleD));
}

__device__ __forceinline__ void wgmma_n192_ss_tb_z(float (&d)[96], uint64_t descA, uint64_t descB) {
    asm volatile("{\n.reg .pred p;\nsetp.ne.b32 p, 0, 0;\n"
        "wgmma.mma_async.sync.aligned.m64n192k16.f32.bf16.bf16 {"
        "%0, %1, %2, %3, %4, %5, %6, %7, %8, %9, %10, %11, %12, %13, %14, %15, "
        "%16, %17, %18, %19, %20, %21, %22, %23, %24, %25, %26, %27, %28, %29, %30, %31, "
        "%32, %33, %34, %35, %36, %37, %38, %39, %40, %41, %42, %43, %44, %45, %46, %47, "
        "%48, %49, %50, %51, %52, %53, %54, %55, %56, %57, %58, %59, %60, %61, %62, %63, "
        "%64, %65, %66, %67, %68, %69, %70, %71, %72, %73, %74, %75, %76, %77, %78, %79, "
        "%80, %81, %82, %83, %84, %85, %86, %87, %88, %89, %90, %91, %92, %93, %94, %95}, "
        "%96, %97, p, 1, 1, 0, 1;\n}\n"
        : "=f"(d[0]), "=f"(d[1]), "=f"(d[2]), "=f"(d[3]), "=f"(d[4]), "=f"(d[5]), "=f"(d[6]), "=f"(d[7]),
          "=f"(d[8]), "=f"(d[9]), "=f"(d[10]), "=f"(d[11]), "=f"(d[12]), "=f"(d[13]), "=f"(d[14]), "=f"(d[15]),
          "=f"(d[16]), "=f"(d[17]), "=f"(d[18]), "=f"(d[19]), "=f"(d[20]), "=f"(d[21]), "=f"(d[22]), "=f"(d[23]),
          "=f"(d[24]), "=f"(d[25]), "=f"(d[26]), "=f"(d[27]), "=f"(d[28]), "=f"(d[29]), "=f"(d[30]), "=f"(d[31]),
          "=f"(d[32]), "=f"(d[33]), "=f"(d[34]), "=f"(d[35]), "=f"(d[36]), "=f"(d[37]), "=f"(d[38]), "=f"(d[39]),
          "=f"(d[40]), "=f"(d[41]), "=f"(d[42]), "=f"(d[43]), "=f"(d[44]), "=f"(d[45]), "=f"(d[46]), "=f"(d[47]),
          "=f"(d[48]), "=f"(d[49]), "=f"(d[50]), "=f"(d[51]), "=f"(d[52]), "=f"(d[53]), "=f"(d[54]), "=f"(d[55]),
          "=f"(d[56]), "=f"(d[57]), "=f"(d[58]), "=f"(d[59]), "=f"(d[60]), "=f"(d[61]), "=f"(d[62]), "=f"(d[63]),
          "=f"(d[64]), "=f"(d[65]), "=f"(d[66]), "=f"(d[67]), "=f"(d[68]), "=f"(d[69]), "=f"(d[70]), "=f"(d[71]),
          "=f"(d[72]), "=f"(d[73]), "=f"(d[74]), "=f"(d[75]), "=f"(d[76]), "=f"(d[77]), "=f"(d[78]), "=f"(d[79]),
          "=f"(d[80]), "=f"(d[81]), "=f"(d[82]), "=f"(d[83]), "=f"(d[84]), "=f"(d[85]), "=f"(d[86]), "=f"(d[87]),
          "=f"(d[88]), "=f"(d[89]), "=f"(d[90]), "=f"(d[91]), "=f"(d[92]), "=f"(d[93]), "=f"(d[94]), "=f"(d[95])
        : "l"(descA), "l"(descB));
}

__device__ __forceinline__ void wgmma_n160_ss_tb(float (&d)[80], uint64_t descA, uint64_t descB, int scaleD) {
    asm volatile("{\n.reg .pred p;\nsetp.ne.b32 p, %82, 0;\n"
        "wgmma.mma_async.sync.aligned.m64n160k16.f32.bf16.bf16 {"
        "%0, %1, %2, %3, %4, %5, %6, %7, %8, %9, %10, %11, %12, %13, %14, %15, "
        "%16, %17, %18, %19, %20, %21, %22, %23, %24, %25, %26, %27, %28, %29, %30, %31, "
        "%32, %33, %34, %35, %36, %37, %38, %39, %40, %41, %42, %43, %44, %45, %46, %47, "
        "%48, %49, %50, %51, %52, %53, %54, %55, %56, %57, %58, %59, %60, %61, %62, %63, "
        "%64, %65, %66, %67, %68, %69, %70, %71, %72, %73, %74, %75, %76, %77, %78, %79}, "
        "%80, %81, p, 1, 1, 0, 1;\n}\n"
        : "+f"(d[0]), "+f"(d[1]), "+f"(d[2]), "+f"(d[3]), "+f"(d[4]), "+f"(d[5]), "+f"(d[6]), "+f"(d[7]),
          "+f"(d[8]), "+f"(d[9]), "+f"(d[10]), "+f"(d[11]), "+f"(d[12]), "+f"(d[13]), "+f"(d[14]), "+f"(d[15]),
          "+f"(d[16]), "+f"(d[17]), "+f"(d[18]), "+f"(d[19]), "+f"(d[20]), "+f"(d[21]), "+f"(d[22]), "+f"(d[23]),
          "+f"(d[24]), "+f"(d[25]), "+f"(d[26]), "+f"(d[27]), "+f"(d[28]), "+f"(d[29]), "+f"(d[30]), "+f"(d[31]),
          "+f"(d[32]), "+f"(d[33]), "+f"(d[34]), "+f"(d[35]), "+f"(d[36]), "+f"(d[37]), "+f"(d[38]), "+f"(d[39]),
          "+f"(d[40]), "+f"(d[41]), "+f"(d[42]), "+f"(d[43]), "+f"(d[44]), "+f"(d[45]), "+f"(d[46]), "+f"(d[47]),
          "+f"(d[48]), "+f"(d[49]), "+f"(d[50]), "+f"(d[51]), "+f"(d[52]), "+f"(d[53]), "+f"(d[54]), "+f"(d[55]),
          "+f"(d[56]), "+f"(d[57]), "+f"(d[58]), "+f"(d[59]), "+f"(d[60]), "+f"(d[61]), "+f"(d[62]), "+f"(d[63]),
          "+f"(d[64]), "+f"(d[65]), "+f"(d[66]), "+f"(d[67]), "+f"(d[68]), "+f"(d[69]), "+f"(d[70]), "+f"(d[71]),
          "+f"(d[72]), "+f"(d[73]), "+f"(d[74]), "+f"(d[75]), "+f"(d[76]), "+f"(d[77]), "+f"(d[78]), "+f"(d[79])
        : "l"(descA), "l"(descB), "r"(scaleD));
}

__device__ __forceinline__ void wgmma_n64_ss(float (&d)[32], uint64_t descA, uint64_t descB, int scaleD) {
    asm volatile("{\n.reg .pred p;\nsetp.ne.b32 p, %34, 0;\n"
        "wgmma.mma_async.sync.aligned.m64n64k16.f32.bf16.bf16 {"
        "%0, %1, %2, %3, %4, %5, %6, %7, %8, %9, %10, %11, %12, %13, %14, %15, "
        "%16, %17, %18, %19, %20, %21, %22, %23, %24, %25, %26, %27, %28, %29, %30, %31}, "
        "%32, %33, p, 1, 1, 0, 0;\n}\n"
        : "+f"(d[0]), "+f"(d[1]), "+f"(d[2]), "+f"(d[3]), "+f"(d[4]), "+f"(d[5]), "+f"(d[6]), "+f"(d[7]),
          "+f"(d[8]), "+f"(d[9]), "+f"(d[10]), "+f"(d[11]), "+f"(d[12]), "+f"(d[13]), "+f"(d[14]), "+f"(d[15]),
          "+f"(d[16]), "+f"(d[17]), "+f"(d[18]), "+f"(d[19]), "+f"(d[20]), "+f"(d[21]), "+f"(d[22]), "+f"(d[23]),
          "+f"(d[24]), "+f"(d[25]), "+f"(d[26]), "+f"(d[27]), "+f"(d[28]), "+f"(d[29]), "+f"(d[30]), "+f"(d[31])
        : "l"(descA), "l"(descB), "r"(scaleD));
}

__device__ __forceinline__ void wgmma_n64_ss_z(float (&d)[32], uint64_t descA, uint64_t descB) {
    asm volatile("{\n.reg .pred p;\nsetp.ne.b32 p, 0, 0;\n"
        "wgmma.mma_async.sync.aligned.m64n64k16.f32.bf16.bf16 {"
        "%0, %1, %2, %3, %4, %5, %6, %7, %8, %9, %10, %11, %12, %13, %14, %15, "
        "%16, %17, %18, %19, %20, %21, %22, %23, %24, %25, %26, %27, %28, %29, %30, %31}, "
        "%32, %33, p, 1, 1, 0, 0;\n}\n"
        : "=f"(d[0]), "=f"(d[1]), "=f"(d[2]), "=f"(d[3]), "=f"(d[4]), "=f"(d[5]), "=f"(d[6]), "=f"(d[7]),
          "=f"(d[8]), "=f"(d[9]), "=f"(d[10]), "=f"(d[11]), "=f"(d[12]), "=f"(d[13]), "=f"(d[14]), "=f"(d[15]),
          "=f"(d[16]), "=f"(d[17]), "=f"(d[18]), "=f"(d[19]), "=f"(d[20]), "=f"(d[21]), "=f"(d[22]), "=f"(d[23]),
          "=f"(d[24]), "=f"(d[25]), "=f"(d[26]), "=f"(d[27]), "=f"(d[28]), "=f"(d[29]), "=f"(d[30]), "=f"(d[31])
        : "l"(descA), "l"(descB));
}

__device__ __forceinline__ void wgmma_n24_rs_tb(float (&d)[12], uint32_t a0, uint32_t a1, uint32_t a2, uint32_t a3, uint64_t descB, int scaleD) {
    asm volatile("{\n.reg .pred p;\nsetp.ne.b32 p, %17, 0;\n"
        "wgmma.mma_async.sync.aligned.m64n24k16.f32.bf16.bf16 {"
        "%0, %1, %2, %3, %4, %5, %6, %7, %8, %9, %10, %11}, "
        "{%12, %13, %14, %15}, %16, p, 1, 1, 1;\n}\n"
        : "+f"(d[0]), "+f"(d[1]), "+f"(d[2]), "+f"(d[3]), "+f"(d[4]), "+f"(d[5]), "+f"(d[6]), "+f"(d[7]),
          "+f"(d[8]), "+f"(d[9]), "+f"(d[10]), "+f"(d[11])
        : "r"(a0), "r"(a1), "r"(a2), "r"(a3), "l"(descB), "r"(scaleD));
}

__device__ __forceinline__ void cnt_signal(int idx) {
    asm volatile("fence.acq_rel.gpu;\nred.relaxed.gpu.global.add.u32 [%0], 1;"
                 ::"l"(g_cnt + idx * 32) : "memory");
}
__device__ __forceinline__ void cnt_wait(int idx, uint32_t target) {
    const uint32_t* p = g_cnt + idx * 32;
#pragma unroll 1
    for (uint32_t i = 0; i < (1u << 22); i++) {
        uint32_t v;
        asm volatile("ld.acquire.gpu.global.u32 %0, [%1];" : "=r"(v) : "l"(p) : "memory");
        if ((int32_t)(v - target) >= 0) break;
    }
    asm volatile("fence.proxy.async.global;" ::: "memory");
}
__device__ __forceinline__ void cluster_arrive() { asm volatile("barrier.cluster.arrive.release.aligned;" ::: "memory"); }
__device__ __forceinline__ void cluster_arrive_relaxed() { asm volatile("barrier.cluster.arrive.relaxed.aligned;" ::: "memory"); }
__device__ __forceinline__ void cluster_wait() { asm volatile("barrier.cluster.wait.acquire.aligned;" ::: "memory"); }
__device__ __forceinline__ void bulk_wait_read() { asm volatile("cp.async.bulk.wait_group.read 0;" ::: "memory"); }

__device__ __forceinline__ float gelu_tanh(float x) {
    const float u = x * (0.7978845608028654f + 0.035677408136300125f * x * x);
    float t;
    asm("tanh.approx.f32 %0, %1;" : "=f"(t) : "f"(u));
    const float h = 0.5f * x;
    return fmaf(h, t, h);
}
__device__ __forceinline__ void release_stage(uint32_t bar, uint32_t peer, int lane) {
    if (lane == 0) { mbar_arrive(bar); mbar_arrive_cluster(bar, peer); }
}

constexpr int SM_RING = 163840;
constexpr int SM_Q = 2 * IMG_BYTES, SM_ZERO = SM_Q + 24576;
constexpr int G2_STAGE = 8192 + 20480;
constexpr int SM_MISC = 229376;
constexpr int SM_BIAS = SM_MISC, SM_RED = SM_BIAS + 768, SM_BAR = SM_RED + 128;
constexpr int B_A = 0, B_F1 = 10, B_E1 = 14, B_F2 = 18, B_E2 = 23, B_KV = 28, B_Q = 45, B_F3 = 47, B_E3 = 55, B_ST = 63, B_COUNT = 65;
constexpr int SM_TOTAL = SM_BAR + B_COUNT * 8;

struct Maps { CUtensorMap xn, wqkv, w1, h, o, wo, w2; };

__device__ __forceinline__ uint32_t bf2_fma(uint32_t a, uint32_t b, uint32_t c) {
    uint32_t r;
    asm("fma.rn.bf16x2 %0, %1, %2, %3;" : "=r"(r) : "r"(a), "r"(b), "r"(c));
    return r;
}
__device__ __forceinline__ uint32_t lop_and_or(uint32_t a, uint32_t m, uint32_t o) {
    uint32_t r;
    asm("lop3.b32 %0, %1, %2, %3, 0xEA;" : "=r"(r) : "r"(a), "r"(m), "r"(o));
    return r;
}
struct ExpConst { uint32_t mask, slope; };
__device__ __forceinline__ ExpConst make_exp_const() {
    ExpConst k;
    asm volatile("mov.b32 %0, 0x007F007F;" : "=r"(k.mask));
    asm volatile("mov.b32 %0, 0x3EF83EF8;" : "=r"(k.slope));
    return k;
}
__device__ __forceinline__ uint32_t exp2_pair_fma(float t0, float t1, const ExpConst& k) {
    const uint32_t L = __byte_perm(__float_as_uint(t0), __float_as_uint(t1), 0x6521);
    const uint32_t g = lop_and_or(L, k.mask, 0x3F803F80u);
    const uint32_t u = bf2_fma(g, k.slope, 0xBF37BF37u);
    const uint32_t e = bf2_fma(u, u, 0xBD71BD71u);
    return bf2_fma(L, e, L);
}
template <int SHIFT>
__device__ __forceinline__ void exp_tile(const float (&s)[32], uint32_t (&p)[16], const ExpConst& k) {
#pragma unroll
    for (int b = 0; b < 8; b++) {
        if ((EMU_MASK >> (b + SHIFT)) & 1) {
            p[2 * b] = exp2_pair_fma(s[4 * b], s[4 * b + 1], k);
            p[2 * b + 1] = exp2_pair_fma(s[4 * b + 2], s[4 * b + 3], k);
        } else {
            p[2 * b] = pack_bf16(ex2(s[4 * b]), ex2(s[4 * b + 1]));
            p[2 * b + 1] = pack_bf16(ex2(s[4 * b + 2]), ex2(s[4 * b + 3]));
        }
    }
}

__device__ __forceinline__ void qk_tile(float (&s)[32], uint64_t dQ, uint64_t dQ2, uint64_t dK) {
    wg_fence();
    wgmma_n64_ss_z(s, dQ, dK);
    wgmma_n64_ss(s, dQ2, dK + 16, 1);
    wg_commit();
}
__device__ __forceinline__ void pv_tile(float (&o)[12], const uint32_t (&p)[16], uint64_t dV) {
    wg_fence();
#pragma unroll
    for (int ks = 0; ks < 4; ks++)
        wgmma_n24_rs_tb(o, p[4 * ks], p[4 * ks + 1], p[4 * ks + 2], p[4 * ks + 3], dV + ks * 48, 1);
    wg_commit();
}
__device__ __forceinline__ void store_o(const float (&o)[12], int h, int rbase, int lane) {
    const int g = lane >> 2, c = lane & 3;
    const bool odd = h & 1;
    const int lsrc = (lane & ~3) | (odd ? 0 : 2);
    const float i0 = 1.f / __shfl_sync(~0u, o[8], lsrc), i1 = 1.f / __shfl_sync(~0u, o[10], lsrc);
    __nv_bfloat16* dst = g_o + (size_t)(rbase + g) * DM + h * 20;
    const int d0 = (odd ? 4 : 0) + 2 * c, d1 = d0 + 8, d2 = odd ? 2 * c - 4 : 16 + 2 * c;
    *(uint32_t*)(dst + d0) = pack_bf16(o[0] * i0, o[1] * i0);
    *(uint32_t*)(dst + d1) = pack_bf16(o[4] * i0, o[5] * i0);
    *(uint32_t*)(dst + 8 * DM + d0) = pack_bf16(o[2] * i1, o[3] * i1);
    *(uint32_t*)(dst + 8 * DM + d1) = pack_bf16(o[6] * i1, o[7] * i1);
    if (odd ? (c >= 2) : (c < 2)) {
        *(uint32_t*)(dst + d2) = pack_bf16(o[8] * i0, o[9] * i0);
        *(uint32_t*)(dst + 8 * DM + d2) = pack_bf16(o[10] * i1, o[11] * i1);
    }
}

__device__ __forceinline__ void attn_rows_maxshift(uint32_t sK, uint32_t barKV, uint64_t dQ, uint64_t dQ2, int h, int rbase) {
    const int lane = threadIdx.x & 31;
    const uint64_t dK0 = make_desc(sK, 128, 384, 0), dV0 = make_desc(sK + IMG_BYTES, 384, 128, 0);
    float o[12], s[32];
    uint32_t p[16];
#pragma unroll
    for (int i = 0; i < 12; i++) o[i] = 0.f;
    float m0 = -3.0e38f, m1 = -3.0e38f;
    mbar_wait(barKV + 128, 0);
#pragma unroll 1
    for (int t = 0; t < 32; t++) {
        mbar_wait(barKV + (t >> 1) * 8, 0);
        qk_tile(s, dQ, dQ2, dK0 + t * 192);
        wg_wait<0>();
        fence_regs(s);
        const uint32_t mask = EMU_MASK >> ((t & 1) * 8);
        float n0 = m0, n1 = m1;
#pragma unroll
        for (int b = 0; b < 8; b++) {
            const bool emu = (mask >> b) & 1;
            const float f = emu ? 0.5f : 1.f, off = emu ? -383.00390625f : 0.f;
#pragma unroll
            for (int i = 0; i < 4; i++) s[4 * b + i] = fmaf(s[4 * b + i], f, off);
            n0 = fmaxf(n0, fmaxf(s[4 * b], s[4 * b + 1]));
            n1 = fmaxf(n1, fmaxf(s[4 * b + 2], s[4 * b + 3]));
        }
        n0 = fmaxf(n0, __shfl_xor_sync(~0u, n0, 1)); n0 = fmaxf(n0, __shfl_xor_sync(~0u, n0, 2));
        n1 = fmaxf(n1, __shfl_xor_sync(~0u, n1, 1)); n1 = fmaxf(n1, __shfl_xor_sync(~0u, n1, 2));
        const float c0 = ex2(m0 - n0), c1 = ex2(m1 - n1);
        m0 = n0; m1 = n1;
#pragma unroll
        for (int b = 0; b < 3; b++) { o[4 * b] *= c0; o[4 * b + 1] *= c0; o[4 * b + 2] *= c1; o[4 * b + 3] *= c1; }
#pragma unroll
        for (int b = 0; b < 8; b++) {
            p[2 * b] = pack_bf16(ex2(s[4 * b] - m0), ex2(s[4 * b + 1] - m0));
            p[2 * b + 1] = pack_bf16(ex2(s[4 * b + 2] - m1), ex2(s[4 * b + 3] - m1));
        }
        pv_tile(o, p, dV0 + t * 192);
        wg_wait<0>();
        fence_regs(o);
    }
    store_o(o, h, rbase, lane);
}

__global__ void __launch_bounds__(512, 1) __cluster_dims__(2, 1, 1)
k_fused(const __grid_constant__ Maps tm, const __nv_bfloat16* __restrict__ x, const uint8_t* __restrict__ wqkv,
        const uint8_t* __restrict__ w1, const uint8_t* __restrict__ w2, const uint8_t* __restrict__ wo,
        const __nv_bfloat16* __restrict__ b1, const __nv_bfloat16* __restrict__ b2, __nv_bfloat16* __restrict__ out) {
    extern __shared__ __align__(1024) uint8_t smem[];
    const uint32_t sb = smem_u32(smem);
    const uint32_t bar = sb + SM_BAR;
    const int warp = __shfl_sync(~0u, threadIdx.x >> 5, 0), lane = threadIdx.x & 31;
    const int wgi = warp >> 2, w4 = warp & 3, g = lane >> 2, c = lane & 3;
    const uint32_t rank = blockIdx.x & 1, peer = rank ^ 1;
    const int cl = blockIdx.x >> 1;
    const int cg = cl & 7, rb = (cl >> 3) * 2 + rank;
    const uint32_t epoch = *(volatile uint32_t*)&g_epoch;

    if (threadIdx.x == 0) TL(0, 0);
    if (threadIdx.x == 160) IT(2, 0);
    {
        const int row = rb * 128 + cg * 16 + warp;
        const uint2* src = reinterpret_cast<const uint2*>(x + (size_t)row * DM);
        uint2 v[5];
#pragma unroll
        for (int i = 0; i < 5; i++) v[i] = __ldg(src + lane + 32 * i);
        if (threadIdx.x < B_COUNT) {
            const int i = threadIdx.x;
            const int cnt = (i >= B_E1 && i < B_F2) || (i >= B_E2 && i < B_KV) ? 16 : (i >= B_E3 && i <= B_ST) ? 8 : i == B_ST + 1 ? 2 : 1;
            mbar_init(bar + i * 8, cnt);
            fence_barrier_init();
        }
        if (warp == 3 && elect_one()) {
            prefetch_l2(wqkv + blockIdx.x * 19200, 19200);
            prefetch_l2(w1 + blockIdx.x * 15360, 15360);
            prefetch_l2(w2 + blockIdx.x * 15360, 15360);
            prefetch_l2(wo + blockIdx.x * 6400, 6400);
            prefetch_map(&tm.xn); prefetch_map(&tm.wqkv); prefetch_map(&tm.w1); prefetch_map(&tm.h);
        }
        if (threadIdx.x == 160) IT(2, 1);
        __syncthreads();
        if (threadIdx.x == 160) IT(2, 2);
        cluster_arrive_relaxed();
        cluster_wait();
        if (threadIdx.x == 160) IT(2, 3);
        if (threadIdx.x == 0) TL(0, 1);
        if (warp == 0 && elect_one()) {
#pragma unroll
            for (int it = 0; it < 4; it++) {
                const uint32_t dst = sb + SM_RING + it * 16384 + rank * 8192, fb = bar + (B_F1 + it) * 8;
                const int c0 = cg * 240 + rank * 120;
                mbar_expect_tx(fb, 16384);
                tma_load_mc(dst, &tm.wqkv, c0, it * 32, fb, 3);
                tma_load_mc(dst + 4096, &tm.wqkv, c0 + 64, it * 32, fb, 3);
            }
        }
        float f[20];
#pragma unroll
        for (int i = 0; i < 5; i++) {
            f[4 * i] = bf_lo(v[i].x); f[4 * i + 1] = bf_hi(v[i].x);
            f[4 * i + 2] = bf_lo(v[i].y); f[4 * i + 3] = bf_hi(v[i].y);
        }
        float s = 0.f;
#pragma unroll
        for (int i = 0; i < 20; i++) s += f[i];
#pragma unroll
        for (int o = 16; o; o >>= 1) s += __shfl_xor_sync(~0u, s, o);
        const float mu = s * (1.f / DM);
        if (threadIdx.x == 160) IT(2, 4);
        float q = 0.f;
#pragma unroll
        for (int i = 0; i < 20; i++) { f[i] -= mu; q += f[i] * f[i]; }
#pragma unroll
        for (int o = 16; o; o >>= 1) q += __shfl_xor_sync(~0u, q, o);
        const float var = q * (1.f / DM);
        const float r1 = 1.f / sqrtf(var + LN_EPS);
        uint2* dst = reinterpret_cast<uint2*>(g_xn + (size_t)row * DM);
#pragma unroll
        for (int i = 0; i < 5; i++) {
            uint2 w;
            w.x = pack_bf16(f[4 * i] * r1, f[4 * i + 1] * r1);
            w.y = pack_bf16(f[4 * i + 2] * r1, f[4 * i + 3] * r1);
            dst[lane + 32 * i] = w;
        }
        if (threadIdx.x >= 416)
            reinterpret_cast<uint32_t*>(smem + SM_BIAS)[threadIdx.x - 416] =
                __ldg(reinterpret_cast<const uint32_t*>(b1 + cg * 192) + (threadIdx.x - 416));
        if (lane == 0) g_r2[row] = 1.f / sqrtf(var * r1 * r1 + LN_EPS);
        if (threadIdx.x == 0) TL(0, 2);
        if (threadIdx.x == 160) IT(2, 5);
        __syncthreads();
        if (threadIdx.x == 160) IT(2, 6);
        if (threadIdx.x == 0) { cnt_signal(CNT_LN + rb); TL(0, 3); IT(2, 7); }
    }

    {
        const uint32_t sB = sb + SM_RING;
        if (threadIdx.x == 0) TL(1, 0);
        if (wgi < 2) {
            reg_dealloc<40>();
            if (warp == 0) {
                if (elect_one()) { cnt_wait(CNT_LN + rb, (epoch + 1) * 8); IT(2, 8); }
                __syncwarp();
#pragma unroll 1
                for (int it = 0; it < 20; it++) {
                    if (it >= 4) {
                        const int s = it & 3;
                        mbar_wait(bar + (B_E1 + s) * 8, ((it >> 2) - 1) & 1);
                        if (elect_one()) {
                            const uint32_t dst = sB + s * 16384 + rank * 8192, fb = bar + (B_F1 + s) * 8;
                            const int c0 = cg * 240 + rank * 120;
                            mbar_expect_tx(fb, 16384);
                            tma_load_mc(dst, &tm.wqkv, c0, it * 32, fb, 3);
                            tma_load_mc(dst + 4096, &tm.wqkv, c0 + 64, it * 32, fb, 3);
                        }
                        __syncwarp();
                    }
                    const int kb = it < 3 ? it : (it & 1) ? 10 : (it >> 1) + 1;
                    if (kb < 10 && elect_one()) {
                        mbar_expect_tx(bar + (B_A + kb) * 8, 16384);
                        tma_load(sb + kb * 16384, &tm.xn, kb * 64, rb * 128, bar + (B_A + kb) * 8);
                    }
                    __syncwarp();
                }
#pragma unroll 1
                for (int it = 0; it < 20; it++) {
                    const int s = it % 5;
                    if (it < 5) { if (it != 3) mbar_wait(bar + (B_E1 + (it == 4 ? 3 : it)) * 8, 0); }
                    else mbar_wait(bar + (B_E2 + s) * 8, ((it / 5) - 1) & 1);
                    if (elect_one()) {
                        const uint32_t dst = sB + s * 12288, fb = bar + (B_F2 + s) * 8;
                        mbar_expect_tx(fb, 12288);
                        if ((it & 1) == (int)rank) {
                            tma_load_mc(dst, &tm.w1, cg * 192, it * 32, fb, 3);
                            tma_load_mc(dst + 4096, &tm.w1, cg * 192 + 64, it * 32, fb, 3);
                        } else {
                            tma_load_mc(dst + 8192, &tm.w1, cg * 192 + 128, it * 32, fb, 3);
                        }
                    }
                    __syncwarp();
                }
            } else if (warp == 4) {
                mbar_wait(bar + B_ST * 8, 0);
                if (elect_one()) cnt_signal(CNT_QKV + cg);
                __syncwarp();
                mbar_wait(bar + (B_ST + 1) * 8, 0);
                if (elect_one()) cnt_signal(CNT_H + rb);
                __syncwarp();
            }
            asm volatile("bar.sync %0, 128;" ::"r"(wgi + 3) : "memory");
            reg_alloc<128>();
        } else {
            reg_alloc<216>();
            const int wi = wgi - 2;
            const int row0 = rb * 128 + wi * 64 + w4 * 16 + g;
            const uint32_t sAw = sb + wi * 8192;
            const int rbk = row0 >> 3, hs0 = cg * 12;
            float acc1[2][60];
#pragma unroll 1
            for (int it = 0; it < 20; it++) {
                const int s = it & 3;
                if (!(it & 1)) mbar_wait(bar + (B_A + (it >> 1)) * 8, 0);
                if (threadIdx.x == 256) IT(0, it);
                mbar_wait(bar + (B_F1 + s) * 8, (it >> 2) & 1);
                if (threadIdx.x == 256) IT(1, it);
                wg_fence();
                const uint64_t dA = make_desc(sAw + (it >> 1) * 16384 + (it & 1) * 64, 16, 1024, 1);
                const uint64_t dB = make_desc(sB + s * 16384, 4096, 1024, 1);
                wgmma_n120_ss_tb(acc1[0], dA, dB, it > 0);
                wgmma_n120_ss_tb(acc1[1], dA, dB + 512, it > 0);
                wgmma_n120_ss_tb(acc1[0], dA + 2, dB + 128, 1);
                wgmma_n120_ss_tb(acc1[1], dA + 2, dB + 640, 1);
                wg_commit();
                if (it > 0) { wg_wait<1>(); release_stage(bar + (B_E1 + ((it - 1) & 3)) * 8, peer, lane); }
            }
            wg_wait<0>();
            release_stage(bar + (B_E1 + 3) * 8, peer, lane);
            fence_regs(acc1[0]);
            fence_regs(acc1[1]);
            if (threadIdx.x == 256) TL(1, 1);
            const float r20 = g_r2[row0], r21 = g_r2[row0 + 8];
            uint8_t* img = g_img + (size_t)hs0 * IMG_BYTES + rbk * 384 + g * 16 + c * 4;
            const bool emu0 = (EMU_MASK >> (rbk & 15)) & 1, emu1 = (EMU_MASK >> ((rbk + 1) & 15)) & 1;
            const bool low = c < 2;
            uint32_t pk[60];
#pragma unroll
            for (int m = 0; m < 6; m++) {
                const int which = (hs0 + 2 * m) >> 5;
                const float m0 = which == 0 ? QSCALE : (which == 1 && emu0) ? 2.f : 1.f;
                const float m1 = which == 0 ? QSCALE : (which == 1 && emu1) ? 2.f : 1.f;
                const float* a = &acc1[m / 3][20 * (m % 3)];
#pragma unroll
                for (int b = 0; b < 5; b++) {
                    pk[10 * m + 2 * b] = pack_bf16(a[4 * b] * m0, a[4 * b + 1] * m0);
                    pk[10 * m + 2 * b + 1] = pack_bf16(a[4 * b + 2] * m1, a[4 * b + 3] * m1);
                }
            }
            float acc2[96];
#pragma unroll
            for (int it = 0; it < 20; it++) {
                const int s = it % 5;
                if (threadIdx.x == 256) IT(0, 20 + it);
                mbar_wait(bar + (B_F2 + s) * 8, (it / 5) & 1);
                if (threadIdx.x == 256) IT(1, 20 + it);
                wg_fence();
                const uint64_t dA = make_desc(sAw + (it >> 1) * 16384 + (it & 1) * 64, 16, 1024, 1);
                const uint64_t dB = make_desc(sB + s * 12288, 4096, 1024, 1);
                if (it == 0) wgmma_n192_ss_tb_z(acc2, dA, dB); else wgmma_n192_ss_tb(acc2, dA, dB, 1);
                wgmma_n192_ss_tb(acc2, dA + 2, dB + 128, 1);
                wg_commit();
                if (it > 0) {
                    wg_wait<1>();
                    if (it <= 15) release_stage(bar + (B_E2 + (it - 1) % 5) * 8, peer, lane);
                }
                if (it < 12) {
                    const int m = it / 2, part = it % 2;
                    const int hs = hs0 + 2 * m, which = hs >> 5;
                    const uint32_t* a = pk + 10 * m;
                    uint8_t* pe = img + (2 * m) * IMG_BYTES;
                    uint8_t* po = pe + IMG_BYTES;
                    if (part == 0) {
                        const uint32_t padv = which == 0 ? 0x3F803F80u : which == 1 ? 0xBFFF4440u : 0x00003F80u;
                        const uint32_t p0 = ((c & 1) || (which == 1 && !emu0)) ? 0u : padv;
                        const uint32_t p1 = ((c & 1) || (which == 1 && !emu1)) ? 0u : padv;
                        *(uint32_t*)(pe) = a[0];
                        *(uint32_t*)(pe + 128) = a[2];
                        *(uint32_t*)(pe + 256) = low ? a[4] : p0;
                        *(uint32_t*)(pe + 384) = a[1];
                        *(uint32_t*)(pe + 512) = a[3];
                        *(uint32_t*)(pe + 640) = low ? a[5] : p1;
                        *(uint32_t*)(po + 256) = low ? p0 : a[4];
                        *(uint32_t*)(po + 640) = low ? p1 : a[5];
                    } else {
                        *(uint32_t*)(po) = a[6];
                        *(uint32_t*)(po + 128) = a[8];
                        *(uint32_t*)(po + 384) = a[7];
                        *(uint32_t*)(po + 512) = a[9];
                        if (which < 2) {
                            const uint32_t u0 = bf2_fma(a[4], a[4], 0u), u1 = bf2_fma(a[5], a[5], 0u);
                            const uint32_t pe0 = bf2_fma(a[0], a[0], bf2_fma(a[2], a[2], low ? u0 : 0u));
                            const uint32_t pe1 = bf2_fma(a[1], a[1], bf2_fma(a[3], a[3], low ? u1 : 0u));
                            const uint32_t po0 = bf2_fma(a[6], a[6], bf2_fma(a[8], a[8], low ? 0u : u0));
                            const uint32_t po1 = bf2_fma(a[7], a[7], bf2_fma(a[9], a[9], low ? 0u : u1));
                            const float e0 = bf_lo(pe0) + bf_hi(pe0), e1 = bf_lo(pe1) + bf_hi(pe1);
                            const float o0 = bf_lo(po0) + bf_hi(po0), o1 = bf_lo(po1) + bf_hi(po1);
                            const bool b0 = c & 1, b1_ = c & 2;
                            const float x0 = (b0 ? e1 : e0) + __shfl_xor_sync(~0u, b0 ? e0 : e1, 1);
                            const float x1 = (b0 ? o1 : o0) + __shfl_xor_sync(~0u, b0 ? o0 : o1, 1);
                            float y = (b1_ ? x1 : x0) + __shfl_xor_sync(~0u, b1_ ? x0 : x1, 2);
                            if (which == 1 && (b0 ? emu1 : emu0)) y *= 0.25f;
                            g_nrm[(hs + (c >> 1)) * SEQ + row0 + (c & 1) * 8] = y;
                        }
                    }
                    if (it == 11) { __syncwarp(); if (lane == 0) mbar_arrive(bar + B_ST * 8); }
                }
            }
            wg_wait<0>();
            fence_regs(acc2);
            if (threadIdx.x == 256) TL(1, 2);
            const uint32_t* bias = reinterpret_cast<const uint32_t*>(smem + SM_BIAS) + c;
            const int mrow = w4 * 16 + (lane & 15);
            const uint32_t st_row = sAw + mrow * 128;
#pragma unroll
            for (int j = 0; j < 24; j += 2) {
                const uint32_t bA = bias[j * 4], bB = bias[j * 4 + 4];
                const float* a = acc2 + j * 4;
                const uint32_t r00 = pack_bf16(gelu_tanh(fmaf(a[0], r20, bf_lo(bA))), gelu_tanh(fmaf(a[1], r20, bf_hi(bA))));
                const uint32_t r10 = pack_bf16(gelu_tanh(fmaf(a[2], r21, bf_lo(bA))), gelu_tanh(fmaf(a[3], r21, bf_hi(bA))));
                const uint32_t r01 = pack_bf16(gelu_tanh(fmaf(a[4], r20, bf_lo(bB))), gelu_tanh(fmaf(a[5], r20, bf_hi(bB))));
                const uint32_t r11 = pack_bf16(gelu_tanh(fmaf(a[6], r21, bf_lo(bB))), gelu_tanh(fmaf(a[7], r21, bf_hi(bB))));
                const int chunk = (j & 7) + (lane >> 4);
                stmatrix_x4(st_row + (j >> 3) * 16384 + ((chunk ^ (mrow & 7)) << 4), r00, r10, r01, r11);
            }
            fence_proxy_async();
            asm volatile("bar.sync %0, 128;" ::"r"(wgi + 3) : "memory");
            if (w4 == 0 && elect_one()) {
#pragma unroll
                for (int b = 0; b < 3; b++) tma_store(&tm.h, sAw + b * 16384, cg * 192 + b * 64, rb * 128 + wi * 64);
                bulk_commit();
                bulk_wait_all();
                mbar_arrive(bar + (B_ST + 1) * 8);
            }
            __syncwarp();
            reg_dealloc<128>();
        }
        __syncthreads();
        if (threadIdx.x == 0) TL(1, 3);
    }

    {
        const int h = blockIdx.x >> 2, qb = blockIdx.x & 3;
        const uint32_t sK = sb, sV = sb + IMG_BYTES, barKV = bar + B_KV * 8;
        if (threadIdx.x == 0) TL(2, 0);
        if (threadIdx.x < 192) *reinterpret_cast<uint4*>(smem + SM_ZERO + threadIdx.x * 16) = make_uint4(0, 0, 0, 0);
        fence_proxy_async();
        if (warp == 0) {
            if (elect_one()) {
                cnt_wait(CNT_QKV + h / 12, (epoch + 1) * 16);
                cnt_wait(CNT_QKV + (32 + h) / 12, (epoch + 1) * 16);
                cnt_wait(CNT_QKV + (64 + h) / 12, (epoch + 1) * 16);
                const uint8_t* gK = g_img + (size_t)(32 + h) * IMG_BYTES;
                const uint8_t* gV = g_img + (size_t)(64 + h) * IMG_BYTES;
                const uint8_t* gQ = g_img + (size_t)h * IMG_BYTES + qb * 64 * 384;
                mbar_expect_tx(barKV + 128, 6144);
                bulk_load(sK, gK, 6144, barKV + 128);
                for (int p = 0; p < 2; p++) {
                    mbar_expect_tx(bar + (B_Q + p) * 8, 12288);
                    bulk_load(sb + SM_Q + p * 12288, gQ + p * 12288, 12288, bar + (B_Q + p) * 8);
                }
                for (int i = 0; i < 16; i++) {
                    mbar_expect_tx(barKV + i * 8, i < 15 ? 12288 : 6144);
                    bulk_load(sV + i * 6144, gV + i * 6144, 6144, barKV + i * 8);
                    if (i < 15) bulk_load(sK + (i + 1) * 6144, gK + (i + 1) * 6144, 6144, barKV + i * 8);
                }
            }
            __syncwarp();
        }
        __syncthreads();
        if (threadIdx.x == 0) TL(2, 1);
        float* red = reinterpret_cast<float*>(smem + SM_RED);
        float kmax = 0.f, qmax = __ldcg(g_nrm + h * SEQ + qb * 512 + threadIdx.x);
#pragma unroll
        for (int i = 0; i < 4; i++) kmax = fmaxf(kmax, __ldcg(g_nrm + (32 + h) * SEQ + i * 512 + threadIdx.x));
#pragma unroll
        for (int o = 16; o; o >>= 1) {
            kmax = fmaxf(kmax, __shfl_xor_sync(~0u, kmax, o));
            qmax = fmaxf(qmax, __shfl_xor_sync(~0u, qmax, o));
        }
        if (lane == 0) { red[warp] = kmax; red[16 + warp] = qmax; }
        __syncthreads();
        kmax = red[lane & 15]; qmax = red[16 + (lane & 15)];
#pragma unroll
        for (int o = 8; o; o >>= 1) {
            kmax = fmaxf(kmax, __shfl_xor_sync(~0u, kmax, o));
            qmax = fmaxf(qmax, __shfl_xor_sync(~0u, qmax, o));
        }
        const bool safe = __all_sync(~0u, kmax * qmax * 1.1f <= SAFE_BOUND * SAFE_BOUND);
        const uint64_t dK0 = make_desc(sK, 128, 384, 0), dV0 = make_desc(sV, 384, 128, 0);
        if (!safe) {
#pragma unroll 1
            for (int pass = 0; pass < 2; pass++) {
                const uint32_t sQ = sb + SM_Q + pass * 12288 + wgi * 3072;
                mbar_wait(bar + (B_Q + pass) * 8, 0);
                if (lane < 16) *reinterpret_cast<uint32_t*>(smem + (sQ - sb) + (w4 * 2 + (lane >> 3)) * 384 + 256 + (lane & 7) * 16 + ((h & 1) ? 0 : 8)) = 0u;
                fence_proxy_async();
                asm volatile("bar.sync %0, 128;" ::"r"(wgi + 3) : "memory");
                attn_rows_maxshift(sK, barKV, make_desc(sQ, 128, 384, 0), make_desc(sQ + 256, sb + SM_ZERO - (sQ + 256), 384, 0), h,
                                   qb * 512 + pass * 256 + wgi * 64 + w4 * 16);
            }
        } else {
            const ExpConst kc = make_exp_const();
#pragma unroll 1
            for (int pass = 0; pass < 2; pass++) {
                const int rbase = qb * 512 + pass * 256 + wgi * 64 + w4 * 16;
                const uint32_t sQ = sb + SM_Q + pass * 12288 + wgi * 3072;
                const uint64_t dQ = make_desc(sQ, 128, 384, 0), dQ2 = make_desc(sQ + 256, sb + SM_ZERO - (sQ + 256), 384, 0);
                float o[12], sa[32], sc[32];
                uint32_t p[16];
#pragma unroll
                for (int i = 0; i < 12; i++) o[i] = 0.f;
                fence_regs(o);
                mbar_wait(bar + (B_Q + pass) * 8, 0);
                mbar_wait(barKV + 128, 0);
                qk_tile(sa, dQ, dQ2, dK0);
                wg_wait<0>();
                fence_regs(sa);
                uint64_t dK = dK0, dV = dV0;
                uint32_t bj = barKV;
#pragma unroll 1
                for (int j = 0; j < 16; j++) {
                    mbar_wait(bj, 0);
                    qk_tile(sc, dQ, dQ2, dK + 192);
                    wg_wait<1>();
                    exp_tile<0>(sa, p, kc);
                    pv_tile(o, p, dV);
                    wg_wait<1>();
                    fence_regs(sc);
                    mbar_wait(bj, 0);
                    qk_tile(sa, dQ, dQ2, dK + 384);
                    wg_wait<1>();
                    exp_tile<8>(sc, p, kc);
                    pv_tile(o, p, dV + 192);
                    wg_wait<1>();
                    fence_regs(sa);
                    dK += 384; dV += 384; bj += 8;
                }
                wg_wait<0>();
                fence_regs(o);
                store_o(o, h, rbase, lane);
                if (threadIdx.x == 0) TL(2, 2 + pass);
            }
        }
        __syncthreads();
        if (threadIdx.x == 0) cnt_signal(CNT_O + qb);
        cluster_arrive_relaxed();
    }

    {
        const int ct = cl & 3, rt = (cl >> 2) * 2 + rank;
        if (threadIdx.x == 0) TL(3, 0);
        const int orow = threadIdx.x >> 3, oseg = threadIdx.x & 7;
        const size_t ooff = (size_t)(rt * 64 + orow) * DM + ct * 160 + oseg * 20;
        uint2 xr[5], br[5];
#pragma unroll
        for (int i = 0; i < 5; i++) {
            xr[i] = __ldg(reinterpret_cast<const uint2*>(x + ooff) + i);
            br[i] = __ldg(reinterpret_cast<const uint2*>(b2 + ct * 160 + oseg * 20) + i);
        }
        cluster_wait();
        float* stg = reinterpret_cast<float*>(smem);
        if (warp == 4) {
            if (elect_one()) { prefetch_map(&tm.h); prefetch_map(&tm.o); prefetch_map(&tm.w2); prefetch_map(&tm.wo); cnt_wait(CNT_H + (rt >> 1), (epoch + 1) * 8); }
            __syncwarp();
#pragma unroll 1
            for (int kb = 0; kb < 34; kb++) {
                const int s = kb & 7;
                if (kb >= 8) mbar_wait(bar + (B_E3 + s) * 8, ((kb >> 3) - 1) & 1);
                if (elect_one()) {
                    if (kb == 24) { cnt_wait(CNT_O + (rt >> 3), (epoch + 1) * 32); TL(3, 1); }
                    const uint32_t dst = sb + s * G2_STAGE, fb = bar + (B_F3 + s) * 8;
                    const CUtensorMap* mA = kb < 24 ? &tm.h : &tm.o;
                    const CUtensorMap* mB = kb < 24 ? &tm.w2 : &tm.wo;
                    const int k0 = (kb < 24 ? kb : kb - 24) * 64;
                    mbar_expect_tx(fb, G2_STAGE);
                    tma_load(dst, mA, k0, rt * 64, fb);
                    const int first = ((kb & 1) == (int)rank) ? 0 : 3, last = ((kb & 1) == (int)rank) ? 3 : 5;
                    for (int b = first; b < last; b++) tma_load_mc(dst + 8192 + b * 4096, mB, ct * 160 + b * 32, k0, fb, 3);
                }
                __syncwarp();
            }
        } else if (wgi == 0) {
            float acc[80];
#pragma unroll 1
            for (int kb = 0; kb < 34; kb++) {
                const int s = kb & 7;
                mbar_wait(bar + (B_F3 + s) * 8, (kb >> 3) & 1);
                wg_fence();
                const uint64_t dA = make_desc(sb + s * G2_STAGE, 16, 1024, 1);
                const uint64_t dB = make_desc(sb + s * G2_STAGE + 8192, 4096, 512, 2);
#pragma unroll
                for (int kk = 0; kk < 4; kk++) wgmma_n160_ss_tb(acc, dA + kk * 2, dB + kk * 64, (kb | kk) != 0);
                wg_commit();
                if (kb > 0) {
                    wg_wait<1>();
                    if (kb <= 26) release_stage(bar + (B_E3 + ((kb - 1) & 7)) * 8, peer, lane);
                }
            }
            wg_wait<0>();
            fence_regs(acc);
            if (threadIdx.x == 0) TL(3, 2);
            const int r = w4 * 16 + g;
#pragma unroll
            for (int j = 0; j < 20; j++) {
                *reinterpret_cast<float2*>(stg + r * 168 + j * 8 + 2 * c) = make_float2(acc[4 * j], acc[4 * j + 1]);
                *reinterpret_cast<float2*>(stg + (r + 8) * 168 + j * 8 + 2 * c) = make_float2(acc[4 * j + 2], acc[4 * j + 3]);
            }
        }
        __syncthreads();
        const float4* sp = reinterpret_cast<const float4*>(stg + orow * 168 + oseg * 20);
#pragma unroll
        for (int i = 0; i < 5; i++) {
            const float4 a = sp[i];
            uint2 w;
            w.x = pack_bf16(a.x + bf_lo(br[i].x) + bf_lo(xr[i].x), a.y + bf_hi(br[i].x) + bf_hi(xr[i].x));
            w.y = pack_bf16(a.z + bf_lo(br[i].y) + bf_lo(xr[i].y), a.w + bf_hi(br[i].y) + bf_hi(xr[i].y));
            reinterpret_cast<uint2*>(out + ooff)[i] = w;
        }
        if (blockIdx.x == 0 && threadIdx.x == 0) g_epoch = epoch + 1;
        if (threadIdx.x == 0) TL(3, 3);
    }
    cluster_arrive_relaxed();
    cluster_wait();
}

typedef CUresult (*EncodeTiledFn)(CUtensorMap*, CUtensorMapDataType, cuuint32_t, void*, const cuuint64_t*,
                                  const cuuint64_t*, const cuuint32_t*, const cuuint32_t*, CUtensorMapInterleave,
                                  CUtensorMapSwizzle, CUtensorMapL2promotion, CUtensorMapFloatOOBfill);

CUtensorMap make_map(EncodeTiledFn enc, const void* ptr, int rows, int cols, int box_rows, int box_cols,
                     CUtensorMapSwizzle swz) {
    CUtensorMap m;
    cuuint64_t gd[2] = {(cuuint64_t)cols, (cuuint64_t)rows};
    cuuint64_t gs[1] = {(cuuint64_t)cols * 2};
    cuuint32_t bd[2] = {(cuuint32_t)box_cols, (cuuint32_t)box_rows};
    cuuint32_t es[2] = {1, 1};
    enc(&m, CU_TENSOR_MAP_DATA_TYPE_BFLOAT16, 2, const_cast<void*>(ptr), gd, gs, bd, es, CU_TENSOR_MAP_INTERLEAVE_NONE,
        swz, CU_TENSOR_MAP_L2_PROMOTION_L2_128B, CU_TENSOR_MAP_FLOAT_OOB_FILL_NONE);
    return m;
}

}

extern "C" void kernel_launch(void* const* d_in, const int* in_sizes, int n_in, void* d_out, int out_size) {
    (void)in_sizes; (void)n_in; (void)out_size;
    const __nv_bfloat16* x = (const __nv_bfloat16*)d_in[0];
    const __nv_bfloat16* wqkv = (const __nv_bfloat16*)d_in[1];
    const __nv_bfloat16* wo = (const __nv_bfloat16*)d_in[2];
    const __nv_bfloat16* w1 = (const __nv_bfloat16*)d_in[4];
    const __nv_bfloat16* b1 = (const __nv_bfloat16*)d_in[5];
    const __nv_bfloat16* w2 = (const __nv_bfloat16*)d_in[6];
    const __nv_bfloat16* b2 = (const __nv_bfloat16*)d_in[7];
    __nv_bfloat16* out = (__nv_bfloat16*)d_out;

    static EncodeTiledFn enc = nullptr;
    static void *p_xn, *p_h, *p_o;
    if (!enc) {
        cudaDriverEntryPointQueryResult qr;
        cudaGetDriverEntryPoint("cuTensorMapEncodeTiled", (void**)&enc, cudaEnableDefault, &qr);
        cudaGetSymbolAddress(&p_xn, g_xn);
        cudaGetSymbolAddress(&p_h, g_h);
        cudaGetSymbolAddress(&p_o, g_o);
        cudaFuncSetAttribute(k_fused, cudaFuncAttributeMaxDynamicSharedMemorySize, SM_TOTAL);
    }
    Maps tm;
    tm.xn = make_map(enc, p_xn, SEQ, DM, 128, 64, CU_TENSOR_MAP_SWIZZLE_128B);
    tm.wqkv = make_map(enc, wqkv, DM, 3 * DM, 32, 64, CU_TENSOR_MAP_SWIZZLE_128B);
    tm.w1 = make_map(enc, w1, DM, FF, 32, 64, CU_TENSOR_MAP_SWIZZLE_128B);
    tm.h = make_map(enc, p_h, SEQ, FF, 64, 64, CU_TENSOR_MAP_SWIZZLE_128B);
    tm.o = make_map(enc, p_o, SEQ, DM, 64, 64, CU_TENSOR_MAP_SWIZZLE_128B);
    tm.wo = make_map(enc, wo, DM, DM, 64, 32, CU_TENSOR_MAP_SWIZZLE_64B);
    tm.w2 = make_map(enc, w2, FF, DM, 64, 32, CU_TENSOR_MAP_SWIZZLE_64B);
    k_fused<<<128, 512, SM_TOTAL, cudaStreamPerThread>>>(tm, x, (const uint8_t*)wqkv, (const uint8_t*)w1, (const uint8_t*)w2,
                                                         (const uint8_t*)wo, b1, b2, out);
}
```

```cpp
#include <cuda_runtime.h>
#include <cuda_bf16.h>
#include <cuda.h>
#include <stdint.h>

namespace {

constexpr int SEQ = 2048, DM = 640, FF = 1536;
constexpr float LN_EPS = 1e-5f;

constexpr int IMG_BYTES = 256 * 384;
constexpr uint32_t EMU_MASK = 0xD5D5u;
constexpr float SAFE_BOUND = 80.0f;
constexpr float QSCALE = 0.22360679774997896f * 1.4426950408889634f;

__device__ float4 g_stat[SEQ];
__device__ float2 g_csp[16 * 1728];
__device__ __align__(1024) uint8_t g_img[96 * IMG_BYTES + 1024];
__device__ float g_nrm[64 * SEQ];
__device__ __align__(1024) __nv_bfloat16 g_h[SEQ * FF];
__device__ __align__(1024) __nv_bfloat16 g_o[SEQ * DM];
constexpr int CNT_ST = 0, CNT_QKV = 16, CNT_H = 24, CNT_O = 40, CNT_CS = 44;
__device__ uint32_t g_cnt[52 * 32];
__device__ uint32_t g_epoch;

#define TL(kern, slot) do { } while (0)
#define IT(row, i) do { } while (0)

__device__ __forceinline__ uint32_t smem_u32(const void* p) { return (uint32_t)__cvta_generic_to_shared(p); }
__device__ __forceinline__ void mbar_init(uint32_t bar, int cnt) {
    asm volatile("mbarrier.init.shared::cta.b64 [%0], %1;" ::"r"(bar), "r"(cnt));
}
__device__ __forceinline__ void mbar_expect_tx(uint32_t bar, uint32_t bytes) {
    asm volatile("mbarrier.arrive.expect_tx.shared::cta.b64 _, [%0], %1;" ::"r"(bar), "r"(bytes) : "memory");
}
__device__ __forceinline__ void mbar_wait(uint32_t bar, uint32_t parity) {
    asm volatile("{\n.reg .pred p;\n.reg .u32 n;\nmov.u32 n, 0;\n"
                 "WAIT_LOOP:\nmbarrier.try_wait.parity.shared::cta.b64 p, [%0], %1;\n@p bra WAIT_DONE;\n"
                 "add.u32 n, n, 1;\nsetp.lt.u32 p, n, 4194304;\n@p bra WAIT_LOOP;\nWAIT_DONE:\n}"
                 ::"r"(bar), "r"(parity) : "memory");
}
__device__ __forceinline__ void mbar_arrive(uint32_t bar) {
    asm volatile("mbarrier.arrive.shared::cta.b64 _, [%0];" ::"r"(bar) : "memory");
}
__device__ __forceinline__ void mbar_arrive_cluster(uint32_t bar, uint32_t cta) {
    asm volatile("{\n.reg .b32 ra;\nmapa.shared::cluster.u32 ra, %0, %1;\n"
                 "mbarrier.arrive.shared::cluster.b64 _, [ra];\n}" ::"r"(bar), "r"(cta) : "memory");
}
__device__ __forceinline__ void fence_barrier_init() { asm volatile("fence.mbarrier_init.release.cluster;" ::: "memory"); }
__device__ __forceinline__ void fence_proxy_async() { asm volatile("fence.proxy.async.shared::cta;" ::: "memory"); }
__device__ __forceinline__ void cluster_sync() {
    asm volatile("barrier.cluster.arrive.release.aligned;\nbarrier.cluster.wait.acquire.aligned;" ::: "memory");
}
__device__ __forceinline__ bool elect_one() {
    uint32_t pred;
    asm volatile("{\n.reg .pred p;\nelect.sync _|p, 0xFFFFFFFF;\nselp.b32 %0, 1, 0, p;\n}" : "=r"(pred));
    return pred != 0;
}
__device__ __forceinline__ void pdl_launch() { asm volatile("griddepcontrol.launch_dependents;" ::: "memory"); }
__device__ __forceinline__ void pdl_wait() { asm volatile("griddepcontrol.wait;" ::: "memory"); }
__device__ __forceinline__ void prefetch_map(const CUtensorMap* m) {
    asm volatile("prefetch.tensormap [%0];" ::"l"(m) : "memory");
}
__device__ __forceinline__ void tma_load(uint32_t dst, const CUtensorMap* m, int c0, int c1, uint32_t bar) {
    asm volatile("cp.async.bulk.tensor.2d.shared::cluster.global.mbarrier::complete_tx::bytes [%0], [%1, {%3, %4}], [%2];"
                 ::"r"(dst), "l"(m), "r"(bar), "r"(c0), "r"(c1) : "memory");
}
__device__ __forceinline__ void tma_load_mc(uint32_t dst, const CUtensorMap* m, int c0, int c1, uint32_t bar, uint16_t mask) {
    asm volatile("cp.async.bulk.tensor.2d.shared::cluster.global.mbarrier::complete_tx::bytes.multicast::cluster"
                 " [%0], [%1, {%3, %4}], [%2], %5;"
                 ::"r"(dst), "l"(m), "r"(bar), "r"(c0), "r"(c1), "h"(mask) : "memory");
}
__device__ __forceinline__ void tma_store(const CUtensorMap* m, uint32_t src, int c0, int c1) {
    asm volatile("cp.async.bulk.tensor.2d.global.shared::cta.bulk_group [%0, {%2, %3}], [%1];"
                 ::"l"(m), "r"(src), "r"(c0), "r"(c1) : "memory");
}
__device__ __forceinline__ void bulk_commit() { asm volatile("cp.async.bulk.commit_group;" ::: "memory"); }
__device__ __forceinline__ void bulk_wait_all() { asm volatile("cp.async.bulk.wait_group 0;" ::: "memory"); }
__device__ __forceinline__ void bulk_load(uint32_t dst, const void* src, uint32_t bytes, uint32_t bar) {
    asm volatile("cp.async.bulk.shared::cluster.global.mbarrier::complete_tx::bytes [%0], [%1], %2, [%3];"
                 ::"r"(dst), "l"(src), "r"(bytes), "r"(bar) : "memory");
}
__device__ __forceinline__ void prefetch_l2(const void* p, uint32_t bytes) {
    asm volatile("cp.async.bulk.prefetch.L2.global [%0], %1;" ::"l"(p), "r"(bytes) : "memory");
}
__device__ __forceinline__ void wg_fence() { asm volatile("wgmma.fence.sync.aligned;" ::: "memory"); }
__device__ __forceinline__ void wg_commit() { asm volatile("wgmma.commit_group.sync.aligned;" ::: "memory"); }
template <int N> __device__ __forceinline__ void wg_wait() {
    asm volatile("wgmma.wait_group.sync.aligned %0;" ::"n"(N) : "memory");
}
template <int N> __device__ __forceinline__ void reg_alloc() { asm volatile("setmaxnreg.inc.sync.aligned.u32 %0;" ::"n"(N)); }
template <int N> __device__ __forceinline__ void reg_dealloc() { asm volatile("setmaxnreg.dec.sync.aligned.u32 %0;" ::"n"(N)); }
template <int N> __device__ __forceinline__ void fence_regs(float (&d)[N]) {
#pragma unroll
    for (int i = 0; i < N; i++) asm volatile("" : "+f"(d[i])::"memory");
}
__device__ __forceinline__ uint64_t make_desc(uint32_t addr, uint32_t lbo, uint32_t sbo, uint32_t swz) {
    return (uint64_t)((addr & 0x3FFFF) >> 4) | ((uint64_t)(lbo >> 4) << 16) | ((uint64_t)(sbo >> 4) << 32) |
           ((uint64_t)swz << 62);
}
__device__ __forceinline__ uint32_t pack_bf16(float lo, float hi) {
    uint32_t r;
    asm("cvt.rn.bf16x2.f32 %0, %1, %2;" : "=r"(r) : "f"(hi), "f"(lo));
    return r;
}
__device__ __forceinline__ float ex2(float x) {
    float r;
    asm("ex2.approx.ftz.f32 %0, %1;" : "=f"(r) : "f"(x));
    return r;
}
__device__ __forceinline__ float bf_lo(uint32_t v) { return __uint_as_float(v << 16); }
__device__ __forceinline__ float bf_hi(uint32_t v) { return __uint_as_float(v & 0xFFFF0000u); }
__device__ __forceinline__ void stmatrix_x4(uint32_t addr, uint32_t r0, uint32_t r1, uint32_t r2, uint32_t r3) {
    asm volatile("stmatrix.sync.aligned.m8n8.x4.shared.b16 [%0], {%1, %2, %3, %4};"
                 ::"r"(addr), "r"(r0), "r"(r1), "r"(r2), "r"(r3) : "memory");
}

__device__ __forceinline__ void wgmma_n120_ss_tb(float (&d)[60], uint64_t descA, uint64_t descB, int scaleD) {
    asm volatile("{\n.reg .pred p;\nsetp.ne.b32 p, %62, 0;\n"
        "wgmma.mma_async.sync.aligned.m64n120k16.f32.bf16.bf16 {"
        "%0, %1, %2, %3, %4, %5, %6, %7, %8, %9, %10, %11, %12, %13, %14, %15, "
        "%16, %17, %18, %19, %20, %21, %22, %23, %24, %25, %26, %27, %28, %29, %30, %31, "
        "%32, %33, %34, %35, %36, %37, %38, %39, %40, %41, %42, %43, %44, %45, %46, %47, "
        "%48, %49, %50, %51, %52, %53, %54, %55, %56, %57, %58, %59}, "
        "%60, %61, p, 1, 1, 0, 1;\n}\n"
        : "+f"(d[0]), "+f"(d[1]), "+f"(d[2]), "+f"(d[3]), "+f"(d[4]), "+f"(d[5]), "+f"(d[6]), "+f"(d[7]),
          "+f"(d[8]), "+f"(d[9]), "+f"(d[10]), "+f"(d[11]), "+f"(d[12]), "+f"(d[13]), "+f"(d[14]), "+f"(d[15]),
          "+f"(d[16]), "+f"(d[17]), "+f"(d[18]), "+f"(d[19]), "+f"(d[20]), "+f"(d[21]), "+f"(d[22]), "+f"(d[23]),
          "+f"(d[24]), "+f"(d[25]), "+f"(d[26]), "+f"(d[27]), "+f"(d[28]), "+f"(d[29]), "+f"(d[30]), "+f"(d[31]),
          "+f"(d[32]), "+f"(d[33]), "+f"(d[34]), "+f"(d[35]), "+f"(d[36]), "+f"(d[37]), "+f"(d[38]), "+f"(d[39]),
          "+f"(d[40]), "+f"(d[41]), "+f"(d[42]), "+f"(d[43]), "+f"(d[44]), "+f"(d[45]), "+f"(d[46]), "+f"(d[47]),
          "+f"(d[48]), "+f"(d[49]), "+f"(d[50]), "+f"(d[51]), "+f"(d[52]), "+f"(d[53]), "+f"(d[54]), "+f"(d[55]),
          "+f"(d[56]), "+f"(d[57]), "+f"(d[58]), "+f"(d[59])
        : "l"(descA), "l"(descB), "r"(scaleD));
}

__device__ __forceinline__ void wgmma_n192_ss_tb(float (&d)[96], uint64_t descA, uint64_t descB, int scaleD) {
    asm volatile("{\n.reg .pred p;\nsetp.ne.b32 p, %98, 0;\n"
        "wgmma.mma_async.sync.aligned.m64n192k16.f32.bf16.bf16 {"
        "%0, %1, %2, %3, %4, %5, %6, %7, %8, %9, %10, %11, %12, %13, %14, %15, "
        "%16, %17, %18, %19, %20, %21, %22, %23, %24, %25, %26, %27, %28, %29, %30, %31, "
        "%32, %33, %34, %35, %36, %37, %38, %39, %40, %41, %42, %43, %44, %45, %46, %47, "
        "%48, %49, %50, %51, %52, %53, %54, %55, %56, %57, %58, %59, %60, %61, %62, %63, "
        "%64, %65, %66, %67, %68, %69, %70, %71, %72, %73, %74, %75, %76, %77, %78, %79, "
        "%80, %81, %82, %83, %84, %85, %86, %87, %88, %89, %90, %91, %92, %93, %94, %95}, "
        "%96, %97, p, 1, 1, 0, 1;\n}\n"
        : "+f"(d[0]), "+f"(d[1]), "+f"(d[2]), "+f"(d[3]), "+f"(d[4]), "+f"(d[5]), "+f"(d[6]), "+f"(d[7]),
          "+f"(d[8]), "+f"(d[9]), "+f"(d[10]), "+f"(d[11]), "+f"(d[12]), "+f"(d[13]), "+f"(d[14]), "+f"(d[15]),
          "+f"(d[16]), "+f"(d[17]), "+f"(d[18]), "+f"(d[19]), "+f"(d[20]), "+f"(d[21]), "+f"(d[22]), "+f"(d[23]),
          "+f"(d[24]), "+f"(d[25]), "+f"(d[26]), "+f"(d[27]), "+f"(d[28]), "+f"(d[29]), "+f"(d[30]), "+f"(d[31]),
          "+f"(d[32]), "+f"(d[33]), "+f"(d[34]), "+f"(d[35]), "+f"(d[36]), "+f"(d[37]), "+f"(d[38]), "+f"(d[39]),
          "+f"(d[40]), "+f"(d[41]), "+f"(d[42]), "+f"(d[43]), "+f"(d[44]), "+f"(d[45]), "+f"(d[46]), "+f"(d[47]),
          "+f"(d[48]), "+f"(d[49]), "+f"(d[50]), "+f"(d[51]), "+f"(d[52]), "+f"(d[53]), "+f"(d[54]), "+f"(d[55]),
          "+f"(d[56]), "+f"(d[57]), "+f"(d[58]), "+f"(d[59]), "+f"(d[60]), "+f"(d[61]), "+f"(d[62]), "+f"(d[63]),
          "+f"(d[64]), "+f"(d[65]), "+f"(d[66]), "+f"(d[67]), "+f"(d[68]), "+f"(d[69]), "+f"(d[70]), "+f"(d[71]),
          "+f"(d[72]), "+f"(d[73]), "+f"(d[74]), "+f"(d[75]), "+f"(d[76]), "+f"(d[77]), "+f"(d[78]), "+f"(d[79]),
          "+f"(d[80]), "+f"(d[81]), "+f"(d[82]), "+f"(d[83]), "+f"(d[84]), "+f"(d[85]), "+f"(d[86]), "+f"(d[87]),
          "+f"(d[88]), "+f"(d[89]), "+f"(d[90]), "+f"(d[91]), "+f"(d[92]), "+f"(d[93]), "+f"(d[94]), "+f"(d[95])
        : "l"(descA), "l"(descB), "r"(scaleD));
}

__device__ __forceinline__ void wgmma_n192_ss_tb_z(float (&d)[96], uint64_t descA, uint64_t descB) {
    asm volatile("{\n.reg .pred p;\nsetp.ne.b32 p, 0, 0;\n"
        "wgmma.mma_async.sync.aligned.m64n192k16.f32.bf16.bf16 {"
        "%0, %1, %2, %3, %4, %5, %6, %7, %8, %9, %10, %11, %12, %13, %14, %15, "
        "%16, %17, %18, %19, %20, %21, %22, %23, %24, %25, %26, %27, %28, %29, %30, %31, "
        "%32, %33, %34, %35, %36, %37, %38, %39, %40, %41, %42, %43, %44, %45, %46, %47, "
        "%48, %49, %50, %51, %52, %53, %54, %55, %56, %57, %58, %59, %60, %61, %62, %63, "
        "%64, %65, %66, %67, %68, %69, %70, %71, %72, %73, %74, %75, %76, %77, %78, %79, "
        "%80, %81, %82, %83, %84, %85, %86, %87, %88, %89, %90, %91, %92, %93, %94, %95}, "
        "%96, %97, p, 1, 1, 0, 1;\n}\n"
        : "=f"(d[0]), "=f"(d[1]), "=f"(d[2]), "=f"(d[3]), "=f"(d[4]), "=f"(d[5]), "=f"(d[6]), "=f"(d[7]),
          "=f"(d[8]), "=f"(d[9]), "=f"(d[10]), "=f"(d[11]), "=f"(d[12]), "=f"(d[13]), "=f"(d[14]), "=f"(d[15]),
          "=f"(d[16]), "=f"(d[17]), "=f"(d[18]), "=f"(d[19]), "=f"(d[20]), "=f"(d[21]), "=f"(d[22]), "=f"(d[23]),
          "=f"(d[24]), "=f"(d[25]), "=f"(d[26]), "=f"(d[27]), "=f"(d[28]), "=f"(d[29]), "=f"(d[30]), "=f"(d[31]),
          "=f"(d[32]), "=f"(d[33]), "=f"(d[34]), "=f"(d[35]), "=f"(d[36]), "=f"(d[37]), "=f"(d[38]), "=f"(d[39]),
          "=f"(d[40]), "=f"(d[41]), "=f"(d[42]), "=f"(d[43]), "=f"(d[44]), "=f"(d[45]), "=f"(d[46]), "=f"(d[47]),
          "=f"(d[48]), "=f"(d[49]), "=f"(d[50]), "=f"(d[51]), "=f"(d[52]), "=f"(d[53]), "=f"(d[54]), "=f"(d[55]),
          "=f"(d[56]), "=f"(d[57]), "=f"(d[58]), "=f"(d[59]), "=f"(d[60]), "=f"(d[61]), "=f"(d[62]), "=f"(d[63]),
          "=f"(d[64]), "=f"(d[65]), "=f"(d[66]), "=f"(d[67]), "=f"(d[68]), "=f"(d[69]), "=f"(d[70]), "=f"(d[71]),
          "=f"(d[72]), "=f"(d[73]), "=f"(d[74]), "=f"(d[75]), "=f"(d[76]), "=f"(d[77]), "=f"(d[78]), "=f"(d[79]),
          "=f"(d[80]), "=f"(d[81]), "=f"(d[82]), "=f"(d[83]), "=f"(d[84]), "=f"(d[85]), "=f"(d[86]), "=f"(d[87]),
          "=f"(d[88]), "=f"(d[89]), "=f"(d[90]), "=f"(d[91]), "=f"(d[92]), "=f"(d[93]), "=f"(d[94]), "=f"(d[95])
        : "l"(descA), "l"(descB));
}

__device__ __forceinline__ void wgmma_n160_ss_tb(float (&d)[80], uint64_t descA, uint64_t descB, int scaleD) {
    asm volatile("{\n.reg .pred p;\nsetp.ne.b32 p, %82, 0;\n"
        "wgmma.mma_async.sync.aligned.m64n160k16.f32.bf16.bf16 {"
        "%0, %1, %2, %3, %4, %5, %6, %7, %8, %9, %10, %11, %12, %13, %14, %15, "
        "%16, %17, %18, %19, %20, %21, %22, %23, %24, %25, %26, %27, %28, %29, %30, %31, "
        "%32, %33, %34, %35, %36, %37, %38, %39, %40, %41, %42, %43, %44, %45, %46, %47, "
        "%48, %49, %50, %51, %52, %53, %54, %55, %56, %57, %58, %59, %60, %61, %62, %63, "
        "%64, %65, %66, %67, %68, %69, %70, %71, %72, %73, %74, %75, %76, %77, %78, %79}, "
        "%80, %81, p, 1, 1, 0, 1;\n}\n"
        : "+f"(d[0]), "+f"(d[1]), "+f"(d[2]), "+f"(d[3]), "+f"(d[4]), "+f"(d[5]), "+f"(d[6]), "+f"(d[7]),
          "+f"(d[8]), "+f"(d[9]), "+f"(d[10]), "+f"(d[11]), "+f"(d[12]), "+f"(d[13]), "+f"(d[14]), "+f"(d[15]),
          "+f"(d[16]), "+f"(d[17]), "+f"(d[18]), "+f"(d[19]), "+f"(d[20]), "+f"(d[21]), "+f"(d[22]), "+f"(d[23]),
          "+f"(d[24]), "+f"(d[25]), "+f"(d[26]), "+f"(d[27]), "+f"(d[28]), "+f"(d[29]), "+f"(d[30]), "+f"(d[31]),
          "+f"(d[32]), "+f"(d[33]), "+f"(d[34]), "+f"(d[35]), "+f"(d[36]), "+f"(d[37]), "+f"(d[38]), "+f"(d[39]),
          "+f"(d[40]), "+f"(d[41]), "+f"(d[42]), "+f"(d[43]), "+f"(d[44]), "+f"(d[45]), "+f"(d[46]), "+f"(d[47]),
          "+f"(d[48]), "+f"(d[49]), "+f"(d[50]), "+f"(d[51]), "+f"(d[52]), "+f"(d[53]), "+f"(d[54]), "+f"(d[55]),
          "+f"(d[56]), "+f"(d[57]), "+f"(d[58]), "+f"(d[59]), "+f"(d[60]), "+f"(d[61]), "+f"(d[62]), "+f"(d[63]),
          "+f"(d[64]), "+f"(d[65]), "+f"(d[66]), "+f"(d[67]), "+f"(d[68]), "+f"(d[69]), "+f"(d[70]), "+f"(d[71]),
          "+f"(d[72]), "+f"(d[73]), "+f"(d[74]), "+f"(d[75]), "+f"(d[76]), "+f"(d[77]), "+f"(d[78]), "+f"(d[79])
        : "l"(descA), "l"(descB), "r"(scaleD));
}

__device__ __forceinline__ void wgmma_n64_ss(float (&d)[32], uint64_t descA, uint64_t descB, int scaleD) {
    asm volatile("{\n.reg .pred p;\nsetp.ne.b32 p, %34, 0;\n"
        "wgmma.mma_async.sync.aligned.m64n64k16.f32.bf16.bf16 {"
        "%0, %1, %2, %3, %4, %5, %6, %7, %8, %9, %10, %11, %12, %13, %14, %15, "
        "%16, %17, %18, %19, %20, %21, %22, %23, %24, %25, %26, %27, %28, %29, %30, %31}, "
        "%32, %33, p, 1, 1, 0, 0;\n}\n"
        : "+f"(d[0]), "+f"(d[1]), "+f"(d[2]), "+f"(d[3]), "+f"(d[4]), "+f"(d[5]), "+f"(d[6]), "+f"(d[7]),
          "+f"(d[8]), "+f"(d[9]), "+f"(d[10]), "+f"(d[11]), "+f"(d[12]), "+f"(d[13]), "+f"(d[14]), "+f"(d[15]),
          "+f"(d[16]), "+f"(d[17]), "+f"(d[18]), "+f"(d[19]), "+f"(d[20]), "+f"(d[21]), "+f"(d[22]), "+f"(d[23]),
          "+f"(d[24]), "+f"(d[25]), "+f"(d[26]), "+f"(d[27]), "+f"(d[28]), "+f"(d[29]), "+f"(d[30]), "+f"(d[31])
        : "l"(descA), "l"(descB), "r"(scaleD));
}

__device__ __forceinline__ void wgmma_n64_ss_z(float (&d)[32], uint64_t descA, uint64_t descB) {
    asm volatile("{\n.reg .pred p;\nsetp.ne.b32 p, 0, 0;\n"
        "wgmma.mma_async.sync.aligned.m64n64k16.f32.bf16.bf16 {"
        "%0, %1, %2, %3, %4, %5, %6, %7, %8, %9, %10, %11, %12, %13, %14, %15, "
        "%16, %17, %18, %19, %20, %21, %22, %23, %24, %25, %26, %27, %28, %29, %30, %31}, "
        "%32, %33, p, 1, 1, 0, 0;\n}\n"
        : "=f"(d[0]), "=f"(d[1]), "=f"(d[2]), "=f"(d[3]), "=f"(d[4]), "=f"(d[5]), "=f"(d[6]), "=f"(d[7]),
          "=f"(d[8]), "=f"(d[9]), "=f"(d[10]), "=f"(d[11]), "=f"(d[12]), "=f"(d[13]), "=f"(d[14]), "=f"(d[15]),
          "=f"(d[16]), "=f"(d[17]), "=f"(d[18]), "=f"(d[19]), "=f"(d[20]), "=f"(d[21]), "=f"(d[22]), "=f"(d[23]),
          "=f"(d[24]), "=f"(d[25]), "=f"(d[26]), "=f"(d[27]), "=f"(d[28]), "=f"(d[29]), "=f"(d[30]), "=f"(d[31])
        : "l"(descA), "l"(descB));
}

__device__ __forceinline__ void wgmma_n24_rs_tb(float (&d)[12], uint32_t a0, uint32_t a1, uint32_t a2, uint32_t a3, uint64_t descB, int scaleD) {
    asm volatile("{\n.reg .pred p;\nsetp.ne.b32 p, %17, 0;\n"
        "wgmma.mma_async.sync.aligned.m64n24k16.f32.bf16.bf16 {"
        "%0, %1, %2, %3, %4, %5, %6, %7, %8, %9, %10, %11}, "
        "{%12, %13, %14, %15}, %16, p, 1, 1, 1;\n}\n"
        : "+f"(d[0]), "+f"(d[1]), "+f"(d[2]), "+f"(d[3]), "+f"(d[4]), "+f"(d[5]), "+f"(d[6]), "+f"(d[7]),
          "+f"(d[8]), "+f"(d[9]), "+f"(d[10]), "+f"(d[11])
        : "r"(a0), "r"(a1), "r"(a2), "r"(a3), "l"(descB), "r"(scaleD));
}

__device__ __forceinline__ void cnt_signal(int idx) {
    asm volatile("fence.acq_rel.gpu;\nred.relaxed.gpu.global.add.u32 [%0], 1;"
                 ::"l"(g_cnt + idx * 32) : "memory");
}
__device__ __forceinline__ void cnt_wait(int idx, uint32_t target) {
    const uint32_t* p = g_cnt + idx * 32;
#pragma unroll 1
    for (uint32_t i = 0; i < (1u << 22); i++) {
        uint32_t v;
        asm volatile("ld.acquire.gpu.global.u32 %0, [%1];" : "=r"(v) : "l"(p) : "memory");
        if ((int32_t)(v - target) >= 0) break;
    }
    asm volatile("fence.proxy.async.global;" ::: "memory");
}
__device__ __forceinline__ void cluster_arrive() { asm volatile("barrier.cluster.arrive.release.aligned;" ::: "memory"); }
__device__ __forceinline__ void cluster_arrive_relaxed() { asm volatile("barrier.cluster.arrive.relaxed.aligned;" ::: "memory"); }
__device__ __forceinline__ void cluster_wait() { asm volatile("barrier.cluster.wait.acquire.aligned;" ::: "memory"); }
__device__ __forceinline__ void bulk_wait_read() { asm volatile("cp.async.bulk.wait_group.read 0;" ::: "memory"); }

__device__ __forceinline__ float gelu_tanh(float x) {
    const float u = x * (0.7978845608028654f + 0.035677408136300125f * x * x);
    float t;
    asm("tanh.approx.f32 %0, %1;" : "=f"(t) : "f"(u));
    const float h = 0.5f * x;
    return fmaf(h, t, h);
}
__device__ __forceinline__ void release_stage(uint32_t bar, uint32_t peer, int lane) {
    if (lane == 0) { mbar_arrive(bar); mbar_arrive_cluster(bar, peer); }
}

constexpr int SM_RING = 163840;
constexpr int SM_Q = 2 * IMG_BYTES, SM_ZERO = SM_Q + 24576;
constexpr int G2_STAGE = 8192 + 20480;
constexpr int SM_MISC = 229376;
constexpr int SM_BIAS = SM_MISC, SM_RED = SM_BIAS + 384, SM_BAR = SM_RED + 128;
constexpr int B_A = 0, B_F1 = 10, B_E1 = 14, B_F2 = 18, B_E2 = 23, B_KV = 28, B_Q = 45, B_F3 = 47, B_E3 = 55, B_ST = 63, B_STAT = 65, B_AUX = 66, B_COUNT = 67;
constexpr int SM_CS = SM_BAR + 544;
constexpr int SM_TOTAL = SM_CS + 1728;
static_assert(SM_TOTAL <= 232448, "shared memory budget");

struct Maps { CUtensorMap x, wqkv, w1, h, o, wo, w2; };

__device__ __forceinline__ uint32_t bf2_fma(uint32_t a, uint32_t b, uint32_t c) {
    uint32_t r;
    asm("fma.rn.bf16x2 %0, %1, %2, %3;" : "=r"(r) : "r"(a), "r"(b), "r"(c));
    return r;
}
__device__ __forceinline__ uint32_t lop_and_or(uint32_t a, uint32_t m, uint32_t o) {
    uint32_t r;
    asm("lop3.b32 %0, %1, %2, %3, 0xEA;" : "=r"(r) : "r"(a), "r"(m), "r"(o));
    return r;
}
struct ExpConst { uint32_t mask, slope; };
__device__ __forceinline__ ExpConst make_exp_const() {
    ExpConst k;
    asm volatile("mov.b32 %0, 0x007F007F;" : "=r"(k.mask));
    asm volatile("mov.b32 %0, 0x3EF83EF8;" : "=r"(k.slope));
    return k;
}
__device__ __forceinline__ uint32_t exp2_pair_fma(float t0, float t1, const ExpConst& k) {
    const uint32_t L = __byte_perm(__float_as_uint(t0), __float_as_uint(t1), 0x6521);
    const uint32_t g = lop_and_or(L, k.mask, 0x3F803F80u);
    const uint32_t u = bf2_fma(g, k.slope, 0xBF37BF37u);
    const uint32_t e = bf2_fma(u, u, 0xBD71BD71u);
    return bf2_fma(L, e, L);
}
template <int SHIFT>
__device__ __forceinline__ void exp_tile(const float (&s)[32], uint32_t (&p)[16], const ExpConst& k) {
#pragma unroll
    for (int b = 0; b < 8; b++) {
        if ((EMU_MASK >> (b + SHIFT)) & 1) {
            p[2 * b] = exp2_pair_fma(s[4 * b], s[4 * b + 1], k);
            p[2 * b + 1] = exp2_pair_fma(s[4 * b + 2], s[4 * b + 3], k);
        } else {
            p[2 * b] = pack_bf16(ex2(s[4 * b]), ex2(s[4 * b + 1]));
            p[2 * b + 1] = pack_bf16(ex2(s[4 * b + 2]), ex2(s[4 * b + 3]));
        }
    }
}

__device__ __forceinline__ void qk_tile(float (&s)[32], uint64_t dQ, uint64_t dQ2, uint64_t dK) {
    wg_fence();
    wgmma_n64_ss_z(s, dQ, dK);
    wgmma_n64_ss(s, dQ2, dK + 16, 1);
    wg_commit();
}
__device__ __forceinline__ void pv_tile(float (&o)[12], const uint32_t (&p)[16], uint64_t dV) {
    wg_fence();
#pragma unroll
    for (int ks = 0; ks < 4; ks++)
        wgmma_n24_rs_tb(o, p[4 * ks], p[4 * ks + 1], p[4 * ks + 2], p[4 * ks + 3], dV + ks * 48, 1);
    wg_commit();
}
__device__ __forceinline__ void store_o(const float (&o)[12], int h, int rbase, int lane) {
    const int g = lane >> 2, c = lane & 3;
    const bool odd = h & 1;
    const int lsrc = (lane & ~3) | (odd ? 0 : 2);
    const float i0 = 1.f / __shfl_sync(~0u, o[8], lsrc), i1 = 1.f / __shfl_sync(~0u, o[10], lsrc);
    __nv_bfloat16* dst = g_o + (size_t)(rbase + g) * DM + h * 20;
    const int d0 = (odd ? 4 : 0) + 2 * c, d1 = d0 + 8, d2 = odd ? 2 * c - 4 : 16 + 2 * c;
    *(uint32_t*)(dst + d0) = pack_bf16(o[0] * i0, o[1] * i0);
    *(uint32_t*)(dst + d1) = pack_bf16(o[4] * i0, o[5] * i0);
    *(uint32_t*)(dst + 8 * DM + d0) = pack_bf16(o[2] * i1, o[3] * i1);
    *(uint32_t*)(dst + 8 * DM + d1) = pack_bf16(o[6] * i1, o[7] * i1);
    if (odd ? (c >= 2) : (c < 2)) {
        *(uint32_t*)(dst + d2) = pack_bf16(o[8] * i0, o[9] * i0);
        *(uint32_t*)(dst + 8 * DM + d2) = pack_bf16(o[10] * i1, o[11] * i1);
    }
}

__device__ __forceinline__ void attn_rows_maxshift(uint32_t sK, uint32_t barKV, uint64_t dQ, uint64_t dQ2, int h, int rbase) {
    const int lane = threadIdx.x & 31;
    const uint64_t dK0 = make_desc(sK, 128, 384, 0), dV0 = make_desc(sK + IMG_BYTES, 384, 128, 0);
    float o[12], s[32];
    uint32_t p[16];
#pragma unroll
    for (int i = 0; i < 12; i++) o[i] = 0.f;
    float m0 = -3.0e38f, m1 = -3.0e38f;
    mbar_wait(barKV + 128, 0);
#pragma unroll 1
    for (int t = 0; t < 32; t++) {
        mbar_wait(barKV + (t >> 1) * 8, 0);
        qk_tile(s, dQ, dQ2, dK0 + t * 192);
        wg_wait<0>();
        fence_regs(s);
        const uint32_t mask = EMU_MASK >> ((t & 1) * 8);
        float n0 = m0, n1 = m1;
#pragma unroll
        for (int b = 0; b < 8; b++) {
            const bool emu = (mask >> b) & 1;
            const float f = emu ? 0.5f : 1.f, off = emu ? -383.00390625f : 0.f;
#pragma unroll
            for (int i = 0; i < 4; i++) s[4 * b + i] = fmaf(s[4 * b + i], f, off);
            n0 = fmaxf(n0, fmaxf(s[4 * b], s[4 * b + 1]));
            n1 = fmaxf(n1, fmaxf(s[4 * b + 2], s[4 * b + 3]));
        }
        n0 = fmaxf(n0, __shfl_xor_sync(~0u, n0, 1)); n0 = fmaxf(n0, __shfl_xor_sync(~0u, n0, 2));
        n1 = fmaxf(n1, __shfl_xor_sync(~0u, n1, 1)); n1 = fmaxf(n1, __shfl_xor_sync(~0u, n1, 2));
        const float c0 = ex2(m0 - n0), c1 = ex2(m1 - n1);
        m0 = n0; m1 = n1;
#pragma unroll
        for (int b = 0; b < 3; b++) { o[4 * b] *= c0; o[4 * b + 1] *= c0; o[4 * b + 2] *= c1; o[4 * b + 3] *= c1; }
#pragma unroll
        for (int b = 0; b < 8; b++) {
            p[2 * b] = pack_bf16(ex2(s[4 * b] - m0), ex2(s[4 * b + 1] - m0));
            p[2 * b + 1] = pack_bf16(ex2(s[4 * b + 2] - m1), ex2(s[4 * b + 3] - m1));
        }
        pv_tile(o, p, dV0 + t * 192);
        wg_wait<0>();
        fence_regs(o);
    }
    store_o(o, h, rbase, lane);
}

__global__ void __launch_bounds__(512, 1) __cluster_dims__(2, 1, 1)
k_fused(const __grid_constant__ Maps tm, const __nv_bfloat16* __restrict__ x, const uint8_t* __restrict__ wqkv,
        const uint8_t* __restrict__ w1, const uint8_t* __restrict__ w2, const uint8_t* __restrict__ wo,
        const __nv_bfloat16* __restrict__ b1, const __nv_bfloat16* __restrict__ b2, __nv_bfloat16* __restrict__ out) {
    extern __shared__ __align__(1024) uint8_t smem[];
    const uint32_t sb = smem_u32(smem);
    const uint32_t bar = sb + SM_BAR;
    const int warp = __shfl_sync(~0u, threadIdx.x >> 5, 0), lane = threadIdx.x & 31;
    const int wgi = warp >> 2, w4 = warp & 3, g = lane >> 2, c = lane & 3;
    const uint32_t rank = blockIdx.x & 1, peer = rank ^ 1;
    const int cl = blockIdx.x >> 1;
    const int cg = cl & 7, rb = (cl >> 3) * 2 + rank;
    const uint32_t epoch = *(volatile uint32_t*)&g_epoch;

    if (threadIdx.x == 0) TL(0, 0);
    if (threadIdx.x < B_COUNT) {
        const int i = threadIdx.x;
        const int cnt = (i >= B_E1 && i < B_F2) || (i >= B_E2 && i < B_KV) ? 16
                      : (i >= B_E3 && i <= B_ST) || i == B_STAT ? 8 : i == B_ST + 1 ? 2 : i == B_AUX ? 7 : 1;
        mbar_init(bar + i * 8, cnt);
        fence_barrier_init();
    }
    __syncthreads();
    cluster_arrive_relaxed();
    cluster_wait();
    if (threadIdx.x == 0) TL(0, 3);

    {
        const uint32_t sB = sb + SM_RING;
        if (threadIdx.x == 0) TL(1, 0);
        if (wgi < 2) {
            reg_dealloc<40>();
            if (warp == 0) {
                if (elect_one()) { prefetch_map(&tm.x); prefetch_map(&tm.wqkv); prefetch_map(&tm.w1); prefetch_map(&tm.h); }
                __syncwarp();
#pragma unroll 1
                for (int it = 0; it < 20; it++) {
                    const int s = it & 3;
                    if (it >= 4) mbar_wait(bar + (B_E1 + s) * 8, ((it >> 2) - 1) & 1);
                    if (elect_one()) {
                        const uint32_t dst = sB + s * 16384 + rank * 8192, fb = bar + (B_F1 + s) * 8;
                        const int c0 = cg * 240 + rank * 120;
                        mbar_expect_tx(fb, 16384);
                        tma_load_mc(dst, &tm.wqkv, c0, it * 32, fb, 3);
                        tma_load_mc(dst + 4096, &tm.wqkv, c0 + 64, it * 32, fb, 3);
                    }
                    __syncwarp();
                    const int kb = it < 3 ? it : (it & 1) ? 10 : (it >> 1) + 1;
                    if (kb < 10 && elect_one()) {
                        mbar_expect_tx(bar + (B_A + kb) * 8, 16384);
                        tma_load(sb + kb * 16384, &tm.x, kb * 64, rb * 128, bar + (B_A + kb) * 8);
                    }
                    __syncwarp();
                }
#pragma unroll 1
                for (int it = 0; it < 20; it++) {
                    const int s = it % 5;
                    if (it < 5) { if (it != 3) mbar_wait(bar + (B_E1 + (it == 4 ? 3 : it)) * 8, 0); }
                    else mbar_wait(bar + (B_E2 + s) * 8, ((it / 5) - 1) & 1);
                    if (elect_one()) {
                        const uint32_t dst = sB + s * 12288, fb = bar + (B_F2 + s) * 8;
                        mbar_expect_tx(fb, 12288);
                        if ((it & 1) == (int)rank) {
                            tma_load_mc(dst, &tm.w1, cg * 192, it * 32, fb, 3);
                            tma_load_mc(dst + 4096, &tm.w1, cg * 192 + 64, it * 32, fb, 3);
                        } else {
                            tma_load_mc(dst + 8192, &tm.w1, cg * 192 + 128, it * 32, fb, 3);
                        }
                    }
                    __syncwarp();
                }
            } else {
                const int ht = threadIdx.x - 32;
                if (ht < 216) {
                    const uint32_t* src = ht < 120 ? reinterpret_cast<const uint32_t*>(wqkv) + rb * 40 * 960 + cg * 120 + ht
                                                   : reinterpret_cast<const uint32_t*>(w1) + rb * 40 * 768 + cg * 96 + (ht - 120);
                    const int pitch = ht < 120 ? 960 : 768;
                    float s0 = 0.f, s1 = 0.f;
#pragma unroll
                    for (int h2 = 0; h2 < 2; h2++) {
                        uint32_t v[20];
#pragma unroll
                        for (int k = 0; k < 20; k++) v[k] = __ldg(src + (h2 * 20 + k) * pitch);
#pragma unroll
                        for (int k = 0; k < 20; k++) { s0 += bf_lo(v[k]); s1 += bf_hi(v[k]); }
                    }
                    g_csp[rb * 1728 + cg * 216 + ht] = make_float2(s0, s1);
                }
                if (ht < 96) reinterpret_cast<uint32_t*>(smem + SM_BIAS)[ht] = __ldg(reinterpret_cast<const uint32_t*>(b1 + cg * 192) + ht);
                asm volatile("bar.sync 8, 224;" ::: "memory");
                if (warp == 2) { if (elect_one()) cnt_signal(CNT_CS + cg); __syncwarp(); }
                if (warp == 1) {
                    mbar_wait(bar + B_STAT * 8, 0);
                    if (elect_one()) cnt_signal(CNT_ST + rb);
                    __syncwarp();
                }
                if (warp == 3 && elect_one()) {
                    prefetch_l2(w2 + blockIdx.x * 15360, 15360);
                    prefetch_l2(wo + blockIdx.x * 6400, 6400);
                }
                if (lane == 0) { cnt_wait(CNT_CS + cg, (epoch + 1) * 16); cnt_wait(CNT_ST + rb, (epoch + 1) * 8); }
                __syncwarp();
                if (ht < 216) {
                    float s0 = 0.f, s1 = 0.f;
#pragma unroll
                    for (int r = 0; r < 16; r++) {
                        const float2 v = __ldcg(g_csp + r * 1728 + cg * 216 + ht);
                        s0 += v.x; s1 += v.y;
                    }
                    reinterpret_cast<float2*>(smem + SM_CS)[ht] = make_float2(s0, s1);
                }
                __syncwarp();
                if (lane == 0) mbar_arrive(bar + B_AUX * 8);
                if (warp == 4) {
                    mbar_wait(bar + B_ST * 8, 0);
                    if (elect_one()) cnt_signal(CNT_QKV + cg);
                    __syncwarp();
                    mbar_wait(bar + (B_ST + 1) * 8, 0);
                    if (elect_one()) cnt_signal(CNT_H + rb);
                    __syncwarp();
                }
            }
            asm volatile("bar.sync %0, 128;" ::"r"(wgi + 3) : "memory");
            reg_alloc<128>();
        } else {
            reg_alloc<216>();
            const int wi = wgi - 2;
            const int row0 = rb * 128 + wi * 64 + w4 * 16 + g;
            const uint32_t sAw = sb + wi * 8192;
            const int rbk = row0 >> 3, hs0 = cg * 12;
            {
                const int srow = rb * 128 + cg * 16 + (warp - 8) * 2 + (lane >> 4);
                const uint4* src = reinterpret_cast<const uint4*>(x + (size_t)srow * DM) + (lane & 15);
                uint4 v[5];
#pragma unroll
                for (int i = 0; i < 5; i++) v[i] = __ldg(src + 16 * i);
                float f[40];
#pragma unroll
                for (int i = 0; i < 5; i++) {
                    f[8 * i] = bf_lo(v[i].x); f[8 * i + 1] = bf_hi(v[i].x); f[8 * i + 2] = bf_lo(v[i].y); f[8 * i + 3] = bf_hi(v[i].y);
                    f[8 * i + 4] = bf_lo(v[i].z); f[8 * i + 5] = bf_hi(v[i].z); f[8 * i + 6] = bf_lo(v[i].w); f[8 * i + 7] = bf_hi(v[i].w);
                }
                float sm = 0.f;
#pragma unroll
                for (int i = 0; i < 40; i++) sm += f[i];
#pragma unroll
                for (int o = 8; o; o >>= 1) sm += __shfl_xor_sync(~0u, sm, o);
                const float mu = sm * (1.f / DM);
                float q = 0.f;
#pragma unroll
                for (int i = 0; i < 40; i++) { const float d = f[i] - mu; q = fmaf(d, d, q); }
#pragma unroll
                for (int o = 8; o; o >>= 1) q += __shfl_xor_sync(~0u, q, o);
                const float var = q * (1.f / DM);
                const float r1 = 1.f / sqrtf(var + LN_EPS);
                const float r2 = 1.f / sqrtf(var * r1 * r1 + LN_EPS);
                if ((lane & 15) == 0) g_stat[srow] = make_float4(mu, r1, r1 * r2, 0.f);
                __syncwarp();
                if (lane == 0) mbar_arrive(bar + B_STAT * 8);
            }
            float acc1[2][60];
#pragma unroll 1
            for (int it = 0; it < 20; it++) {
                const int s = it & 3;
                if (!(it & 1)) mbar_wait(bar + (B_A + (it >> 1)) * 8, 0);
                if (threadIdx.x == 256) IT(0, it);
                mbar_wait(bar + (B_F1 + s) * 8, (it >> 2) & 1);
                if (threadIdx.x == 256) IT(1, it);
                wg_fence();
                const uint64_t dA = make_desc(sAw + (it >> 1) * 16384 + (it & 1) * 64, 16, 1024, 1);
                const uint64_t dB = make_desc(sB + s * 16384, 4096, 1024, 1);
                wgmma_n120_ss_tb(acc1[0], dA, dB, it > 0);
                wgmma_n120_ss_tb(acc1[1], dA, dB + 512, it > 0);
                wgmma_n120_ss_tb(acc1[0], dA + 2, dB + 128, 1);
                wgmma_n120_ss_tb(acc1[1], dA + 2, dB + 640, 1);
                wg_commit();
                if (it > 0) { wg_wait<1>(); release_stage(bar + (B_E1 + ((it - 1) & 3)) * 8, peer, lane); }
            }
            wg_wait<0>();
            release_stage(bar + (B_E1 + 3) * 8, peer, lane);
            fence_regs(acc1[0]);
            fence_regs(acc1[1]);
            if (threadIdx.x == 256) TL(1, 1);
            mbar_wait(bar + B_AUX * 8, 0);
            const float4 st0 = __ldcg(g_stat + row0), st1 = __ldcg(g_stat + row0 + 8);
            const float2* cs = reinterpret_cast<const float2*>(smem + SM_CS) + c;
            uint8_t* img = g_img + (size_t)hs0 * IMG_BYTES + rbk * 384 + g * 16 + c * 4;
            const bool emu0 = (EMU_MASK >> (rbk & 15)) & 1, emu1 = (EMU_MASK >> ((rbk + 1) & 15)) & 1;
            const bool low = c < 2;
            uint32_t pk[60];
#pragma unroll
            for (int m = 0; m < 6; m++) {
                const int which = (hs0 + 2 * m) >> 5;
                const float m0 = st0.y * (which == 0 ? QSCALE : (which == 1 && emu0) ? 2.f : 1.f);
                const float m1 = st1.y * (which == 0 ? QSCALE : (which == 1 && emu1) ? 2.f : 1.f);
                const float d0 = -st0.x * m0, d1 = -st1.x * m1;
                const float* a = &acc1[m / 3][20 * (m % 3)];
#pragma unroll
                for (int b = 0; b < 5; b++) {
                    const float2 cv = cs[(5 * m + b) * 4];
                    pk[10 * m + 2 * b] = pack_bf16(fmaf(a[4 * b], m0, d0 * cv.x), fmaf(a[4 * b + 1], m0, d0 * cv.y));
                    pk[10 * m + 2 * b + 1] = pack_bf16(fmaf(a[4 * b + 2], m1, d1 * cv.x), fmaf(a[4 * b + 3], m1, d1 * cv.y));
                }
            }
            const float r20 = st0.z, r21 = st1.z, e20 = -st0.x * st0.z, e21 = -st1.x * st1.z;
            float acc2[96];
#pragma unroll
            for (int it = 0; it < 20; it++) {
                const int s = it % 5;
                if (threadIdx.x == 256) IT(0, 20 + it);
                mbar_wait(bar + (B_F2 + s) * 8, (it / 5) & 1);
                if (threadIdx.x == 256) IT(1, 20 + it);
                wg_fence();
                const uint64_t dA = make_desc(sAw + (it >> 1) * 16384 + (it & 1) * 64, 16, 1024, 1);
                const uint64_t dB = make_desc(sB + s * 12288, 4096, 1024, 1);
                if (it == 0) wgmma_n192_ss_tb_z(acc2, dA, dB); else wgmma_n192_ss_tb(acc2, dA, dB, 1);
                wgmma_n192_ss_tb(acc2, dA + 2, dB + 128, 1);
                wg_commit();
                if (it > 0) {
                    wg_wait<1>();
                    if (it <= 15) release_stage(bar + (B_E2 + (it - 1) % 5) * 8, peer, lane);
                }
                if (it < 12) {
                    const int m = it / 2, part = it % 2;
                    const int hs = hs0 + 2 * m, which = hs >> 5;
                    const uint32_t* a = pk + 10 * m;
                    uint8_t* pe = img + (2 * m) * IMG_BYTES;
                    uint8_t* po = pe + IMG_BYTES;
                    if (part == 0) {
                        const uint32_t padv = which == 0 ? 0x3F803F80u : which == 1 ? 0xBFFF4440u : 0x00003F80u;
                        const uint32_t p0 = ((c & 1) || (which == 1 && !emu0)) ? 0u : padv;
                        const uint32_t p1 = ((c & 1) || (which == 1 && !emu1)) ? 0u : padv;
                        *(uint32_t*)(pe) = a[0];
                        *(uint32_t*)(pe + 128) = a[2];
                        *(uint32_t*)(pe + 256) = low ? a[4] : p0;
                        *(uint32_t*)(pe + 384) = a[1];
                        *(uint32_t*)(pe + 512) = a[3];
                        *(uint32_t*)(pe + 640) = low ? a[5] : p1;
                        *(uint32_t*)(po + 256) = low ? p0 : a[4];
                        *(uint32_t*)(po + 640) = low ? p1 : a[5];
                    } else {
                        *(uint32_t*)(po) = a[6];
                        *(uint32_t*)(po + 128) = a[8];
                        *(uint32_t*)(po + 384) = a[7];
                        *(uint32_t*)(po + 512) = a[9];
                        if (which < 2) {
                            const uint32_t u0 = bf2_fma(a[4], a[4], 0u), u1 = bf2_fma(a[5], a[5], 0u);
                            const uint32_t pe0 = bf2_fma(a[0], a[0], bf2_fma(a[2], a[2], low ? u0 : 0u));
                            const uint32_t pe1 = bf2_fma(a[1], a[1], bf2_fma(a[3], a[3], low ? u1 : 0u));
                            const uint32_t po0 = bf2_fma(a[6], a[6], bf2_fma(a[8], a[8], low ? 0u : u0));
                            const uint32_t po1 = bf2_fma(a[7], a[7], bf2_fma(a[9], a[9], low ? 0u : u1));
                            const float e0 = bf_lo(pe0) + bf_hi(pe0), e1 = bf_lo(pe1) + bf_hi(pe1);
                            const float o0 = bf_lo(po0) + bf_hi(po0), o1 = bf_lo(po1) + bf_hi(po1);
                            const bool b0 = c & 1, b1_ = c & 2;
                            const float x0 = (b0 ? e1 : e0) + __shfl_xor_sync(~0u, b0 ? e0 : e1, 1);
                            const float x1 = (b0 ? o1 : o0) + __shfl_xor_sync(~0u, b0 ? o0 : o1, 1);
                            float y = (b1_ ? x1 : x0) + __shfl_xor_sync(~0u, b1_ ? x0 : x1, 2);
                            if (which == 1 && (b0 ? emu1 : emu0)) y *= 0.25f;
                            g_nrm[(hs + (c >> 1)) * SEQ + row0 + (c & 1) * 8] = y;
                        }
                    }
                    if (it == 11) { __syncwarp(); if (lane == 0) mbar_arrive(bar + B_ST * 8); }
                }
            }
            wg_wait<0>();
            fence_regs(acc2);
            if (threadIdx.x == 256) TL(1, 2);
            const uint32_t* bias = reinterpret_cast<const uint32_t*>(smem + SM_BIAS) + c;
            const int mrow = w4 * 16 + (lane & 15);
            const uint32_t st_row = sAw + mrow * 128;
#pragma unroll
            for (int j = 0; j < 24; j += 2) {
                const uint32_t bA = bias[j * 4], bB = bias[j * 4 + 4];
                const float2 cA = cs[(30 + j) * 4], cB = cs[(31 + j) * 4];
                const float* a = acc2 + j * 4;
                const uint32_t r00 = pack_bf16(gelu_tanh(fmaf(a[0], r20, fmaf(e20, cA.x, bf_lo(bA)))), gelu_tanh(fmaf(a[1], r20, fmaf(e20, cA.y, bf_hi(bA)))));
                const uint32_t r10 = pack_bf16(gelu_tanh(fmaf(a[2], r21, fmaf(e21, cA.x, bf_lo(bA)))), gelu_tanh(fmaf(a[3], r21, fmaf(e21, cA.y, bf_hi(bA)))));
                const uint32_t r01 = pack_bf16(gelu_tanh(fmaf(a[4], r20, fmaf(e20, cB.x, bf_lo(bB)))), gelu_tanh(fmaf(a[5], r20, fmaf(e20, cB.y, bf_hi(bB)))));
                const uint32_t r11 = pack_bf16(gelu_tanh(fmaf(a[6], r21, fmaf(e21, cB.x, bf_lo(bB)))), gelu_tanh(fmaf(a[7], r21, fmaf(e21, cB.y, bf_hi(bB)))));
                const int chunk = (j & 7) + (lane >> 4);
                stmatrix_x4(st_row + (j >> 3) * 16384 + ((chunk ^ (mrow & 7)) << 4), r00, r10, r01, r11);
            }
            fence_proxy_async();
            asm volatile("bar.sync %0, 128;" ::"r"(wgi + 3) : "memory");
            if (w4 == 0 && elect_one()) {
#pragma unroll
                for (int b = 0; b < 3; b++) tma_store(&tm.h, sAw + b * 16384, cg * 192 + b * 64, rb * 128 + wi * 64);
                bulk_commit();
                bulk_wait_all();
                mbar_arrive(bar + (B_ST + 1) * 8);
            }
            __syncwarp();
            reg_dealloc<128>();
        }
        __syncthreads();
        if (threadIdx.x == 0) TL(1, 3);
    }

    {
        const int h = blockIdx.x >> 2, qb = blockIdx.x & 3;
        const uint32_t sK = sb, sV = sb + IMG_BYTES, barKV = bar + B_KV * 8;
        if (threadIdx.x == 0) TL(2, 0);
        if (threadIdx.x < 192) *reinterpret_cast<uint4*>(smem + SM_ZERO + threadIdx.x * 16) = make_uint4(0, 0, 0, 0);
        fence_proxy_async();
        if (warp == 0) {
            if (elect_one()) {
                cnt_wait(CNT_QKV + h / 12, (epoch + 1) * 16);
                cnt_wait(CNT_QKV + (32 + h) / 12, (epoch + 1) * 16);
                cnt_wait(CNT_QKV + (64 + h) / 12, (epoch + 1) * 16);
                const uint8_t* gK = g_img + (size_t)(32 + h) * IMG_BYTES;
                const uint8_t* gV = g_img + (size_t)(64 + h) * IMG_BYTES;
                const uint8_t* gQ = g_img + (size_t)h * IMG_BYTES + qb * 64 * 384;
                mbar_expect_tx(barKV + 128, 6144);
                bulk_load(sK, gK, 6144, barKV + 128);
                for (int p = 0; p < 2; p++) {
                    mbar_expect_tx(bar + (B_Q + p) * 8, 12288);
                    bulk_load(sb + SM_Q + p * 12288, gQ + p * 12288, 12288, bar + (B_Q + p) * 8);
                }
                for (int i = 0; i < 16; i++) {
                    mbar_expect_tx(barKV + i * 8, i < 15 ? 12288 : 6144);
                    bulk_load(sV + i * 6144, gV + i * 6144, 6144, barKV + i * 8);
                    if (i < 15) bulk_load(sK + (i + 1) * 6144, gK + (i + 1) * 6144, 6144, barKV + i * 8);
                }
            }
            __syncwarp();
        }
        __syncthreads();
        if (threadIdx.x == 0) TL(2, 1);
        float* red = reinterpret_cast<float*>(smem + SM_RED);
        float kmax = 0.f, qmax = __ldcg(g_nrm + h * SEQ + qb * 512 + threadIdx.x);
#pragma unroll
        for (int i = 0; i < 4; i++) kmax = fmaxf(kmax, __ldcg(g_nrm + (32 + h) * SEQ + i * 512 + threadIdx.x));
#pragma unroll
        for (int o = 16; o; o >>= 1) {
            kmax = fmaxf(kmax, __shfl_xor_sync(~0u, kmax, o));
            qmax = fmaxf(qmax, __shfl_xor_sync(~0u, qmax, o));
        }
        if (lane == 0) { red[warp] = kmax; red[16 + warp] = qmax; }
        __syncthreads();
        kmax = red[lane & 15]; qmax = red[16 + (lane & 15)];
#pragma unroll
        for (int o = 8; o; o >>= 1) {
            kmax = fmaxf(kmax, __shfl_xor_sync(~0u, kmax, o));
            qmax = fmaxf(qmax, __shfl_xor_sync(~0u, qmax, o));
        }
        const bool safe = __all_sync(~0u, kmax * qmax * 1.1f <= SAFE_BOUND * SAFE_BOUND);
        const uint64_t dK0 = make_desc(sK, 128, 384, 0), dV0 = make_desc(sV, 384, 128, 0);
        if (!safe) {
#pragma unroll 1
            for (int pass = 0; pass < 2; pass++) {
                const uint32_t sQ = sb + SM_Q + pass * 12288 + wgi * 3072;
                mbar_wait(bar + (B_Q + pass) * 8, 0);
                if (lane < 16) *reinterpret_cast<uint32_t*>(smem + (sQ - sb) + (w4 * 2 + (lane >> 3)) * 384 + 256 + (lane & 7) * 16 + ((h & 1) ? 0 : 8)) = 0u;
                fence_proxy_async();
                asm volatile("bar.sync %0, 128;" ::"r"(wgi + 3) : "memory");
                attn_rows_maxshift(sK, barKV, make_desc(sQ, 128, 384, 0), make_desc(sQ + 256, sb + SM_ZERO - (sQ + 256), 384, 0), h,
                                   qb * 512 + pass * 256 + wgi * 64 + w4 * 16);
            }
        } else {
            const ExpConst kc = make_exp_const();
#pragma unroll 1
            for (int pass = 0; pass < 2; pass++) {
                const int rbase = qb * 512 + pass * 256 + wgi * 64 + w4 * 16;
                const uint32_t sQ = sb + SM_Q + pass * 12288 + wgi * 3072;
                const uint64_t dQ = make_desc(sQ, 128, 384, 0), dQ2 = make_desc(sQ + 256, sb + SM_ZERO - (sQ + 256), 384, 0);
                float o[12], sa[32], sc[32];
                uint32_t p[16];
#pragma unroll
                for (int i = 0; i < 12; i++) o[i] = 0.f;
                fence_regs(o);
                mbar_wait(bar + (B_Q + pass) * 8, 0);
                mbar_wait(barKV + 128, 0);
                qk_tile(sa, dQ, dQ2, dK0);
                wg_wait<0>();
                fence_regs(sa);
                uint64_t dK = dK0, dV = dV0;
                uint32_t bj = barKV;
#pragma unroll 1
                for (int j = 0; j < 16; j++) {
                    mbar_wait(bj, 0);
                    qk_tile(sc, dQ, dQ2, dK + 192);
                    wg_wait<1>();
                    exp_tile<0>(sa, p, kc);
                    pv_tile(o, p, dV);
                    wg_wait<1>();
                    fence_regs(sc);
                    mbar_wait(bj, 0);
                    qk_tile(sa, dQ, dQ2, dK + 384);
                    wg_wait<1>();
                    exp_tile<8>(sc, p, kc);
                    pv_tile(o, p, dV + 192);
                    wg_wait<1>();
                    fence_regs(sa);
                    dK += 384; dV += 384; bj += 8;
                }
                wg_wait<0>();
                fence_regs(o);
                store_o(o, h, rbase, lane);
                if (threadIdx.x == 0) TL(2, 2 + pass);
            }
        }
        __syncthreads();
        if (threadIdx.x == 64) cnt_signal(CNT_O + qb);
        cluster_arrive_relaxed();
    }

    {
        const int ct = cl & 3, rt = (cl >> 2) * 2 + rank;
        if (threadIdx.x == 0) TL(3, 0);
        const int orow = threadIdx.x >> 3, oseg = threadIdx.x & 7;
        const size_t ooff = (size_t)(rt * 64 + orow) * DM + ct * 160 + oseg * 20;
        uint2 xr[5], br[5];
#pragma unroll
        for (int i = 0; i < 5; i++) {
            xr[i] = __ldg(reinterpret_cast<const uint2*>(x + ooff) + i);
            br[i] = __ldg(reinterpret_cast<const uint2*>(b2 + ct * 160 + oseg * 20) + i);
        }
        cluster_wait();
        float* stg = reinterpret_cast<float*>(smem);
        if (warp == 4) {
            if (elect_one()) { prefetch_map(&tm.h); prefetch_map(&tm.o); prefetch_map(&tm.w2); prefetch_map(&tm.wo); cnt_wait(CNT_H + (rt >> 1), (epoch + 1) * 8); }
            __syncwarp();
#pragma unroll 1
            for (int kb = 0; kb < 34; kb++) {
                const int s = kb & 7;
                if (kb >= 8) mbar_wait(bar + (B_E3 + s) * 8, ((kb >> 3) - 1) & 1);
                if (elect_one()) {
                    if (kb == 24) { cnt_wait(CNT_O + (rt >> 3), (epoch + 1) * 32); TL(3, 1); }
                    const uint32_t dst = sb + s * G2_STAGE, fb = bar + (B_F3 + s) * 8;
                    const CUtensorMap* mA = kb < 24 ? &tm.h : &tm.o;
                    const CUtensorMap* mB = kb < 24 ? &tm.w2 : &tm.wo;
                    const int k0 = (kb < 24 ? kb : kb - 24) * 64;
                    mbar_expect_tx(fb, G2_STAGE);
                    tma_load(dst, mA, k0, rt * 64, fb);
                    const int first = ((kb & 1) == (int)rank) ? 0 : 3, last = ((kb & 1) == (int)rank) ? 3 : 5;
                    for (int b = first; b < last; b++) tma_load_mc(dst + 8192 + b * 4096, mB, ct * 160 + b * 32, k0, fb, 3);
                }
                __syncwarp();
            }
        } else if (wgi == 0) {
            float acc[80];
#pragma unroll 1
            for (int kb = 0; kb < 34; kb++) {
                const int s = kb & 7;
                mbar_wait(bar + (B_F3 + s) * 8, (kb >> 3) & 1);
                wg_fence();
                const uint64_t dA = make_desc(sb + s * G2_STAGE, 16, 1024, 1);
                const uint64_t dB = make_desc(sb + s * G2_STAGE + 8192, 4096, 512, 2);
#pragma unroll
                for (int kk = 0; kk < 4; kk++) wgmma_n160_ss_tb(acc, dA + kk * 2, dB + kk * 64, (kb | kk) != 0);
                wg_commit();
                if (kb > 0) {
                    wg_wait<1>();
                    if (kb <= 26) release_stage(bar + (B_E3 + ((kb - 1) & 7)) * 8, peer, lane);
                }
            }
            wg_wait<0>();
            fence_regs(acc);
            if (threadIdx.x == 0) TL(3, 2);
            const int r = w4 * 16 + g;
#pragma unroll
            for (int j = 0; j < 20; j++) {
                *reinterpret_cast<float2*>(stg + r * 168 + j * 8 + 2 * c) = make_float2(acc[4 * j], acc[4 * j + 1]);
                *reinterpret_cast<float2*>(stg + (r + 8) * 168 + j * 8 + 2 * c) = make_float2(acc[4 * j + 2], acc[4 * j + 3]);
            }
        }
        __syncthreads();
        const float4* sp = reinterpret_cast<const float4*>(stg + orow * 168 + oseg * 20);
#pragma unroll
        for (int i = 0; i < 5; i++) {
            const float4 a = sp[i];
            uint2 w;
            w.x = pack_bf16(a.x + bf_lo(br[i].x) + bf_lo(xr[i].x), a.y + bf_hi(br[i].x) + bf_hi(xr[i].x));
            w.y = pack_bf16(a.z + bf_lo(br[i].y) + bf_lo(xr[i].y), a.w + bf_hi(br[i].y) + bf_hi(xr[i].y));
            reinterpret_cast<uint2*>(out + ooff)[i] = w;
        }
        if (blockIdx.x == 0 && threadIdx.x == 0) g_epoch = epoch + 1;
        if (threadIdx.x == 0) TL(3, 3);
    }
    cluster_arrive_relaxed();
    cluster_wait();
}

typedef CUresult (*EncodeTiledFn)(CUtensorMap*, CUtensorMapDataType, cuuint32_t, void*, const cuuint64_t*,
                                  const cuuint64_t*, const cuuint32_t*, const cuuint32_t*, CUtensorMapInterleave,
                                  CUtensorMapSwizzle, CUtensorMapL2promotion, CUtensorMapFloatOOBfill);

CUtensorMap make_map(EncodeTiledFn enc, const void* ptr, int rows, int cols, int box_rows, int box_cols,
                     CUtensorMapSwizzle swz) {
    CUtensorMap m;
    cuuint64_t gd[2] = {(cuuint64_t)cols, (cuuint64_t)rows};
    cuuint64_t gs[1] = {(cuuint64_t)cols * 2};
    cuuint32_t bd[2] = {(cuuint32_t)box_cols, (cuuint32_t)box_rows};
    cuuint32_t es[2] = {1, 1};
    enc(&m, CU_TENSOR_MAP_DATA_TYPE_BFLOAT16, 2, const_cast<void*>(ptr), gd, gs, bd, es, CU_TENSOR_MAP_INTERLEAVE_NONE,
        swz, CU_TENSOR_MAP_L2_PROMOTION_L2_128B, CU_TENSOR_MAP_FLOAT_OOB_FILL_NONE);
    return m;
}

}

extern "C" void kernel_launch(void* const* d_in, const int* in_sizes, int n_in, void* d_out, int out_size) {
    (void)in_sizes; (void)n_in; (void)out_size;
    const __nv_bfloat16* x = (const __nv_bfloat16*)d_in[0];
    const __nv_bfloat16* wqkv = (const __nv_bfloat16*)d_in[1];
    const __nv_bfloat16* wo = (const __nv_bfloat16*)d_in[2];
    const __nv_bfloat16* w1 = (const __nv_bfloat16*)d_in[4];
    const __nv_bfloat16* b1 = (const __nv_bfloat16*)d_in[5];
    const __nv_bfloat16* w2 = (const __nv_bfloat16*)d_in[6];
    const __nv_bfloat16* b2 = (const __nv_bfloat16*)d_in[7];
    __nv_bfloat16* out = (__nv_bfloat16*)d_out;

    static EncodeTiledFn enc = nullptr;
    static void *p_h, *p_o;
    if (!enc) {
        cudaDriverEntryPointQueryResult qr;
        cudaGetDriverEntryPoint("cuTensorMapEncodeTiled", (void**)&enc, cudaEnableDefault, &qr);
        cudaGetSymbolAddress(&p_h, g_h);
        cudaGetSymbolAddress(&p_o, g_o);
        cudaFuncSetAttribute(k_fused, cudaFuncAttributeMaxDynamicSharedMemorySize, SM_TOTAL);
    }
    Maps tm;
    tm.x = make_map(enc, x, SEQ, DM, 128, 64, CU_TENSOR_MAP_SWIZZLE_128B);
    tm.wqkv = make_map(enc, wqkv, DM, 3 * DM, 32, 64, CU_TENSOR_MAP_SWIZZLE_128B);
    tm.w1 = make_map(enc, w1, DM, FF, 32, 64, CU_TENSOR_MAP_SWIZZLE_128B);
    tm.h = make_map(enc, p_h, SEQ, FF, 64, 64, CU_TENSOR_MAP_SWIZZLE_128B);
    tm.o = make_map(enc, p_o, SEQ, DM, 64, 64, CU_TENSOR_MAP_SWIZZLE_128B);
    tm.wo = make_map(enc, wo, DM, DM, 64, 32, CU_TENSOR_MAP_SWIZZLE_64B);
    tm.w2 = make_map(enc, w2, FF, DM, 64, 32, CU_TENSOR_MAP_SWIZZLE_64B);
    k_fused<<<128, 512, SM_TOTAL, cudaStreamPerThread>>>(tm, x, (const uint8_t*)wqkv, (const uint8_t*)w1, (const uint8_t*)w2,
                                                         (const uint8_t*)wo, b1, b2, out);
}
```

```cpp
#include <cuda_runtime.h>
#include <cuda_bf16.h>
#include <cuda.h>
#include <stdint.h>

namespace {

constexpr int SEQ = 2048, DM = 640, FF = 1536;
constexpr float LN_EPS = 1e-5f;

constexpr int IMG_BYTES = 256 * 384;
constexpr uint32_t EMU_MASK = 0xD5D5u;
constexpr float SAFE_BOUND = 80.0f;
constexpr float QSCALE = 0.22360679774997896f * 1.4426950408889634f;

__device__ float4 g_stat[SEQ];
__device__ float2 g_csp[16 * 1728];
__device__ __align__(1024) uint8_t g_img[96 * IMG_BYTES + 1024];
__device__ float g_nrm[64 * SEQ];
__device__ __align__(1024) __nv_bfloat16 g_h[SEQ * FF];
__device__ __align__(1024) __nv_bfloat16 g_o[SEQ * DM];
constexpr int CNT_ST = 0, CNT_QKV = 16, CNT_H = 24, CNT_O = 40, CNT_CS = 44, CNT_CS2 = 52;
__device__ uint32_t g_cnt[60 * 32];
__device__ uint32_t g_epoch;

#define TL(kern, slot) do { } while (0)
#define IT(row, i) do { } while (0)

__device__ __forceinline__ uint32_t smem_u32(const void* p) { return (uint32_t)__cvta_generic_to_shared(p); }
__device__ __forceinline__ void mbar_init(uint32_t bar, int cnt) {
    asm volatile("mbarrier.init.shared::cta.b64 [%0], %1;" ::"r"(bar), "r"(cnt));
}
__device__ __forceinline__ void mbar_expect_tx(uint32_t bar, uint32_t bytes) {
    asm volatile("mbarrier.arrive.expect_tx.shared::cta.b64 _, [%0], %1;" ::"r"(bar), "r"(bytes) : "memory");
}
__device__ __forceinline__ void mbar_wait(uint32_t bar, uint32_t parity) {
    asm volatile("{\n.reg .pred p;\n.reg .u32 n;\nmov.u32 n, 0;\n"
                 "WAIT_LOOP:\nmbarrier.try_wait.parity.shared::cta.b64 p, [%0], %1;\n@p bra WAIT_DONE;\n"
                 "add.u32 n, n, 1;\nsetp.lt.u32 p, n, 4194304;\n@p bra WAIT_LOOP;\nWAIT_DONE:\n}"
                 ::"r"(bar), "r"(parity) : "memory");
}
__device__ __forceinline__ void mbar_arrive(uint32_t bar) {
    asm volatile("mbarrier.arrive.shared::cta.b64 _, [%0];" ::"r"(bar) : "memory");
}
__device__ __forceinline__ void mbar_arrive_cluster(uint32_t bar, uint32_t cta) {
    asm volatile("{\n.reg .b32 ra;\nmapa.shared::cluster.u32 ra, %0, %1;\n"
                 "mbarrier.arrive.shared::cluster.b64 _, [ra];\n}" ::"r"(bar), "r"(cta) : "memory");
}
__device__ __forceinline__ void fence_barrier_init() { asm volatile("fence.mbarrier_init.release.cluster;" ::: "memory"); }
__device__ __forceinline__ void fence_proxy_async() { asm volatile("fence.proxy.async.shared::cta;" ::: "memory"); }
__device__ __forceinline__ void cluster_sync() {
    asm volatile("barrier.cluster.arrive.release.aligned;\nbarrier.cluster.wait.acquire.aligned;" ::: "memory");
}
__device__ __forceinline__ bool elect_one() {
    uint32_t pred;
    asm volatile("{\n.reg .pred p;\nelect.sync _|p, 0xFFFFFFFF;\nselp.b32 %0, 1, 0, p;\n}" : "=r"(pred));
    return pred != 0;
}
__device__ __forceinline__ void pdl_launch() { asm volatile("griddepcontrol.launch_dependents;" ::: "memory"); }
__device__ __forceinline__ void pdl_wait() { asm volatile("griddepcontrol.wait;" ::: "memory"); }
__device__ __forceinline__ void prefetch_map(const CUtensorMap* m) {
    asm volatile("prefetch.tensormap [%0];" ::"l"(m) : "memory");
}
__device__ __forceinline__ void tma_load(uint32_t dst, const CUtensorMap* m, int c0, int c1, uint32_t bar) {
    asm volatile("cp.async.bulk.tensor.2d.shared::cluster.global.mbarrier::complete_tx::bytes [%0], [%1, {%3, %4}], [%2];"
                 ::"r"(dst), "l"(m), "r"(bar), "r"(c0), "r"(c1) : "memory");
}
__device__ __forceinline__ void tma_load_mc(uint32_t dst, const CUtensorMap* m, int c0, int c1, uint32_t bar, uint16_t mask) {
    asm volatile("cp.async.bulk.tensor.2d.shared::cluster.global.mbarrier::complete_tx::bytes.multicast::cluster"
                 " [%0], [%1, {%3, %4}], [%2], %5;"
                 ::"r"(dst), "l"(m), "r"(bar), "r"(c0), "r"(c1), "h"(mask) : "memory");
}
__device__ __forceinline__ void tma_store(const CUtensorMap* m, uint32_t src, int c0, int c1) {
    asm volatile("cp.async.bulk.tensor.2d.global.shared::cta.bulk_group [%0, {%2, %3}], [%1];"
                 ::"l"(m), "r"(src), "r"(c0), "r"(c1) : "memory");
}
__device__ __forceinline__ void bulk_commit() { asm volatile("cp.async.bulk.commit_group;" ::: "memory"); }
__device__ __forceinline__ void bulk_wait_all() { asm volatile("cp.async.bulk.wait_group 0;" ::: "memory"); }
__device__ __forceinline__ void bulk_load(uint32_t dst, const void* src, uint32_t bytes, uint32_t bar) {
    asm volatile("cp.async.bulk.shared::cluster.global.mbarrier::complete_tx::bytes [%0], [%1], %2, [%3];"
                 ::"r"(dst), "l"(src), "r"(bytes), "r"(bar) : "memory");
}
__device__ __forceinline__ void prefetch_l2(const void* p, uint32_t bytes) {
    asm volatile("cp.async.bulk.prefetch.L2.global [%0], %1;" ::"l"(p), "r"(bytes) : "memory");
}
__device__ __forceinline__ void tma_prefetch_l2(const CUtensorMap* m, int c0, int c1) {
    asm volatile("cp.async.bulk.prefetch.tensor.2d.L2.global.tile [%0, {%1, %2}];" ::"l"(m), "r"(c0), "r"(c1) : "memory");
}
__device__ __forceinline__ void wg_fence() { asm volatile("wgmma.fence.sync.aligned;" ::: "memory"); }
__device__ __forceinline__ void wg_commit() { asm volatile("wgmma.commit_group.sync.aligned;" ::: "memory"); }
template <int N> __device__ __forceinline__ void wg_wait() {
    asm volatile("wgmma.wait_group.sync.aligned %0;" ::"n"(N) : "memory");
}
template <int N> __device__ __forceinline__ void reg_alloc() { asm volatile("setmaxnreg.inc.sync.aligned.u32 %0;" ::"n"(N)); }
template <int N> __device__ __forceinline__ void reg_dealloc() { asm volatile("setmaxnreg.dec.sync.aligned.u32 %0;" ::"n"(N)); }
template <int N> __device__ __forceinline__ void fence_regs(float (&d)[N]) {
#pragma unroll
    for (int i = 0; i < N; i++) asm volatile("" : "+f"(d[i])::"memory");
}
__device__ __forceinline__ uint64_t make_desc(uint32_t addr, uint32_t lbo, uint32_t sbo, uint32_t swz) {
    return (uint64_t)((addr & 0x3FFFF) >> 4) | ((uint64_t)(lbo >> 4) << 16) | ((uint64_t)(sbo >> 4) << 32) |
           ((uint64_t)swz << 62);
}
__device__ __forceinline__ uint32_t pack_bf16(float lo, float hi) {
    uint32_t r;
    asm("cvt.rn.bf16x2.f32 %0, %1, %2;" : "=r"(r) : "f"(hi), "f"(lo));
    return r;
}
__device__ __forceinline__ float ex2(float x) {
    float r;
    asm("ex2.approx.ftz.f32 %0, %1;" : "=f"(r) : "f"(x));
    return r;
}
__device__ __forceinline__ float bf_lo(uint32_t v) { return __uint_as_float(v << 16); }
__device__ __forceinline__ float bf_hi(uint32_t v) { return __uint_as_float(v & 0xFFFF0000u); }
__device__ __forceinline__ void stmatrix_x4(uint32_t addr, uint32_t r0, uint32_t r1, uint32_t r2, uint32_t r3) {
    asm volatile("stmatrix.sync.aligned.m8n8.x4.shared.b16 [%0], {%1, %2, %3, %4};"
                 ::"r"(addr), "r"(r0), "r"(r1), "r"(r2), "r"(r3) : "memory");
}

__device__ __forceinline__ void wgmma_n120_ss_tb(float (&d)[60], uint64_t descA, uint64_t descB, int scaleD) {
    asm volatile("{\n.reg .pred p;\nsetp.ne.b32 p, %62, 0;\n"
        "wgmma.mma_async.sync.aligned.m64n120k16.f32.bf16.bf16 {"
        "%0, %1, %2, %3, %4, %5, %6, %7, %8, %9, %10, %11, %12, %13, %14, %15, "
        "%16, %17, %18, %19, %20, %21, %22, %23, %24, %25, %26, %27, %28, %29, %30, %31, "
        "%32, %33, %34, %35, %36, %37, %38, %39, %40, %41, %42, %43, %44, %45, %46, %47, "
        "%48, %49, %50, %51, %52, %53, %54, %55, %56, %57, %58, %59}, "
        "%60, %61, p, 1, 1, 0, 1;\n}\n"
        : "+f"(d[0]), "+f"(d[1]), "+f"(d[2]), "+f"(d[3]), "+f"(d[4]), "+f"(d[5]), "+f"(d[6]), "+f"(d[7]),
          "+f"(d[8]), "+f"(d[9]), "+f"(d[10]), "+f"(d[11]), "+f"(d[12]), "+f"(d[13]), "+f"(d[14]), "+f"(d[15]),
          "+f"(d[16]), "+f"(d[17]), "+f"(d[18]), "+f"(d[19]), "+f"(d[20]), "+f"(d[21]), "+f"(d[22]), "+f"(d[23]),
          "+f"(d[24]), "+f"(d[25]), "+f"(d[26]), "+f"(d[27]), "+f"(d[28]), "+f"(d[29]), "+f"(d[30]), "+f"(d[31]),
          "+f"(d[32]), "+f"(d[33]), "+f"(d[34]), "+f"(d[35]), "+f"(d[36]), "+f"(d[37]), "+f"(d[38]), "+f"(d[39]),
          "+f"(d[40]), "+f"(d[41]), "+f"(d[42]), "+f"(d[43]), "+f"(d[44]), "+f"(d[45]), "+f"(d[46]), "+f"(d[47]),
          "+f"(d[48]), "+f"(d[49]), "+f"(d[50]), "+f"(d[51]), "+f"(d[52]), "+f"(d[53]), "+f"(d[54]), "+f"(d[55]),
          "+f"(d[56]), "+f"(d[57]), "+f"(d[58]), "+f"(d[59])
        : "l"(descA), "l"(descB), "r"(scaleD));
}

__device__ __forceinline__ void wgmma_n192_ss_tb(float (&d)[96], uint64_t descA, uint64_t descB, int scaleD) {
    asm volatile("{\n.reg .pred p;\nsetp.ne.b32 p, %98, 0;\n"
        "wgmma.mma_async.sync.aligned.m64n192k16.f32.bf16.bf16 {"
        "%0, %1, %2, %3, %4, %5, %6, %7, %8, %9, %10, %11, %12, %13, %14, %15, "
        "%16, %17, %18, %19, %20, %21, %22, %23, %24, %25, %26, %27, %28, %29, %30, %31, "
        "%32, %33, %34, %35, %36, %37, %38, %39, %40, %41, %42, %43, %44, %45, %46, %47, "
        "%48, %49, %50, %51, %52, %53, %54, %55, %56, %57, %58, %59, %60, %61, %62, %63, "
        "%64, %65, %66, %67, %68, %69, %70, %71, %72, %73, %74, %75, %76, %77, %78, %79, "
        "%80, %81, %82, %83, %84, %85, %86, %87, %88, %89, %90, %91, %92, %93, %94, %95}, "
        "%96, %97, p, 1, 1, 0, 1;\n}\n"
        : "+f"(d[0]), "+f"(d[1]), "+f"(d[2]), "+f"(d[3]), "+f"(d[4]), "+f"(d[5]), "+f"(d[6]), "+f"(d[7]),
          "+f"(d[8]), "+f"(d[9]), "+f"(d[10]), "+f"(d[11]), "+f"(d[12]), "+f"(d[13]), "+f"(d[14]), "+f"(d[15]),
          "+f"(d[16]), "+f"(d[17]), "+f"(d[18]), "+f"(d[19]), "+f"(d[20]), "+f"(d[21]), "+f"(d[22]), "+f"(d[23]),
          "+f"(d[24]), "+f"(d[25]), "+f"(d[26]), "+f"(d[27]), "+f"(d[28]), "+f"(d[29]), "+f"(d[30]), "+f"(d[31]),
          "+f"(d[32]), "+f"(d[33]), "+f"(d[34]), "+f"(d[35]), "+f"(d[36]), "+f"(d[37]), "+f"(d[38]), "+f"(d[39]),
          "+f"(d[40]), "+f"(d[41]), "+f"(d[42]), "+f"(d[43]), "+f"(d[44]), "+f"(d[45]), "+f"(d[46]), "+f"(d[47]),
          "+f"(d[48]), "+f"(d[49]), "+f"(d[50]), "+f"(d[51]), "+f"(d[52]), "+f"(d[53]), "+f"(d[54]), "+f"(d[55]),
          "+f"(d[56]), "+f"(d[57]), "+f"(d[58]), "+f"(d[59]), "+f"(d[60]), "+f"(d[61]), "+f"(d[62]), "+f"(d[63]),
          "+f"(d[64]), "+f"(d[65]), "+f"(d[66]), "+f"(d[67]), "+f"(d[68]), "+f"(d[69]), "+f"(d[70]), "+f"(d[71]),
          "+f"(d[72]), "+f"(d[73]), "+f"(d[74]), "+f"(d[75]), "+f"(d[76]), "+f"(d[77]), "+f"(d[78]), "+f"(d[79]),
          "+f"(d[80]), "+f"(d[81]), "+f"(d[82]), "+f"(d[83]), "+f"(d[84]), "+f"(d[85]), "+f"(d[86]), "+f"(d[87]),
          "+f"(d[88]), "+f"(d[89]), "+f"(d[90]), "+f"(d[91]), "+f"(d[92]), "+f"(d[93]), "+f"(d[94]), "+f"(d[95])
        : "l"(descA), "l"(descB), "r"(scaleD));
}

__device__ __forceinline__ void wgmma_n192_ss_tb_z(float (&d)[96], uint64_t descA, uint64_t descB) {
    asm volatile("{\n.reg .pred p;\nsetp.ne.b32 p, 0, 0;\n"
        "wgmma.mma_async.sync.aligned.m64n192k16.f32.bf16.bf16 {"
        "%0, %1, %2, %3, %4, %5, %6, %7, %8, %9, %10, %11, %12, %13, %14, %15, "
        "%16, %17, %18, %19, %20, %21, %22, %23, %24, %25, %26, %27, %28, %29, %30, %31, "
        "%32, %33, %34, %35, %36, %37, %38, %39, %40, %41, %42, %43, %44, %45, %46, %47, "
        "%48, %49, %50, %51, %52, %53, %54, %55, %56, %57, %58, %59, %60, %61, %62, %63, "
        "%64, %65, %66, %67, %68, %69, %70, %71, %72, %73, %74, %75, %76, %77, %78, %79, "
        "%80, %81, %82, %83, %84, %85, %86, %87, %88, %89, %90, %91, %92, %93, %94, %95}, "
        "%96, %97, p, 1, 1, 0, 1;\n}\n"
        : "=f"(d[0]), "=f"(d[1]), "=f"(d[2]), "=f"(d[3]), "=f"(d[4]), "=f"(d[5]), "=f"(d[6]), "=f"(d[7]),
          "=f"(d[8]), "=f"(d[9]), "=f"(d[10]), "=f"(d[11]), "=f"(d[12]), "=f"(d[13]), "=f"(d[14]), "=f"(d[15]),
          "=f"(d[16]), "=f"(d[17]), "=f"(d[18]), "=f"(d[19]), "=f"(d[20]), "=f"(d[21]), "=f"(d[22]), "=f"(d[23]),
          "=f"(d[24]), "=f"(d[25]), "=f"(d[26]), "=f"(d[27]), "=f"(d[28]), "=f"(d[29]), "=f"(d[30]), "=f"(d[31]),
          "=f"(d[32]), "=f"(d[33]), "=f"(d[34]), "=f"(d[35]), "=f"(d[36]), "=f"(d[37]), "=f"(d[38]), "=f"(d[39]),
          "=f"(d[40]), "=f"(d[41]), "=f"(d[42]), "=f"(d[43]), "=f"(d[44]), "=f"(d[45]), "=f"(d[46]), "=f"(d[47]),
          "=f"(d[48]), "=f"(d[49]), "=f"(d[50]), "=f"(d[51]), "=f"(d[52]), "=f"(d[53]), "=f"(d[54]), "=f"(d[55]),
          "=f"(d[56]), "=f"(d[57]), "=f"(d[58]), "=f"(d[59]), "=f"(d[60]), "=f"(d[61]), "=f"(d[62]), "=f"(d[63]),
          "=f"(d[64]), "=f"(d[65]), "=f"(d[66]), "=f"(d[67]), "=f"(d[68]), "=f"(d[69]), "=f"(d[70]), "=f"(d[71]),
          "=f"(d[72]), "=f"(d[73]), "=f"(d[74]), "=f"(d[75]), "=f"(d[76]), "=f"(d[77]), "=f"(d[78]), "=f"(d[79]),
          "=f"(d[80]), "=f"(d[81]), "=f"(d[82]), "=f"(d[83]), "=f"(d[84]), "=f"(d[85]), "=f"(d[86]), "=f"(d[87]),
          "=f"(d[88]), "=f"(d[89]), "=f"(d[90]), "=f"(d[91]), "=f"(d[92]), "=f"(d[93]), "=f"(d[94]), "=f"(d[95])
        : "l"(descA), "l"(descB));
}

__device__ __forceinline__ void wgmma_n160_ss_tb(float (&d)[80], uint64_t descA, uint64_t descB, int scaleD) {
    asm volatile("{\n.reg .pred p;\nsetp.ne.b32 p, %82, 0;\n"
        "wgmma.mma_async.sync.aligned.m64n160k16.f32.bf16.bf16 {"
        "%0, %1, %2, %3, %4, %5, %6, %7, %8, %9, %10, %11, %12, %13, %14, %15, "
        "%16, %17, %18, %19, %20, %21, %22, %23, %24, %25, %26, %27, %28, %29, %30, %31, "
        "%32, %33, %34, %35, %36, %37, %38, %39, %40, %41, %42, %43, %44, %45, %46, %47, "
        "%48, %49, %50, %51, %52, %53, %54, %55, %56, %57, %58, %59, %60, %61, %62, %63, "
        "%64, %65, %66, %67, %68, %69, %70, %71, %72, %73, %74, %75, %76, %77, %78, %79}, "
        "%80, %81, p, 1, 1, 0, 1;\n}\n"
        : "+f"(d[0]), "+f"(d[1]), "+f"(d[2]), "+f"(d[3]), "+f"(d[4]), "+f"(d[5]), "+f"(d[6]), "+f"(d[7]),
          "+f"(d[8]), "+f"(d[9]), "+f"(d[10]), "+f"(d[11]), "+f"(d[12]), "+f"(d[13]), "+f"(d[14]), "+f"(d[15]),
          "+f"(d[16]), "+f"(d[17]), "+f"(d[18]), "+f"(d[19]), "+f"(d[20]), "+f"(d[21]), "+f"(d[22]), "+f"(d[23]),
          "+f"(d[24]), "+f"(d[25]), "+f"(d[26]), "+f"(d[27]), "+f"(d[28]), "+f"(d[29]), "+f"(d[30]), "+f"(d[31]),
          "+f"(d[32]), "+f"(d[33]), "+f"(d[34]), "+f"(d[35]), "+f"(d[36]), "+f"(d[37]), "+f"(d[38]), "+f"(d[39]),
          "+f"(d[40]), "+f"(d[41]), "+f"(d[42]), "+f"(d[43]), "+f"(d[44]), "+f"(d[45]), "+f"(d[46]), "+f"(d[47]),
          "+f"(d[48]), "+f"(d[49]), "+f"(d[50]), "+f"(d[51]), "+f"(d[52]), "+f"(d[53]), "+f"(d[54]), "+f"(d[55]),
          "+f"(d[56]), "+f"(d[57]), "+f"(d[58]), "+f"(d[59]), "+f"(d[60]), "+f"(d[61]), "+f"(d[62]), "+f"(d[63]),
          "+f"(d[64]), "+f"(d[65]), "+f"(d[66]), "+f"(d[67]), "+f"(d[68]), "+f"(d[69]), "+f"(d[70]), "+f"(d[71]),
          "+f"(d[72]), "+f"(d[73]), "+f"(d[74]), "+f"(d[75]), "+f"(d[76]), "+f"(d[77]), "+f"(d[78]), "+f"(d[79])
        : "l"(descA), "l"(descB), "r"(scaleD));
}

__device__ __forceinline__ void wgmma_n64_ss(float (&d)[32], uint64_t descA, uint64_t descB, int scaleD) {
    asm volatile("{\n.reg .pred p;\nsetp.ne.b32 p, %34, 0;\n"
        "wgmma.mma_async.sync.aligned.m64n64k16.f32.bf16.bf16 {"
        "%0, %1, %2, %3, %4, %5, %6, %7, %8, %9, %10, %11, %12, %13, %14, %15, "
        "%16, %17, %18, %19, %20, %21, %22, %23, %24, %25, %26, %27, %28, %29, %30, %31}, "
        "%32, %33, p, 1, 1, 0, 0;\n}\n"
        : "+f"(d[0]), "+f"(d[1]), "+f"(d[2]), "+f"(d[3]), "+f"(d[4]), "+f"(d[5]), "+f"(d[6]), "+f"(d[7]),
          "+f"(d[8]), "+f"(d[9]), "+f"(d[10]), "+f"(d[11]), "+f"(d[12]), "+f"(d[13]), "+f"(d[14]), "+f"(d[15]),
          "+f"(d[16]), "+f"(d[17]), "+f"(d[18]), "+f"(d[19]), "+f"(d[20]), "+f"(d[21]), "+f"(d[22]), "+f"(d[23]),
          "+f"(d[24]), "+f"(d[25]), "+f"(d[26]), "+f"(d[27]), "+f"(d[28]), "+f"(d[29]), "+f"(d[30]), "+f"(d[31])
        : "l"(descA), "l"(descB), "r"(scaleD));
}

__device__ __forceinline__ void wgmma_n64_ss_z(float (&d)[32], uint64_t descA, uint64_t descB) {
    asm volatile("{\n.reg .pred p;\nsetp.ne.b32 p, 0, 0;\n"
        "wgmma.mma_async.sync.aligned.m64n64k16.f32.bf16.bf16 {"
        "%0, %1, %2, %3, %4, %5, %6, %7, %8, %9, %10, %11, %12, %13, %14, %15, "
        "%16, %17, %18, %19, %20, %21, %22, %23, %24, %25, %26, %27, %28, %29, %30, %31}, "
        "%32, %33, p, 1, 1, 0, 0;\n}\n"
        : "=f"(d[0]), "=f"(d[1]), "=f"(d[2]), "=f"(d[3]), "=f"(d[4]), "=f"(d[5]), "=f"(d[6]), "=f"(d[7]),
          "=f"(d[8]), "=f"(d[9]), "=f"(d[10]), "=f"(d[11]), "=f"(d[12]), "=f"(d[13]), "=f"(d[14]), "=f"(d[15]),
          "=f"(d[16]), "=f"(d[17]), "=f"(d[18]), "=f"(d[19]), "=f"(d[20]), "=f"(d[21]), "=f"(d[22]), "=f"(d[23]),
          "=f"(d[24]), "=f"(d[25]), "=f"(d[26]), "=f"(d[27]), "=f"(d[28]), "=f"(d[29]), "=f"(d[30]), "=f"(d[31])
        : "l"(descA), "l"(descB));
}

__device__ __forceinline__ void wgmma_n24_rs_tb(float (&d)[12], uint32_t a0, uint32_t a1, uint32_t a2, uint32_t a3, uint64_t descB, int scaleD) {
    asm volatile("{\n.reg .pred p;\nsetp.ne.b32 p, %17, 0;\n"
        "wgmma.mma_async.sync.aligned.m64n24k16.f32.bf16.bf16 {"
        "%0, %1, %2, %3, %4, %5, %6, %7, %8, %9, %10, %11}, "
        "{%12, %13, %14, %15}, %16, p, 1, 1, 1;\n}\n"
        : "+f"(d[0]), "+f"(d[1]), "+f"(d[2]), "+f"(d[3]), "+f"(d[4]), "+f"(d[5]), "+f"(d[6]), "+f"(d[7]),
          "+f"(d[8]), "+f"(d[9]), "+f"(d[10]), "+f"(d[11])
        : "r"(a0), "r"(a1), "r"(a2), "r"(a3), "l"(descB), "r"(scaleD));
}

__device__ __forceinline__ void cnt_signal(int idx) {
    asm volatile("fence.acq_rel.gpu;\nred.relaxed.gpu.global.add.u32 [%0], 1;"
                 ::"l"(g_cnt + idx * 32) : "memory");
}
__device__ __forceinline__ void cnt_wait(int idx, uint32_t target) {
    const uint32_t* p = g_cnt + idx * 32;
#pragma unroll 1
    for (uint32_t i = 0; i < (1u << 22); i++) {
        uint32_t v;
        asm volatile("ld.acquire.gpu.global.u32 %0, [%1];" : "=r"(v) : "l"(p) : "memory");
        if ((int32_t)(v - target) >= 0) break;
    }
    asm volatile("fence.proxy.async.global;" ::: "memory");
}
__device__ __forceinline__ void cluster_arrive() { asm volatile("barrier.cluster.arrive.release.aligned;" ::: "memory"); }
__device__ __forceinline__ void cluster_arrive_relaxed() { asm volatile("barrier.cluster.arrive.relaxed.aligned;" ::: "memory"); }
__device__ __forceinline__ void cluster_wait() { asm volatile("barrier.cluster.wait.acquire.aligned;" ::: "memory"); }
__device__ __forceinline__ void bulk_wait_read() { asm volatile("cp.async.bulk.wait_group.read 0;" ::: "memory"); }

__device__ __forceinline__ float gelu_tanh(float x) {
    const float u = x * (0.7978845608028654f + 0.035677408136300125f * x * x);
    float t;
    asm("tanh.approx.f32 %0, %1;" : "=f"(t) : "f"(u));
    const float h = 0.5f * x;
    return fmaf(h, t, h);
}
__device__ __forceinline__ void release_stage(uint32_t bar, uint32_t peer, int lane) {
    if (lane == 0) { mbar_arrive(bar); mbar_arrive_cluster(bar, peer); }
}

constexpr int SM_RING = 163840;
constexpr int SM_Q = 2 * IMG_BYTES, SM_ZERO = SM_Q + 24576;
constexpr int G2_STAGE = 8192 + 20480;
constexpr int SM_MISC = 229376;
constexpr int SM_BIAS = SM_MISC, SM_RED = SM_BIAS + 384, SM_BAR = SM_RED + 128;
constexpr int B_A = 0, B_F1 = 10, B_E1 = 14, B_F2 = 18, B_E2 = 23, B_KV = 28, B_Q = 45, B_F3 = 47, B_E3 = 55, B_ST = 63, B_STAT = 65, B_AUX = 66, B_AUX2 = 67, B_COUNT = 68;
constexpr int SM_EPOCH = SM_BAR + 544;
constexpr int SM_CS = SM_EPOCH + 16;
constexpr int SM_TOTAL = SM_CS + 1728;
static_assert(SM_TOTAL <= 232448, "shared memory budget");

struct Maps { CUtensorMap x, wqkv, w1, h, o, wo, w2; };

__device__ __forceinline__ uint32_t bf2_fma(uint32_t a, uint32_t b, uint32_t c) {
    uint32_t r;
    asm("fma.rn.bf16x2 %0, %1, %2, %3;" : "=r"(r) : "r"(a), "r"(b), "r"(c));
    return r;
}
__device__ __forceinline__ uint32_t lop_and_or(uint32_t a, uint32_t m, uint32_t o) {
    uint32_t r;
    asm("lop3.b32 %0, %1, %2, %3, 0xEA;" : "=r"(r) : "r"(a), "r"(m), "r"(o));
    return r;
}
struct ExpConst { uint32_t mask, slope; };
__device__ __forceinline__ ExpConst make_exp_const() {
    ExpConst k;
    asm volatile("mov.b32 %0, 0x007F007F;" : "=r"(k.mask));
    asm volatile("mov.b32 %0, 0x3EF83EF8;" : "=r"(k.slope));
    return k;
}
__device__ __forceinline__ uint32_t exp2_pair_fma(float t0, float t1, const ExpConst& k) {
    const uint32_t L = __byte_perm(__float_as_uint(t0), __float_as_uint(t1), 0x6521);
    const uint32_t g = lop_and_or(L, k.mask, 0x3F803F80u);
    const uint32_t u = bf2_fma(g, k.slope, 0xBF37BF37u);
    const uint32_t e = bf2_fma(u, u, 0xBD71BD71u);
    return bf2_fma(L, e, L);
}
template <int SHIFT>
__device__ __forceinline__ void exp_tile(const float (&s)[32], uint32_t (&p)[16], const ExpConst& k) {
#pragma unroll
    for (int b = 0; b < 8; b++) {
        if ((EMU_MASK >> (b + SHIFT)) & 1) {
            p[2 * b] = exp2_pair_fma(s[4 * b], s[4 * b + 1], k);
            p[2 * b + 1] = exp2_pair_fma(s[4 * b + 2], s[4 * b + 3], k);
        } else {
            p[2 * b] = pack_bf16(ex2(s[4 * b]), ex2(s[4 * b + 1]));
            p[2 * b + 1] = pack_bf16(ex2(s[4 * b + 2]), ex2(s[4 * b + 3]));
        }
    }
}

__device__ __forceinline__ void qk_tile(float (&s)[32], uint64_t dQ, uint64_t dQ2, uint64_t dK) {
    wg_fence();
    wgmma_n64_ss_z(s, dQ, dK);
    wgmma_n64_ss(s, dQ2, dK + 16, 1);
    wg_commit();
}
__device__ __forceinline__ void pv_tile(float (&o)[12], const uint32_t (&p)[16], uint64_t dV) {
    wg_fence();
#pragma unroll
    for (int ks = 0; ks < 4; ks++)
        wgmma_n24_rs_tb(o, p[4 * ks], p[4 * ks + 1], p[4 * ks + 2], p[4 * ks + 3], dV + ks * 48, 1);
    wg_commit();
}
__device__ __forceinline__ void store_o(const float (&o)[12], int h, int rbase, int lane) {
    const int g = lane >> 2, c = lane & 3;
    const bool odd = h & 1;
    const int lsrc = (lane & ~3) | (odd ? 0 : 2);
    const float i0 = 1.f / __shfl_sync(~0u, o[8], lsrc), i1 = 1.f / __shfl_sync(~0u, o[10], lsrc);
    __nv_bfloat16* dst = g_o + (size_t)(rbase + g) * DM + h * 20;
    const int d0 = (odd ? 4 : 0) + 2 * c, d1 = d0 + 8, d2 = odd ? 2 * c - 4 : 16 + 2 * c;
    *(uint32_t*)(dst + d0) = pack_bf16(o[0] * i0, o[1] * i0);
    *(uint32_t*)(dst + d1) = pack_bf16(o[4] * i0, o[5] * i0);
    *(uint32_t*)(dst + 8 * DM + d0) = pack_bf16(o[2] * i1, o[3] * i1);
    *(uint32_t*)(dst + 8 * DM + d1) = pack_bf16(o[6] * i1, o[7] * i1);
    if (odd ? (c >= 2) : (c < 2)) {
        *(uint32_t*)(dst + d2) = pack_bf16(o[8] * i0, o[9] * i0);
        *(uint32_t*)(dst + 8 * DM + d2) = pack_bf16(o[10] * i1, o[11] * i1);
    }
}

__device__ __forceinline__ void attn_rows_maxshift(uint32_t sK, uint32_t barKV, uint64_t dQ, uint64_t dQ2, int h, int rbase) {
    const int lane = threadIdx.x & 31;
    const uint64_t dK0 = make_desc(sK, 128, 384, 0), dV0 = make_desc(sK + IMG_BYTES, 384, 128, 0);
    float o[12], s[32];
    uint32_t p[16];
#pragma unroll
    for (int i = 0; i < 12; i++) o[i] = 0.f;
    float m0 = -3.0e38f, m1 = -3.0e38f;
    mbar_wait(barKV + 128, 0);
#pragma unroll 1
    for (int t = 0; t < 32; t++) {
        mbar_wait(barKV + (t >> 1) * 8, 0);
        qk_tile(s, dQ, dQ2, dK0 + t * 192);
        wg_wait<0>();
        fence_regs(s);
        const uint32_t mask = EMU_MASK >> ((t & 1) * 8);
        float n0 = m0, n1 = m1;
#pragma unroll
        for (int b = 0; b < 8; b++) {
            const bool emu = (mask >> b) & 1;
            const float f = emu ? 0.5f : 1.f, off = emu ? -383.00390625f : 0.f;
#pragma unroll
            for (int i = 0; i < 4; i++) s[4 * b + i] = fmaf(s[4 * b + i], f, off);
            n0 = fmaxf(n0, fmaxf(s[4 * b], s[4 * b + 1]));
            n1 = fmaxf(n1, fmaxf(s[4 * b + 2], s[4 * b + 3]));
        }
        n0 = fmaxf(n0, __shfl_xor_sync(~0u, n0, 1)); n0 = fmaxf(n0, __shfl_xor_sync(~0u, n0, 2));
        n1 = fmaxf(n1, __shfl_xor_sync(~0u, n1, 1)); n1 = fmaxf(n1, __shfl_xor_sync(~0u, n1, 2));
        const float c0 = ex2(m0 - n0), c1 = ex2(m1 - n1);
        m0 = n0; m1 = n1;
#pragma unroll
        for (int b = 0; b < 3; b++) { o[4 * b] *= c0; o[4 * b + 1] *= c0; o[4 * b + 2] *= c1; o[4 * b + 3] *= c1; }
#pragma unroll
        for (int b = 0; b < 8; b++) {
            p[2 * b] = pack_bf16(ex2(s[4 * b] - m0), ex2(s[4 * b + 1] - m0));
            p[2 * b + 1] = pack_bf16(ex2(s[4 * b + 2] - m1), ex2(s[4 * b + 3] - m1));
        }
        pv_tile(o, p, dV0 + t * 192);
        wg_wait<0>();
        fence_regs(o);
    }
    store_o(o, h, rbase, lane);
}

__global__ void __launch_bounds__(512, 1) __cluster_dims__(2, 1, 1)
k_fused(const __grid_constant__ Maps tm, const __nv_bfloat16* __restrict__ x, const uint8_t* __restrict__ wqkv,
        const uint8_t* __restrict__ w1, const uint8_t* __restrict__ w2, const uint8_t* __restrict__ wo,
        const __nv_bfloat16* __restrict__ b1, const __nv_bfloat16* __restrict__ b2, __nv_bfloat16* __restrict__ out) {
    extern __shared__ __align__(1024) uint8_t smem[];
    const uint32_t sb = smem_u32(smem);
    const uint32_t bar = sb + SM_BAR;
    const int warp = __shfl_sync(~0u, threadIdx.x >> 5, 0), lane = threadIdx.x & 31;
    const int wgi = warp >> 2, w4 = warp & 3, g = lane >> 2, c = lane & 3;
    const uint32_t rank = blockIdx.x & 1, peer = rank ^ 1;
    const int cl = blockIdx.x >> 1;
    const int cg = cl & 7, rb = (cl >> 3) * 2 + rank;

    if (warp == 15 && elect_one()) {
        prefetch_map(&tm.x); prefetch_map(&tm.wqkv);
        for (int kb = 0; kb < 3; kb++) tma_prefetch_l2(&tm.x, kb * 64, rb * 128);
        for (int it = 0; it < 4; it++) {
            tma_prefetch_l2(&tm.wqkv, cg * 240 + rank * 120, it * 32);
            tma_prefetch_l2(&tm.wqkv, cg * 240 + rank * 120 + 64, it * 32);
        }
        prefetch_map(&tm.w1); prefetch_map(&tm.h);
    }
    if (threadIdx.x < B_COUNT) {
        const int i = threadIdx.x;
        const int cnt = (i >= B_E1 && i < B_F2) || (i >= B_E2 && i < B_KV) ? 16
                      : (i >= B_E3 && i <= B_ST) || i == B_STAT ? 8 : i == B_ST + 1 ? 2 : i >= B_AUX ? 7 : 1;
        mbar_init(bar + i * 8, cnt);
        fence_barrier_init();
    }
    __syncthreads();
    cluster_arrive_relaxed();
    cluster_wait();

    {
        const uint32_t sB = sb + SM_RING;
        if (threadIdx.x == 0) TL(1, 0);
        if (wgi < 2) {
            reg_dealloc<40>();
            if (warp == 0) {
#pragma unroll 1
                for (int it = 0; it < 20; it++) {
                    const int s = it & 3;
                    if (it >= 4) mbar_wait(bar + (B_E1 + s) * 8, ((it >> 2) - 1) & 1);
                    if (elect_one()) {
                        const uint32_t dst = sB + s * 16384 + rank * 8192, fb = bar + (B_F1 + s) * 8;
                        const int c0 = cg * 240 + rank * 120;
                        mbar_expect_tx(fb, 16384);
                        tma_load_mc(dst, &tm.wqkv, c0, it * 32, fb, 3);
                        tma_load_mc(dst + 4096, &tm.wqkv, c0 + 64, it * 32, fb, 3);
                    }
                    __syncwarp();
                    const int kb = it < 3 ? it : (it & 1) ? 10 : (it >> 1) + 1;
                    if (kb < 10 && elect_one()) {
                        mbar_expect_tx(bar + (B_A + kb) * 8, 16384);
                        tma_load(sb + kb * 16384, &tm.x, kb * 64, rb * 128, bar + (B_A + kb) * 8);
                    }
                    __syncwarp();
                }
#pragma unroll 1
                for (int it = 0; it < 20; it++) {
                    const int s = it % 5;
                    if (it < 5) { if (it != 3) mbar_wait(bar + (B_E1 + (it == 4 ? 3 : it)) * 8, 0); }
                    else mbar_wait(bar + (B_E2 + s) * 8, ((it / 5) - 1) & 1);
                    if (elect_one()) {
                        const uint32_t dst = sB + s * 12288, fb = bar + (B_F2 + s) * 8;
                        mbar_expect_tx(fb, 12288);
                        if ((it & 1) == (int)rank) {
                            tma_load_mc(dst, &tm.w1, cg * 192, it * 32, fb, 3);
                            tma_load_mc(dst + 4096, &tm.w1, cg * 192 + 64, it * 32, fb, 3);
                        } else {
                            tma_load_mc(dst + 8192, &tm.w1, cg * 192 + 128, it * 32, fb, 3);
                        }
                    }
                    __syncwarp();
                }
            } else {
                const int ht = threadIdx.x - 32;
                if (ht == 192) *reinterpret_cast<volatile uint32_t*>(smem + SM_EPOCH) = *(volatile uint32_t*)&g_epoch;
                auto slab_sum = [&](const uint32_t* src, int pitch) {
                    float s0 = 0.f, s1 = 0.f;
#pragma unroll
                    for (int h2 = 0; h2 < 2; h2++) {
                        uint32_t v[20];
#pragma unroll
                        for (int k = 0; k < 20; k++) v[k] = __ldg(src + (h2 * 20 + k) * pitch);
#pragma unroll
                        for (int k = 0; k < 20; k++) { s0 += bf_lo(v[k]); s1 += bf_hi(v[k]); }
                    }
                    return make_float2(s0, s1);
                };
                auto gather = [&](int idx) {
                    float s0 = 0.f, s1 = 0.f;
#pragma unroll
                    for (int r = 0; r < 16; r++) {
                        const float2 v = __ldcg(g_csp + r * 1728 + cg * 216 + idx);
                        s0 += v.x; s1 += v.y;
                    }
                    reinterpret_cast<float2*>(smem + SM_CS)[idx] = make_float2(s0, s1);
                };
                if (ht < 120)
                    g_csp[rb * 1728 + cg * 216 + ht] = slab_sum(reinterpret_cast<const uint32_t*>(wqkv) + rb * 40 * 960 + cg * 120 + ht, 960);
                if (threadIdx.x == 64) IT(3, 0);
                asm volatile("bar.sync 8, 224;" ::: "memory");
                const uint32_t epoch = *reinterpret_cast<volatile uint32_t*>(smem + SM_EPOCH);
                if (warp == 6) { if (elect_one()) cnt_signal(CNT_CS + cg); __syncwarp(); }
                if (warp == 7) {
                    mbar_wait(bar + B_STAT * 8, 0);
                    if (elect_one()) cnt_signal(CNT_ST + rb);
                    __syncwarp();
                }
                if (ht < 96) {
                    g_csp[rb * 1728 + cg * 216 + 120 + ht] = slab_sum(reinterpret_cast<const uint32_t*>(w1) + rb * 40 * 768 + cg * 96 + ht, 768);
                    reinterpret_cast<uint32_t*>(smem + SM_BIAS)[ht] = __ldg(reinterpret_cast<const uint32_t*>(b1 + cg * 192) + ht);
                }
                asm volatile("bar.sync 8, 224;" ::: "memory");
                if (warp == 6) { if (elect_one()) cnt_signal(CNT_CS2 + cg); __syncwarp(); }
                if (threadIdx.x == 64) IT(3, 2);
                if (lane == 0) { cnt_wait(CNT_CS + cg, (epoch + 1) * 16); cnt_wait(CNT_ST + rb, (epoch + 1) * 8); }
                __syncwarp();
                if (threadIdx.x == 64) IT(3, 4);
                if (ht < 120) gather(ht);
                __syncwarp();
                if (threadIdx.x == 64) IT(3, 5);
                if (lane == 0) mbar_arrive(bar + B_AUX * 8);
                if (warp == 3 && elect_one()) {
                    prefetch_l2(w2 + blockIdx.x * 15360, 15360);
                    prefetch_l2(wo + blockIdx.x * 6400, 6400);
                }
                if (lane == 0) cnt_wait(CNT_CS2 + cg, (epoch + 1) * 16);
                __syncwarp();
                if (ht < 96) gather(120 + ht);
                __syncwarp();
                if (lane == 0) mbar_arrive(bar + B_AUX2 * 8);
                if (warp == 4) {
                    mbar_wait(bar + B_ST * 8, 0);
                    if (elect_one()) cnt_signal(CNT_QKV + cg);
                    __syncwarp();
                }
            }
            asm volatile("bar.sync %0, 128;" ::"r"(wgi + 3) : "memory");
            reg_alloc<128>();
        } else {
            reg_alloc<216>();
            const int wi = wgi - 2;
            const int row0 = rb * 128 + wi * 64 + w4 * 16 + g;
            const uint32_t sAw = sb + wi * 8192;
            const int rbk = row0 >> 3, hs0 = cg * 12;
            const int srow = rb * 128 + cg * 16 + (warp - 8) * 2 + (lane >> 4);
            uint4 xv[5];
#pragma unroll
            for (int i = 0; i < 5; i++) xv[i] = __ldg(reinterpret_cast<const uint4*>(x + (size_t)srow * DM) + (lane & 15) + 16 * i);
            float acc1[2][60];
#pragma unroll 1
            for (int it = 0; it < 20; it++) {
                const int s = it & 3;
                if (!(it & 1)) mbar_wait(bar + (B_A + (it >> 1)) * 8, 0);
                if (threadIdx.x == 256 && it == 0) TL(0, 2);
                if (threadIdx.x == 256) IT(0, it);
                mbar_wait(bar + (B_F1 + s) * 8, (it >> 2) & 1);
                if (threadIdx.x == 256) IT(1, it);
                wg_fence();
                const uint64_t dA = make_desc(sAw + (it >> 1) * 16384 + (it & 1) * 64, 16, 1024, 1);
                const uint64_t dB = make_desc(sB + s * 16384, 4096, 1024, 1);
                wgmma_n120_ss_tb(acc1[0], dA, dB, it > 0);
                wgmma_n120_ss_tb(acc1[1], dA, dB + 512, it > 0);
                wgmma_n120_ss_tb(acc1[0], dA + 2, dB + 128, 1);
                wgmma_n120_ss_tb(acc1[1], dA + 2, dB + 640, 1);
                wg_commit();
                if (it > 0) { wg_wait<1>(); release_stage(bar + (B_E1 + ((it - 1) & 3)) * 8, peer, lane); }
                if (it == 5) {
                    float sm = 0.f;
#pragma unroll
                    for (int i = 0; i < 5; i++)
                        sm += (bf_lo(xv[i].x) + bf_hi(xv[i].x)) + (bf_lo(xv[i].y) + bf_hi(xv[i].y)) +
                              (bf_lo(xv[i].z) + bf_hi(xv[i].z)) + (bf_lo(xv[i].w) + bf_hi(xv[i].w));
#pragma unroll
                    for (int o = 8; o; o >>= 1) sm += __shfl_xor_sync(~0u, sm, o);
                    const float mu = sm * (1.f / DM);
                    float q = 0.f;
#pragma unroll
                    for (int i = 0; i < 5; i++) {
                        const uint32_t w[4] = {xv[i].x, xv[i].y, xv[i].z, xv[i].w};
#pragma unroll
                        for (int j = 0; j < 4; j++) {
                            const float d0 = bf_lo(w[j]) - mu, d1 = bf_hi(w[j]) - mu;
                            q = fmaf(d0, d0, fmaf(d1, d1, q));
                        }
                    }
#pragma unroll
                    for (int o = 8; o; o >>= 1) q += __shfl_xor_sync(~0u, q, o);
                    const float var = q * (1.f / DM);
                    const float r1 = 1.f / sqrtf(var + LN_EPS);
                    const float r2 = 1.f / sqrtf(var * r1 * r1 + LN_EPS);
                    if ((lane & 15) == 0) g_stat[srow] = make_float4(mu, r1, r1 * r2, 0.f);
                    __syncwarp();
                    if (lane == 0) mbar_arrive(bar + B_STAT * 8);
                }
            }
            if (threadIdx.x == 256) IT(2, 0);
            mbar_wait(bar + B_AUX * 8, 0);
            if (threadIdx.x == 256) IT(2, 1);
            const float4 st0 = __ldcg(g_stat + row0), st1 = __ldcg(g_stat + row0 + 8);
            wg_wait<0>();
            release_stage(bar + (B_E1 + 3) * 8, peer, lane);
            fence_regs(acc1[0]);
            fence_regs(acc1[1]);
            if (threadIdx.x == 256) TL(1, 1);
            const float2* cs = reinterpret_cast<const float2*>(smem + SM_CS) + c;
            uint8_t* img = g_img + (size_t)hs0 * IMG_BYTES + rbk * 384 + g * 16 + c * 4;
            const bool emu0 = (EMU_MASK >> (rbk & 15)) & 1, emu1 = (EMU_MASK >> ((rbk + 1) & 15)) & 1;
            const bool low = c < 2;
            uint32_t pk[60];
#pragma unroll
            for (int m = 0; m < 6; m++) {
                const int which = (hs0 + 2 * m) >> 5;
                const float m0 = st0.y * (which == 0 ? QSCALE : (which == 1 && emu0) ? 2.f : 1.f);
                const float m1 = st1.y * (which == 0 ? QSCALE : (which == 1 && emu1) ? 2.f : 1.f);
                const float d0 = -st0.x * m0, d1 = -st1.x * m1;
                const float* a = &acc1[m / 3][20 * (m % 3)];
#pragma unroll
                for (int b = 0; b < 5; b++) {
                    const float2 cv = cs[(5 * m + b) * 4];
                    pk[10 * m + 2 * b] = pack_bf16(fmaf(a[4 * b], m0, d0 * cv.x), fmaf(a[4 * b + 1], m0, d0 * cv.y));
                    pk[10 * m + 2 * b + 1] = pack_bf16(fmaf(a[4 * b + 2], m1, d1 * cv.x), fmaf(a[4 * b + 3], m1, d1 * cv.y));
                }
            }
            const float r20 = st0.z, r21 = st1.z, e20 = -st0.x * st0.z, e21 = -st1.x * st1.z;
            if (threadIdx.x == 256) IT(2, 2);
            float acc2[96];
#pragma unroll
            for (int it = 0; it < 20; it++) {
                const int s = it % 5;
                if (threadIdx.x == 256) IT(0, 20 + it);
                mbar_wait(bar + (B_F2 + s) * 8, (it / 5) & 1);
                if (threadIdx.x == 256) IT(1, 20 + it);
                wg_fence();
                const uint64_t dA = make_desc(sAw + (it >> 1) * 16384 + (it & 1) * 64, 16, 1024, 1);
                const uint64_t dB = make_desc(sB + s * 12288, 4096, 1024, 1);
                if (it == 0) wgmma_n192_ss_tb_z(acc2, dA, dB); else wgmma_n192_ss_tb(acc2, dA, dB, 1);
                wgmma_n192_ss_tb(acc2, dA + 2, dB + 128, 1);
                wg_commit();
                if (it > 0) {
                    wg_wait<1>();
                    if (it <= 15) release_stage(bar + (B_E2 + (it - 1) % 5) * 8, peer, lane);
                }
                if (it < 12) {
                    const int m = it / 2, part = it % 2;
                    const int hs = hs0 + 2 * m, which = hs >> 5;
                    const uint32_t* a = pk + 10 * m;
                    uint8_t* pe = img + (2 * m) * IMG_BYTES;
                    uint8_t* po = pe + IMG_BYTES;
                    if (part == 0) {
                        const uint32_t padv = which == 0 ? 0x3F803F80u : which == 1 ? 0xBFFF4440u : 0x00003F80u;
                        const uint32_t p0 = ((c & 1) || (which == 1 && !emu0)) ? 0u : padv;
                        const uint32_t p1 = ((c & 1) || (which == 1 && !emu1)) ? 0u : padv;
                        *(uint32_t*)(pe) = a[0];
                        *(uint32_t*)(pe + 128) = a[2];
                        *(uint32_t*)(pe + 256) = low ? a[4] : p0;
                        *(uint32_t*)(pe + 384) = a[1];
                        *(uint32_t*)(pe + 512) = a[3];
                        *(uint32_t*)(pe + 640) = low ? a[5] : p1;
                        *(uint32_t*)(po + 256) = low ? p0 : a[4];
                        *(uint32_t*)(po + 640) = low ? p1 : a[5];
                    } else {
                        *(uint32_t*)(po) = a[6];
                        *(uint32_t*)(po + 128) = a[8];
                        *(uint32_t*)(po + 384) = a[7];
                        *(uint32_t*)(po + 512) = a[9];
                        if (which < 2) {
                            const uint32_t u0 = bf2_fma(a[4], a[4], 0u), u1 = bf2_fma(a[5], a[5], 0u);
                            const uint32_t pe0 = bf2_fma(a[0], a[0], bf2_fma(a[2], a[2], low ? u0 : 0u));
                            const uint32_t pe1 = bf2_fma(a[1], a[1], bf2_fma(a[3], a[3], low ? u1 : 0u));
                            const uint32_t po0 = bf2_fma(a[6], a[6], bf2_fma(a[8], a[8], low ? 0u : u0));
                            const uint32_t po1 = bf2_fma(a[7], a[7], bf2_fma(a[9], a[9], low ? 0u : u1));
                            const float e0 = bf_lo(pe0) + bf_hi(pe0), e1 = bf_lo(pe1) + bf_hi(pe1);
                            const float o0 = bf_lo(po0) + bf_hi(po0), o1 = bf_lo(po1) + bf_hi(po1);
                            const bool b0 = c & 1, b1_ = c & 2;
                            const float x0 = (b0 ? e1 : e0) + __shfl_xor_sync(~0u, b0 ? e0 : e1, 1);
                            const float x1 = (b0 ? o1 : o0) + __shfl_xor_sync(~0u, b0 ? o0 : o1, 1);
                            float y = (b1_ ? x1 : x0) + __shfl_xor_sync(~0u, b1_ ? x0 : x1, 2);
                            if (which == 1 && (b0 ? emu1 : emu0)) y *= 0.25f;
                            g_nrm[(hs + (c >> 1)) * SEQ + row0 + (c & 1) * 8] = y;
                        }
                    }
                    if (it == 11) { __syncwarp(); if (lane == 0) mbar_arrive(bar + B_ST * 8); }
                }
            }
            wg_wait<0>();
            fence_regs(acc2);
            if (threadIdx.x == 256) TL(1, 2);
            mbar_wait(bar + B_AUX2 * 8, 0);
            const uint32_t* bias = reinterpret_cast<const uint32_t*>(smem + SM_BIAS) + c;
            const int mrow = w4 * 16 + (lane & 15);
            const uint32_t st_row = sAw + mrow * 128;
#pragma unroll
            for (int j = 0; j < 24; j += 2) {
                const uint32_t bA = bias[j * 4], bB = bias[j * 4 + 4];
                const float2 cA = cs[(30 + j) * 4], cB = cs[(31 + j) * 4];
                const float* a = acc2 + j * 4;
                const uint32_t r00 = pack_bf16(gelu_tanh(fmaf(a[0], r20, fmaf(e20, cA.x, bf_lo(bA)))), gelu_tanh(fmaf(a[1], r20, fmaf(e20, cA.y, bf_hi(bA)))));
                const uint32_t r10 = pack_bf16(gelu_tanh(fmaf(a[2], r21, fmaf(e21, cA.x, bf_lo(bA)))), gelu_tanh(fmaf(a[3], r21, fmaf(e21, cA.y, bf_hi(bA)))));
                const uint32_t r01 = pack_bf16(gelu_tanh(fmaf(a[4], r20, fmaf(e20, cB.x, bf_lo(bB)))), gelu_tanh(fmaf(a[5], r20, fmaf(e20, cB.y, bf_hi(bB)))));
                const uint32_t r11 = pack_bf16(gelu_tanh(fmaf(a[6], r21, fmaf(e21, cB.x, bf_lo(bB)))), gelu_tanh(fmaf(a[7], r21, fmaf(e21, cB.y, bf_hi(bB)))));
                const int chunk = (j & 7) + (lane >> 4);
                stmatrix_x4(st_row + (j >> 3) * 16384 + ((chunk ^ (mrow & 7)) << 4), r00, r10, r01, r11);
            }
            fence_proxy_async();
            asm volatile("bar.sync %0, 128;" ::"r"(wgi + 3) : "memory");
            if (w4 == 0 && lane == 0) {
#pragma unroll
                for (int b = 0; b < 3; b++) tma_store(&tm.h, sAw + b * 16384, cg * 192 + b * 64, rb * 128 + wi * 64);
                bulk_commit();
                bulk_wait_read();
            }
            __syncwarp();
            reg_dealloc<128>();
        }
        __syncthreads();
        if (threadIdx.x == 0) TL(1, 3);
    }

    {
        const uint32_t epoch = *reinterpret_cast<volatile uint32_t*>(smem + SM_EPOCH);
        const int h = blockIdx.x >> 2, qb = blockIdx.x & 3;
        const uint32_t sK = sb, sV = sb + IMG_BYTES, barKV = bar + B_KV * 8;
        if (threadIdx.x == 0) TL(2, 0);
        if (threadIdx.x < 192) *reinterpret_cast<uint4*>(smem + SM_ZERO + threadIdx.x * 16) = make_uint4(0, 0, 0, 0);
        fence_proxy_async();
        if (warp == 0) {
            if (elect_one()) {
                cnt_wait(CNT_QKV + h / 12, (epoch + 1) * 16);
                cnt_wait(CNT_QKV + (32 + h) / 12, (epoch + 1) * 16);
                cnt_wait(CNT_QKV + (64 + h) / 12, (epoch + 1) * 16);
                const uint8_t* gK = g_img + (size_t)(32 + h) * IMG_BYTES;
                const uint8_t* gV = g_img + (size_t)(64 + h) * IMG_BYTES;
                const uint8_t* gQ = g_img + (size_t)h * IMG_BYTES + qb * 64 * 384;
                mbar_expect_tx(barKV + 128, 6144);
                bulk_load(sK, gK, 6144, barKV + 128);
                for (int p = 0; p < 2; p++) {
                    mbar_expect_tx(bar + (B_Q + p) * 8, 12288);
                    bulk_load(sb + SM_Q + p * 12288, gQ + p * 12288, 12288, bar + (B_Q + p) * 8);
                }
                for (int i = 0; i < 16; i++) {
                    mbar_expect_tx(barKV + i * 8, i < 15 ? 12288 : 6144);
                    bulk_load(sV + i * 6144, gV + i * 6144, 6144, barKV + i * 8);
                    if (i < 15) bulk_load(sK + (i + 1) * 6144, gK + (i + 1) * 6144, 6144, barKV + i * 8);
                }
            }
            __syncwarp();
        }
        __syncthreads();
        if (threadIdx.x == 0) TL(2, 1);
        float* red = reinterpret_cast<float*>(smem + SM_RED);
        float kmax = 0.f, qmax = __ldcg(g_nrm + h * SEQ + qb * 512 + threadIdx.x);
#pragma unroll
        for (int i = 0; i < 4; i++) kmax = fmaxf(kmax, __ldcg(g_nrm + (32 + h) * SEQ + i * 512 + threadIdx.x));
#pragma unroll
        for (int o = 16; o; o >>= 1) {
            kmax = fmaxf(kmax, __shfl_xor_sync(~0u, kmax, o));
            qmax = fmaxf(qmax, __shfl_xor_sync(~0u, qmax, o));
        }
        if (lane == 0) { red[warp] = kmax; red[16 + warp] = qmax; }
        __syncthreads();
        kmax = red[lane & 15]; qmax = red[16 + (lane & 15)];
#pragma unroll
        for (int o = 8; o; o >>= 1) {
            kmax = fmaxf(kmax, __shfl_xor_sync(~0u, kmax, o));
            qmax = fmaxf(qmax, __shfl_xor_sync(~0u, qmax, o));
        }
        const bool safe = __all_sync(~0u, kmax * qmax * 1.1f <= SAFE_BOUND * SAFE_BOUND);
        const uint64_t dK0 = make_desc(sK, 128, 384, 0), dV0 = make_desc(sV, 384, 128, 0);
        auto publish_h = [&]() {
            if (warp == 8 || warp == 12) {
                if (lane == 0) { bulk_wait_all(); cnt_signal(CNT_H + rb); }
                __syncwarp();
            }
        };
        if (!safe) {
#pragma unroll 1
            for (int pass = 0; pass < 2; pass++) {
                const uint32_t sQ = sb + SM_Q + pass * 12288 + wgi * 3072;
                mbar_wait(bar + (B_Q + pass) * 8, 0);
                if (lane < 16) *reinterpret_cast<uint32_t*>(smem + (sQ - sb) + (w4 * 2 + (lane >> 3)) * 384 + 256 + (lane & 7) * 16 + ((h & 1) ? 0 : 8)) = 0u;
                fence_proxy_async();
                asm volatile("bar.sync %0, 128;" ::"r"(wgi + 3) : "memory");
                attn_rows_maxshift(sK, barKV, make_desc(sQ, 128, 384, 0), make_desc(sQ + 256, sb + SM_ZERO - (sQ + 256), 384, 0), h,
                                   qb * 512 + pass * 256 + wgi * 64 + w4 * 16);
                if (pass == 0) publish_h();
            }
        } else {
            const ExpConst kc = make_exp_const();
#pragma unroll 1
            for (int pass = 0; pass < 2; pass++) {
                const int rbase = qb * 512 + pass * 256 + wgi * 64 + w4 * 16;
                const uint32_t sQ = sb + SM_Q + pass * 12288 + wgi * 3072;
                const uint64_t dQ = make_desc(sQ, 128, 384, 0), dQ2 = make_desc(sQ + 256, sb + SM_ZERO - (sQ + 256), 384, 0);
                float o[12], sa[32], sc[32];
                uint32_t p[16];
#pragma unroll
                for (int i = 0; i < 12; i++) o[i] = 0.f;
                fence_regs(o);
                mbar_wait(bar + (B_Q + pass) * 8, 0);
                mbar_wait(barKV + 128, 0);
                qk_tile(sa, dQ, dQ2, dK0);
                wg_wait<0>();
                fence_regs(sa);
                uint64_t dK = dK0, dV = dV0;
                uint32_t bj = barKV;
#pragma unroll 1
                for (int j = 0; j < 16; j++) {
                    mbar_wait(bj, 0);
                    qk_tile(sc, dQ, dQ2, dK + 192);
                    wg_wait<1>();
                    exp_tile<0>(sa, p, kc);
                    pv_tile(o, p, dV);
                    wg_wait<1>();
                    fence_regs(sc);
                    mbar_wait(bj, 0);
                    qk_tile(sa, dQ, dQ2, dK + 384);
                    wg_wait<1>();
                    exp_tile<8>(sc, p, kc);
                    pv_tile(o, p, dV + 192);
                    wg_wait<1>();
                    fence_regs(sa);
                    dK += 384; dV += 384; bj += 8;
                }
                wg_wait<0>();
                fence_regs(o);
                store_o(o, h, rbase, lane);
                if (threadIdx.x == 0) TL(2, 2 + pass);
                if (pass == 0) publish_h();
            }
        }
        __syncthreads();
        if (threadIdx.x == 64) cnt_signal(CNT_O + qb);
        cluster_arrive_relaxed();
    }

    {
        const uint32_t epoch = *reinterpret_cast<volatile uint32_t*>(smem + SM_EPOCH);
        const int ct = cl & 3, rt = (cl >> 2) * 2 + rank;
        if (threadIdx.x == 0) TL(3, 0);
        const int orow = threadIdx.x >> 3, oseg = threadIdx.x & 7;
        const size_t ooff = (size_t)(rt * 64 + orow) * DM + ct * 160 + oseg * 20;
        uint2 xr[5], br[5];
#pragma unroll
        for (int i = 0; i < 5; i++) {
            xr[i] = __ldg(reinterpret_cast<const uint2*>(x + ooff) + i);
            br[i] = __ldg(reinterpret_cast<const uint2*>(b2 + ct * 160 + oseg * 20) + i);
        }
        cluster_wait();
        float* stg = reinterpret_cast<float*>(smem);
        if (warp == 4) {
            if (elect_one()) { prefetch_map(&tm.h); prefetch_map(&tm.o); prefetch_map(&tm.w2); prefetch_map(&tm.wo); cnt_wait(CNT_H + (rt >> 1), (epoch + 1) * 16); }
            __syncwarp();
#pragma unroll 1
            for (int kb = 0; kb < 34; kb++) {
                const int s = kb & 7;
                if (kb >= 8) mbar_wait(bar + (B_E3 + s) * 8, ((kb >> 3) - 1) & 1);
                if (elect_one()) {
                    if (kb == 24) { cnt_wait(CNT_O + (rt >> 3), (epoch + 1) * 32); TL(3, 1); }
                    const uint32_t dst = sb + s * G2_STAGE, fb = bar + (B_F3 + s) * 8;
                    const CUtensorMap* mA = kb < 24 ? &tm.h : &tm.o;
                    const CUtensorMap* mB = kb < 24 ? &tm.w2 : &tm.wo;
                    const int k0 = (kb < 24 ? kb : kb - 24) * 64;
                    mbar_expect_tx(fb, G2_STAGE);
                    tma_load(dst, mA, k0, rt * 64, fb);
                    const int first = ((kb & 1) == (int)rank) ? 0 : 3, last = ((kb & 1) == (int)rank) ? 3 : 5;
                    for (int b = first; b < last; b++) tma_load_mc(dst + 8192 + b * 4096, mB, ct * 160 + b * 32, k0, fb, 3);
                }
                __syncwarp();
            }
        } else if (wgi == 0) {
            float acc[80];
#pragma unroll 1
            for (int kb = 0; kb < 34; kb++) {
                const int s = kb & 7;
                mbar_wait(bar + (B_F3 + s) * 8, (kb >> 3) & 1);
                wg_fence();
                const uint64_t dA = make_desc(sb + s * G2_STAGE, 16, 1024, 1);
                const uint64_t dB = make_desc(sb + s * G2_STAGE + 8192, 4096, 512, 2);
#pragma unroll
                for (int kk = 0; kk < 4; kk++) wgmma_n160_ss_tb(acc, dA + kk * 2, dB + kk * 64, (kb | kk) != 0);
                wg_commit();
                if (kb > 0) {
                    wg_wait<1>();
                    if (kb <= 26) release_stage(bar + (B_E3 + ((kb - 1) & 7)) * 8, peer, lane);
                }
            }
            wg_wait<0>();
            fence_regs(acc);
            if (threadIdx.x == 0) TL(3, 2);
            const int r = w4 * 16 + g;
#pragma unroll
            for (int j = 0; j < 20; j++) {
                *reinterpret_cast<float2*>(stg + r * 168 + j * 8 + 2 * c) = make_float2(acc[4 * j], acc[4 * j + 1]);
                *reinterpret_cast<float2*>(stg + (r + 8) * 168 + j * 8 + 2 * c) = make_float2(acc[4 * j + 2], acc[4 * j + 3]);
            }
        }
        __syncthreads();
        const float4* sp = reinterpret_cast<const float4*>(stg + orow * 168 + oseg * 20);
#pragma unroll
        for (int i = 0; i < 5; i++) {
            const float4 a = sp[i];
            uint2 w;
            w.x = pack_bf16(a.x + bf_lo(br[i].x) + bf_lo(xr[i].x), a.y + bf_hi(br[i].x) + bf_hi(xr[i].x));
            w.y = pack_bf16(a.z + bf_lo(br[i].y) + bf_lo(xr[i].y), a.w + bf_hi(br[i].y) + bf_hi(xr[i].y));
            reinterpret_cast<uint2*>(out + ooff)[i] = w;
        }
        if (blockIdx.x == 0 && threadIdx.x == 0) g_epoch = epoch + 1;
        if (threadIdx.x == 0) TL(3, 3);
    }
    cluster_arrive_relaxed();
    cluster_wait();
}

typedef CUresult (*EncodeTiledFn)(CUtensorMap*, CUtensorMapDataType, cuuint32_t, void*, const cuuint64_t*,
                                  const cuuint64_t*, const cuuint32_t*, const cuuint32_t*, CUtensorMapInterleave,
                                  CUtensorMapSwizzle, CUtensorMapL2promotion, CUtensorMapFloatOOBfill);

CUtensorMap make_map(EncodeTiledFn enc, const void* ptr, int rows, int cols, int box_rows, int box_cols,
                     CUtensorMapSwizzle swz) {
    CUtensorMap m;
    cuuint64_t gd[2] = {(cuuint64_t)cols, (cuuint64_t)rows};
    cuuint64_t gs[1] = {(cuuint64_t)cols * 2};
    cuuint32_t bd[2] = {(cuuint32_t)box_cols, (cuuint32_t)box_rows};
    cuuint32_t es[2] = {1, 1};
    enc(&m, CU_TENSOR_MAP_DATA_TYPE_BFLOAT16, 2, const_cast<void*>(ptr), gd, gs, bd, es, CU_TENSOR_MAP_INTERLEAVE_NONE,
        swz, CU_TENSOR_MAP_L2_PROMOTION_L2_128B, CU_TENSOR_MAP_FLOAT_OOB_FILL_NONE);
    return m;
}

}

extern "C" void kernel_launch(void* const* d_in, const int* in_sizes, int n_in, void* d_out, int out_size) {
    (void)in_sizes; (void)n_in; (void)out_size;
    const __nv_bfloat16* x = (const __nv_bfloat16*)d_in[0];
    const __nv_bfloat16* wqkv = (const __nv_bfloat16*)d_in[1];
    const __nv_bfloat16* wo = (const __nv_bfloat16*)d_in[2];
    const __nv_bfloat16* w1 = (const __nv_bfloat16*)d_in[4];
    const __nv_bfloat16* b1 = (const __nv_bfloat16*)d_in[5];
    const __nv_bfloat16* w2 = (const __nv_bfloat16*)d_in[6];
    const __nv_bfloat16* b2 = (const __nv_bfloat16*)d_in[7];
    __nv_bfloat16* out = (__nv_bfloat16*)d_out;

    static EncodeTiledFn enc = nullptr;
    static void *p_h, *p_o;
    if (!enc) {
        cudaDriverEntryPointQueryResult qr;
        cudaGetDriverEntryPoint("cuTensorMapEncodeTiled", (void**)&enc, cudaEnableDefault, &qr);
        cudaGetSymbolAddress(&p_h, g_h);
        cudaGetSymbolAddress(&p_o, g_o);
        cudaFuncSetAttribute(k_fused, cudaFuncAttributeMaxDynamicSharedMemorySize, SM_TOTAL);
    }
    Maps tm;
    tm.x = make_map(enc, x, SEQ, DM, 128, 64, CU_TENSOR_MAP_SWIZZLE_128B);
    tm.wqkv = make_map(enc, wqkv, DM, 3 * DM, 32, 64, CU_TENSOR_MAP_SWIZZLE_128B);
    tm.w1 = make_map(enc, w1, DM, FF, 32, 64, CU_TENSOR_MAP_SWIZZLE_128B);
    tm.h = make_map(enc, p_h, SEQ, FF, 64, 64, CU_TENSOR_MAP_SWIZZLE_128B);
    tm.o = make_map(enc, p_o, SEQ, DM, 64, 64, CU_TENSOR_MAP_SWIZZLE_128B);
    tm.wo = make_map(enc, wo, DM, DM, 64, 32, CU_TENSOR_MAP_SWIZZLE_64B);
    tm.w2 = make_map(enc, w2, FF, DM, 64, 32, CU_TENSOR_MAP_SWIZZLE_64B);
    k_fused<<<128, 512, SM_TOTAL, cudaStreamPerThread>>>(tm, x, (const uint8_t*)wqkv, (const uint8_t*)w1, (const uint8_t*)w2,
                                                         (const uint8_t*)wo, b1, b2, out);
}
```

```cpp
#include <cuda_runtime.h>
#include <cuda_bf16.h>
#include <cuda.h>
#include <stdint.h>

namespace {

constexpr int SEQ = 2048, DM = 640, FF = 1536;
constexpr float LN_EPS = 1e-5f;

constexpr int IMG_BYTES = 256 * 384;
constexpr uint32_t EMU_MASK = 0xD5D5u;
constexpr float SAFE_BOUND = 80.0f;
constexpr float QSCALE = 0.22360679774997896f * 1.4426950408889634f;

__device__ float4 g_stat[SEQ];
__device__ float2 g_csp[16 * 1728];
__device__ __align__(1024) uint8_t g_img[96 * IMG_BYTES + 1024];
__device__ float g_nrm[64 * SEQ];
__device__ __align__(1024) __nv_bfloat16 g_h[SEQ * FF];
__device__ __align__(1024) __nv_bfloat16 g_o[SEQ * DM];
constexpr int CNT_ST = 0, CNT_QKV = 16, CNT_H = 24, CNT_O = 40, CNT_CS = 44, CNT_CS2 = 52;
__device__ uint32_t g_cnt[60 * 32];
__device__ uint32_t g_epoch;

#define TL(kern, slot) do { } while (0)
#define IT(row, i) do { } while (0)

__device__ __forceinline__ uint32_t smem_u32(const void* p) { return (uint32_t)__cvta_generic_to_shared(p); }
__device__ __forceinline__ void mbar_init(uint32_t bar, int cnt) {
    asm volatile("mbarrier.init.shared::cta.b64 [%0], %1;" ::"r"(bar), "r"(cnt));
}
__device__ __forceinline__ void mbar_expect_tx(uint32_t bar, uint32_t bytes) {
    asm volatile("mbarrier.arrive.expect_tx.shared::cta.b64 _, [%0], %1;" ::"r"(bar), "r"(bytes) : "memory");
}
__device__ __forceinline__ void mbar_wait(uint32_t bar, uint32_t parity) {
    asm volatile("{\n.reg .pred p;\n.reg .u32 n;\nmov.u32 n, 0;\n"
                 "WAIT_LOOP:\nmbarrier.try_wait.parity.shared::cta.b64 p, [%0], %1;\n@p bra WAIT_DONE;\n"
                 "add.u32 n, n, 1;\nsetp.lt.u32 p, n, 4194304;\n@p bra WAIT_LOOP;\nWAIT_DONE:\n}"
                 ::"r"(bar), "r"(parity) : "memory");
}
__device__ __forceinline__ void mbar_arrive(uint32_t bar) {
    asm volatile("mbarrier.arrive.shared::cta.b64 _, [%0];" ::"r"(bar) : "memory");
}
__device__ __forceinline__ void mbar_arrive_cluster(uint32_t bar, uint32_t cta) {
    asm volatile("{\n.reg .b32 ra;\nmapa.shared::cluster.u32 ra, %0, %1;\n"
                 "mbarrier.arrive.shared::cluster.b64 _, [ra];\n}" ::"r"(bar), "r"(cta) : "memory");
}
__device__ __forceinline__ void fence_barrier_init() { asm volatile("fence.mbarrier_init.release.cluster;" ::: "memory"); }
__device__ __forceinline__ void fence_proxy_async() { asm volatile("fence.proxy.async.shared::cta;" ::: "memory"); }
__device__ __forceinline__ void cluster_sync() {
    asm volatile("barrier.cluster.arrive.release.aligned;\nbarrier.cluster.wait.acquire.aligned;" ::: "memory");
}
__device__ __forceinline__ bool elect_one() {
    uint32_t pred;
    asm volatile("{\n.reg .pred p;\nelect.sync _|p, 0xFFFFFFFF;\nselp.b32 %0, 1, 0, p;\n}" : "=r"(pred));
    return pred != 0;
}
__device__ __forceinline__ void pdl_launch() { asm volatile("griddepcontrol.launch_dependents;" ::: "memory"); }
__device__ __forceinline__ void pdl_wait() { asm volatile("griddepcontrol.wait;" ::: "memory"); }
__device__ __forceinline__ void prefetch_map(const CUtensorMap* m) {
    asm volatile("prefetch.tensormap [%0];" ::"l"(m) : "memory");
}
__device__ __forceinline__ void tma_load(uint32_t dst, const CUtensorMap* m, int c0, int c1, uint32_t bar) {
    asm volatile("cp.async.bulk.tensor.2d.shared::cluster.global.mbarrier::complete_tx::bytes [%0], [%1, {%3, %4}], [%2];"
                 ::"r"(dst), "l"(m), "r"(bar), "r"(c0), "r"(c1) : "memory");
}
__device__ __forceinline__ void tma_load_mc(uint32_t dst, const CUtensorMap* m, int c0, int c1, uint32_t bar, uint16_t mask) {
    asm volatile("cp.async.bulk.tensor.2d.shared::cluster.global.mbarrier::complete_tx::bytes.multicast::cluster"
                 " [%0], [%1, {%3, %4}], [%2], %5;"
                 ::"r"(dst), "l"(m), "r"(bar), "r"(c0), "r"(c1), "h"(mask) : "memory");
}
__device__ __forceinline__ void tma_store(const CUtensorMap* m, uint32_t src, int c0, int c1) {
    asm volatile("cp.async.bulk.tensor.2d.global.shared::cta.bulk_group [%0, {%2, %3}], [%1];"
                 ::"l"(m), "r"(src), "r"(c0), "r"(c1) : "memory");
}
__device__ __forceinline__ void bulk_commit() { asm volatile("cp.async.bulk.commit_group;" ::: "memory"); }
__device__ __forceinline__ void bulk_wait_all() { asm volatile("cp.async.bulk.wait_group 0;" ::: "memory"); }
__device__ __forceinline__ void bulk_load(uint32_t dst, const void* src, uint32_t bytes, uint32_t bar) {
    asm volatile("cp.async.bulk.shared::cluster.global.mbarrier::complete_tx::bytes [%0], [%1], %2, [%3];"
                 ::"r"(dst), "l"(src), "r"(bytes), "r"(bar) : "memory");
}
__device__ __forceinline__ void prefetch_l2(const void* p, uint32_t bytes) {
    asm volatile("cp.async.bulk.prefetch.L2.global [%0], %1;" ::"l"(p), "r"(bytes) : "memory");
}
__device__ __forceinline__ void tma_prefetch_l2(const CUtensorMap* m, int c0, int c1) {
    asm volatile("cp.async.bulk.prefetch.tensor.2d.L2.global.tile [%0, {%1, %2}];" ::"l"(m), "r"(c0), "r"(c1) : "memory");
}
__device__ __forceinline__ void wg_fence() { asm volatile("wgmma.fence.sync.aligned;" ::: "memory"); }
__device__ __forceinline__ void wg_commit() { asm volatile("wgmma.commit_group.sync.aligned;" ::: "memory"); }
template <int N> __device__ __forceinline__ void wg_wait() {
    asm volatile("wgmma.wait_group.sync.aligned %0;" ::"n"(N) : "memory");
}
template <int N> __device__ __forceinline__ void reg_alloc() { asm volatile("setmaxnreg.inc.sync.aligned.u32 %0;" ::"n"(N)); }
template <int N> __device__ __forceinline__ void reg_dealloc() { asm volatile("setmaxnreg.dec.sync.aligned.u32 %0;" ::"n"(N)); }
template <int N> __device__ __forceinline__ void fence_regs(float (&d)[N]) {
#pragma unroll
    for (int i = 0; i < N; i++) asm volatile("" : "+f"(d[i])::"memory");
}
__device__ __forceinline__ uint64_t make_desc(uint32_t addr, uint32_t lbo, uint32_t sbo, uint32_t swz) {
    return (uint64_t)((addr & 0x3FFFF) >> 4) | ((uint64_t)(lbo >> 4) << 16) | ((uint64_t)(sbo >> 4) << 32) |
           ((uint64_t)swz << 62);
}
__device__ __forceinline__ uint32_t pack_bf16(float lo, float hi) {
    uint32_t r;
    asm("cvt.rn.bf16x2.f32 %0, %1, %2;" : "=r"(r) : "f"(hi), "f"(lo));
    return r;
}
__device__ __forceinline__ float ex2(float x) {
    float r;
    asm("ex2.approx.ftz.f32 %0, %1;" : "=f"(r) : "f"(x));
    return r;
}
__device__ __forceinline__ float bf_lo(uint32_t v) { return __uint_as_float(v << 16); }
__device__ __forceinline__ float bf_hi(uint32_t v) { return __uint_as_float(v & 0xFFFF0000u); }
__device__ __forceinline__ void stmatrix_x4(uint32_t addr, uint32_t r0, uint32_t r1, uint32_t r2, uint32_t r3) {
    asm volatile("stmatrix.sync.aligned.m8n8.x4.shared.b16 [%0], {%1, %2, %3, %4};"
                 ::"r"(addr), "r"(r0), "r"(r1), "r"(r2), "r"(r3) : "memory");
}

__device__ __forceinline__ void wgmma_n120_ss_tb(float (&d)[60], uint64_t descA, uint64_t descB, int scaleD) {
    asm volatile("{\n.reg .pred p;\nsetp.ne.b32 p, %62, 0;\n"
        "wgmma.mma_async.sync.aligned.m64n120k16.f32.bf16.bf16 {"
        "%0, %1, %2, %3, %4, %5, %6, %7, %8, %9, %10, %11, %12, %13, %14, %15, "
        "%16, %17, %18, %19, %20, %21, %22, %23, %24, %25, %26, %27, %28, %29, %30, %31, "
        "%32, %33, %34, %35, %36, %37, %38, %39, %40, %41, %42, %43, %44, %45, %46, %47, "
        "%48, %49, %50, %51, %52, %53, %54, %55, %56, %57, %58, %59}, "
        "%60, %61, p, 1, 1, 0, 1;\n}\n"
        : "+f"(d[0]), "+f"(d[1]), "+f"(d[2]), "+f"(d[3]), "+f"(d[4]), "+f"(d[5]), "+f"(d[6]), "+f"(d[7]),
          "+f"(d[8]), "+f"(d[9]), "+f"(d[10]), "+f"(d[11]), "+f"(d[12]), "+f"(d[13]), "+f"(d[14]), "+f"(d[15]),
          "+f"(d[16]), "+f"(d[17]), "+f"(d[18]), "+f"(d[19]), "+f"(d[20]), "+f"(d[21]), "+f"(d[22]), "+f"(d[23]),
          "+f"(d[24]), "+f"(d[25]), "+f"(d[26]), "+f"(d[27]), "+f"(d[28]), "+f"(d[29]), "+f"(d[30]), "+f"(d[31]),
          "+f"(d[32]), "+f"(d[33]), "+f"(d[34]), "+f"(d[35]), "+f"(d[36]), "+f"(d[37]), "+f"(d[38]), "+f"(d[39]),
          "+f"(d[40]), "+f"(d[41]), "+f"(d[42]), "+f"(d[43]), "+f"(d[44]), "+f"(d[45]), "+f"(d[46]), "+f"(d[47]),
          "+f"(d[48]), "+f"(d[49]), "+f"(d[50]), "+f"(d[51]), "+f"(d[52]), "+f"(d[53]), "+f"(d[54]), "+f"(d[55]),
          "+f"(d[56]), "+f"(d[57]), "+f"(d[58]), "+f"(d[59])
        : "l"(descA), "l"(descB), "r"(scaleD));
}

__device__ __forceinline__ void wgmma_n192_ss_tb(float (&d)[96], uint64_t descA, uint64_t descB, int scaleD) {
    asm volatile("{\n.reg .pred p;\nsetp.ne.b32 p, %98, 0;\n"
        "wgmma.mma_async.sync.aligned.m64n192k16.f32.bf16.bf16 {"
        "%0, %1, %2, %3, %4, %5, %6, %7, %8, %9, %10, %11, %12, %13, %14, %15, "
        "%16, %17, %18, %19, %20, %21, %22, %23, %24, %25, %26, %27, %28, %29, %30, %31, "
        "%32, %33, %34, %35, %36, %37, %38, %39, %40, %41, %42, %43, %44, %45, %46, %47, "
        "%48, %49, %50, %51, %52, %53, %54, %55, %56, %57, %58, %59, %60, %61, %62, %63, "
        "%64, %65, %66, %67, %68, %69, %70, %71, %72, %73, %74, %75, %76, %77, %78, %79, "
        "%80, %81, %82, %83, %84, %85, %86, %87, %88, %89, %90, %91, %92, %93, %94, %95}, "
        "%96, %97, p, 1, 1, 0, 1;\n}\n"
        : "+f"(d[0]), "+f"(d[1]), "+f"(d[2]), "+f"(d[3]), "+f"(d[4]), "+f"(d[5]), "+f"(d[6]), "+f"(d[7]),
          "+f"(d[8]), "+f"(d[9]), "+f"(d[10]), "+f"(d[11]), "+f"(d[12]), "+f"(d[13]), "+f"(d[14]), "+f"(d[15]),
          "+f"(d[16]), "+f"(d[17]), "+f"(d[18]), "+f"(d[19]), "+f"(d[20]), "+f"(d[21]), "+f"(d[22]), "+f"(d[23]),
          "+f"(d[24]), "+f"(d[25]), "+f"(d[26]), "+f"(d[27]), "+f"(d[28]), "+f"(d[29]), "+f"(d[30]), "+f"(d[31]),
          "+f"(d[32]), "+f"(d[33]), "+f"(d[34]), "+f"(d[35]), "+f"(d[36]), "+f"(d[37]), "+f"(d[38]), "+f"(d[39]),
          "+f"(d[40]), "+f"(d[41]), "+f"(d[42]), "+f"(d[43]), "+f"(d[44]), "+f"(d[45]), "+f"(d[46]), "+f"(d[47]),
          "+f"(d[48]), "+f"(d[49]), "+f"(d[50]), "+f"(d[51]), "+f"(d[52]), "+f"(d[53]), "+f"(d[54]), "+f"(d[55]),
          "+f"(d[56]), "+f"(d[57]), "+f"(d[58]), "+f"(d[59]), "+f"(d[60]), "+f"(d[61]), "+f"(d[62]), "+f"(d[63]),
          "+f"(d[64]), "+f"(d[65]), "+f"(d[66]), "+f"(d[67]), "+f"(d[68]), "+f"(d[69]), "+f"(d[70]), "+f"(d[71]),
          "+f"(d[72]), "+f"(d[73]), "+f"(d[74]), "+f"(d[75]), "+f"(d[76]), "+f"(d[77]), "+f"(d[78]), "+f"(d[79]),
          "+f"(d[80]), "+f"(d[81]), "+f"(d[82]), "+f"(d[83]), "+f"(d[84]), "+f"(d[85]), "+f"(d[86]), "+f"(d[87]),
          "+f"(d[88]), "+f"(d[89]), "+f"(d[90]), "+f"(d[91]), "+f"(d[92]), "+f"(d[93]), "+f"(d[94]), "+f"(d[95])
        : "l"(descA), "l"(descB), "r"(scaleD));
}

__device__ __forceinline__ void wgmma_n192_ss_tb_z(float (&d)[96], uint64_t descA, uint64_t descB) {
    asm volatile("{\n.reg .pred p;\nsetp.ne.b32 p, 0, 0;\n"
        "wgmma.mma_async.sync.aligned.m64n192k16.f32.bf16.bf16 {"
        "%0, %1, %2, %3, %4, %5, %6, %7, %8, %9, %10, %11, %12, %13, %14, %15, "
        "%16, %17, %18, %19, %20, %21, %22, %23, %24, %25, %26, %27, %28, %29, %30, %31, "
        "%32, %33, %34, %35, %36, %37, %38, %39, %40, %41, %42, %43, %44, %45, %46, %47, "
        "%48, %49, %50, %51, %52, %53, %54, %55, %56, %57, %58, %59, %60, %61, %62, %63, "
        "%64, %65, %66, %67, %68, %69, %70, %71, %72, %73, %74, %75, %76, %77, %78, %79, "
        "%80, %81, %82, %83, %84, %85, %86, %87, %88, %89, %90, %91, %92, %93, %94, %95}, "
        "%96, %97, p, 1, 1, 0, 1;\n}\n"
        : "=f"(d[0]), "=f"(d[1]), "=f"(d[2]), "=f"(d[3]), "=f"(d[4]), "=f"(d[5]), "=f"(d[6]), "=f"(d[7]),
          "=f"(d[8]), "=f"(d[9]), "=f"(d[10]), "=f"(d[11]), "=f"(d[12]), "=f"(d[13]), "=f"(d[14]), "=f"(d[15]),
          "=f"(d[16]), "=f"(d[17]), "=f"(d[18]), "=f"(d[19]), "=f"(d[20]), "=f"(d[21]), "=f"(d[22]), "=f"(d[23]),
          "=f"(d[24]), "=f"(d[25]), "=f"(d[26]), "=f"(d[27]), "=f"(d[28]), "=f"(d[29]), "=f"(d[30]), "=f"(d[31]),
          "=f"(d[32]), "=f"(d[33]), "=f"(d[34]), "=f"(d[35]), "=f"(d[36]), "=f"(d[37]), "=f"(d[38]), "=f"(d[39]),
          "=f"(d[40]), "=f"(d[41]), "=f"(d[42]), "=f"(d[43]), "=f"(d[44]), "=f"(d[45]), "=f"(d[46]), "=f"(d[47]),
          "=f"(d[48]), "=f"(d[49]), "=f"(d[50]), "=f"(d[51]), "=f"(d[52]), "=f"(d[53]), "=f"(d[54]), "=f"(d[55]),
          "=f"(d[56]), "=f"(d[57]), "=f"(d[58]), "=f"(d[59]), "=f"(d[60]), "=f"(d[61]), "=f"(d[62]), "=f"(d[63]),
          "=f"(d[64]), "=f"(d[65]), "=f"(d[66]), "=f"(d[67]), "=f"(d[68]), "=f"(d[69]), "=f"(d[70]), "=f"(d[71]),
          "=f"(d[72]), "=f"(d[73]), "=f"(d[74]), "=f"(d[75]), "=f"(d[76]), "=f"(d[77]), "=f"(d[78]), "=f"(d[79]),
          "=f"(d[80]), "=f"(d[81]), "=f"(d[82]), "=f"(d[83]), "=f"(d[84]), "=f"(d[85]), "=f"(d[86]), "=f"(d[87]),
          "=f"(d[88]), "=f"(d[89]), "=f"(d[90]), "=f"(d[91]), "=f"(d[92]), "=f"(d[93]), "=f"(d[94]), "=f"(d[95])
        : "l"(descA), "l"(descB));
}

__device__ __forceinline__ void wgmma_n160_ss_tb(float (&d)[80], uint64_t descA, uint64_t descB, int scaleD) {
    asm volatile("{\n.reg .pred p;\nsetp.ne.b32 p, %82, 0;\n"
        "wgmma.mma_async.sync.aligned.m64n160k16.f32.bf16.bf16 {"
        "%0, %1, %2, %3, %4, %5, %6, %7, %8, %9, %10, %11, %12, %13, %14, %15, "
        "%16, %17, %18, %19, %20, %21, %22, %23, %24, %25, %26, %27, %28, %29, %30, %31, "
        "%32, %33, %34, %35, %36, %37, %38, %39, %40, %41, %42, %43, %44, %45, %46, %47, "
        "%48, %49, %50, %51, %52, %53, %54, %55, %56, %57, %58, %59, %60, %61, %62, %63, "
        "%64, %65, %66, %67, %68, %69, %70, %71, %72, %73, %74, %75, %76, %77, %78, %79}, "
        "%80, %81, p, 1, 1, 0, 1;\n}\n"
        : "+f"(d[0]), "+f"(d[1]), "+f"(d[2]), "+f"(d[3]), "+f"(d[4]), "+f"(d[5]), "+f"(d[6]), "+f"(d[7]),
          "+f"(d[8]), "+f"(d[9]), "+f"(d[10]), "+f"(d[11]), "+f"(d[12]), "+f"(d[13]), "+f"(d[14]), "+f"(d[15]),
          "+f"(d[16]), "+f"(d[17]), "+f"(d[18]), "+f"(d[19]), "+f"(d[20]), "+f"(d[21]), "+f"(d[22]), "+f"(d[23]),
          "+f"(d[24]), "+f"(d[25]), "+f"(d[26]), "+f"(d[27]), "+f"(d[28]), "+f"(d[29]), "+f"(d[30]), "+f"(d[31]),
          "+f"(d[32]), "+f"(d[33]), "+f"(d[34]), "+f"(d[35]), "+f"(d[36]), "+f"(d[37]), "+f"(d[38]), "+f"(d[39]),
          "+f"(d[40]), "+f"(d[41]), "+f"(d[42]), "+f"(d[43]), "+f"(d[44]), "+f"(d[45]), "+f"(d[46]), "+f"(d[47]),
          "+f"(d[48]), "+f"(d[49]), "+f"(d[50]), "+f"(d[51]), "+f"(d[52]), "+f"(d[53]), "+f"(d[54]), "+f"(d[55]),
          "+f"(d[56]), "+f"(d[57]), "+f"(d[58]), "+f"(d[59]), "+f"(d[60]), "+f"(d[61]), "+f"(d[62]), "+f"(d[63]),
          "+f"(d[64]), "+f"(d[65]), "+f"(d[66]), "+f"(d[67]), "+f"(d[68]), "+f"(d[69]), "+f"(d[70]), "+f"(d[71]),
          "+f"(d[72]), "+f"(d[73]), "+f"(d[74]), "+f"(d[75]), "+f"(d[76]), "+f"(d[77]), "+f"(d[78]), "+f"(d[79])
        : "l"(descA), "l"(descB), "r"(scaleD));
}

__device__ __forceinline__ void wgmma_n64_ss(float (&d)[32], uint64_t descA, uint64_t descB, int scaleD) {
    asm volatile("{\n.reg .pred p;\nsetp.ne.b32 p, %34, 0;\n"
        "wgmma.mma_async.sync.aligned.m64n64k16.f32.bf16.bf16 {"
        "%0, %1, %2, %3, %4, %5, %6, %7, %8, %9, %10, %11, %12, %13, %14, %15, "
        "%16, %17, %18, %19, %20, %21, %22, %23, %24, %25, %26, %27, %28, %29, %30, %31}, "
        "%32, %33, p, 1, 1, 0, 0;\n}\n"
        : "+f"(d[0]), "+f"(d[1]), "+f"(d[2]), "+f"(d[3]), "+f"(d[4]), "+f"(d[5]), "+f"(d[6]), "+f"(d[7]),
          "+f"(d[8]), "+f"(d[9]), "+f"(d[10]), "+f"(d[11]), "+f"(d[12]), "+f"(d[13]), "+f"(d[14]), "+f"(d[15]),
          "+f"(d[16]), "+f"(d[17]), "+f"(d[18]), "+f"(d[19]), "+f"(d[20]), "+f"(d[21]), "+f"(d[22]), "+f"(d[23]),
          "+f"(d[24]), "+f"(d[25]), "+f"(d[26]), "+f"(d[27]), "+f"(d[28]), "+f"(d[29]), "+f"(d[30]), "+f"(d[31])
        : "l"(descA), "l"(descB), "r"(scaleD));
}

__device__ __forceinline__ void wgmma_n64_ss_z(float (&d)[32], uint64_t descA, uint64_t descB) {
    asm volatile("{\n.reg .pred p;\nsetp.ne.b32 p, 0, 0;\n"
        "wgmma.mma_async.sync.aligned.m64n64k16.f32.bf16.bf16 {"
        "%0, %1, %2, %3, %4, %5, %6, %7, %8, %9, %10, %11, %12, %13, %14, %15, "
        "%16, %17, %18, %19, %20, %21, %22, %23, %24, %25, %26, %27, %28, %29, %30, %31}, "
        "%32, %33, p, 1, 1, 0, 0;\n}\n"
        : "=f"(d[0]), "=f"(d[1]), "=f"(d[2]), "=f"(d[3]), "=f"(d[4]), "=f"(d[5]), "=f"(d[6]), "=f"(d[7]),
          "=f"(d[8]), "=f"(d[9]), "=f"(d[10]), "=f"(d[11]), "=f"(d[12]), "=f"(d[13]), "=f"(d[14]), "=f"(d[15]),
          "=f"(d[16]), "=f"(d[17]), "=f"(d[18]), "=f"(d[19]), "=f"(d[20]), "=f"(d[21]), "=f"(d[22]), "=f"(d[23]),
          "=f"(d[24]), "=f"(d[25]), "=f"(d[26]), "=f"(d[27]), "=f"(d[28]), "=f"(d[29]), "=f"(d[30]), "=f"(d[31])
        : "l"(descA), "l"(descB));
}

__device__ __forceinline__ void wgmma_n24_rs_tb(float (&d)[12], uint32_t a0, uint32_t a1, uint32_t a2, uint32_t a3, uint64_t descB, int scaleD) {
    asm volatile("{\n.reg .pred p;\nsetp.ne.b32 p, %17, 0;\n"
        "wgmma.mma_async.sync.aligned.m64n24k16.f32.bf16.bf16 {"
        "%0, %1, %2, %3, %4, %5, %6, %7, %8, %9, %10, %11}, "
        "{%12, %13, %14, %15}, %16, p, 1, 1, 1;\n}\n"
        : "+f"(d[0]), "+f"(d[1]), "+f"(d[2]), "+f"(d[3]), "+f"(d[4]), "+f"(d[5]), "+f"(d[6]), "+f"(d[7]),
          "+f"(d[8]), "+f"(d[9]), "+f"(d[10]), "+f"(d[11])
        : "r"(a0), "r"(a1), "r"(a2), "r"(a3), "l"(descB), "r"(scaleD));
}

__device__ __forceinline__ void cnt_signal(int idx) {
    asm volatile("fence.acq_rel.gpu;\nred.relaxed.gpu.global.add.u32 [%0], 1;"
                 ::"l"(g_cnt + idx * 32) : "memory");
}
__device__ __forceinline__ void cnt_wait(int idx, uint32_t target) {
    const uint32_t* p = g_cnt + idx * 32;
#pragma unroll 1
    for (uint32_t i = 0; i < (1u << 22); i++) {
        uint32_t v;
        asm volatile("ld.acquire.gpu.global.u32 %0, [%1];" : "=r"(v) : "l"(p) : "memory");
        if ((int32_t)(v - target) >= 0) break;
    }
    asm volatile("fence.proxy.async.global;" ::: "memory");
}
__device__ __forceinline__ void cluster_arrive() { asm volatile("barrier.cluster.arrive.release.aligned;" ::: "memory"); }
__device__ __forceinline__ void cluster_arrive_relaxed() { asm volatile("barrier.cluster.arrive.relaxed.aligned;" ::: "memory"); }
__device__ __forceinline__ void cluster_wait() { asm volatile("barrier.cluster.wait.acquire.aligned;" ::: "memory"); }
__device__ __forceinline__ void bulk_wait_read() { asm volatile("cp.async.bulk.wait_group.read 0;" ::: "memory"); }

__device__ __forceinline__ float gelu_tanh(float x) {
    const float u = x * (0.7978845608028654f + 0.035677408136300125f * x * x);
    float t;
    asm("tanh.approx.f32 %0, %1;" : "=f"(t) : "f"(u));
    const float h = 0.5f * x;
    return fmaf(h, t, h);
}
__device__ __forceinline__ void release_stage(uint32_t bar, uint32_t peer, int lane) {
    if (lane == 0) { mbar_arrive(bar); mbar_arrive_cluster(bar, peer); }
}

constexpr int SM_RING = 163840;
constexpr int SM_Q = 2 * IMG_BYTES, SM_ZERO = SM_Q + 24576;
constexpr int G2_STAGE = 8192 + 20480;
constexpr int SM_MISC = 229376;
constexpr int SM_BIAS = SM_MISC, SM_RED = SM_BIAS + 384, SM_BAR = SM_RED + 128;
constexpr int B_A = 0, B_F1 = 10, B_E1 = 14, B_F2 = 18, B_E2 = 23, B_KV = 28, B_Q = 45, B_F3 = 47, B_E3 = 55, B_ST = 63, B_STAT = 65, B_AUX = 66, B_AUX2 = 67, B_COUNT = 68;
constexpr int SM_EPOCH = SM_BAR + 544;
constexpr int SM_CS = SM_EPOCH + 16;
constexpr int SM_TOTAL = SM_CS + 1728;
static_assert(SM_TOTAL <= 232448, "shared memory budget");

struct Maps { CUtensorMap x, wqkv, w1, h, o, wo, w2; };

__device__ __forceinline__ uint32_t bf2_fma(uint32_t a, uint32_t b, uint32_t c) {
    uint32_t r;
    asm("fma.rn.bf16x2 %0, %1, %2, %3;" : "=r"(r) : "r"(a), "r"(b), "r"(c));
    return r;
}
__device__ __forceinline__ uint32_t lop_and_or(uint32_t a, uint32_t m, uint32_t o) {
    uint32_t r;
    asm("lop3.b32 %0, %1, %2, %3, 0xEA;" : "=r"(r) : "r"(a), "r"(m), "r"(o));
    return r;
}
struct ExpConst { uint32_t mask, slope; };
__device__ __forceinline__ ExpConst make_exp_const() {
    ExpConst k;
    asm volatile("mov.b32 %0, 0x007F007F;" : "=r"(k.mask));
    asm volatile("mov.b32 %0, 0x3EF83EF8;" : "=r"(k.slope));
    return k;
}
__device__ __forceinline__ uint32_t exp2_pair_fma(float t0, float t1, const ExpConst& k) {
    const uint32_t L = __byte_perm(__float_as_uint(t0), __float_as_uint(t1), 0x6521);
    const uint32_t g = lop_and_or(L, k.mask, 0x3F803F80u);
    const uint32_t u = bf2_fma(g, k.slope, 0xBF37BF37u);
    const uint32_t e = bf2_fma(u, u, 0xBD71BD71u);
    return bf2_fma(L, e, L);
}
template <int SHIFT>
__device__ __forceinline__ void exp_tile(const float (&s)[32], uint32_t (&p)[16], const ExpConst& k) {
#pragma unroll
    for (int b = 0; b < 8; b++) {
        if ((EMU_MASK >> (b + SHIFT)) & 1) {
            p[2 * b] = exp2_pair_fma(s[4 * b], s[4 * b + 1], k);
            p[2 * b + 1] = exp2_pair_fma(s[4 * b + 2], s[4 * b + 3], k);
        } else {
            p[2 * b] = pack_bf16(ex2(s[4 * b]), ex2(s[4 * b + 1]));
            p[2 * b + 1] = pack_bf16(ex2(s[4 * b + 2]), ex2(s[4 * b + 3]));
        }
    }
}

__device__ __forceinline__ void qk_tile(float (&s)[32], uint64_t dQ, uint64_t dQ2, uint64_t dK) {
    wg_fence();
    wgmma_n64_ss_z(s, dQ, dK);
    wgmma_n64_ss(s, dQ2, dK + 16, 1);
    wg_commit();
}
__device__ __forceinline__ void pv_tile(float (&o)[12], const uint32_t (&p)[16], uint64_t dV) {
    wg_fence();
#pragma unroll
    for (int ks = 0; ks < 4; ks++)
        wgmma_n24_rs_tb(o, p[4 * ks], p[4 * ks + 1], p[4 * ks + 2], p[4 * ks + 3], dV + ks * 48, 1);
    wg_commit();
}
__device__ __forceinline__ void store_o(const float (&o)[12], int h, int rbase, int lane) {
    const int g = lane >> 2, c = lane & 3;
    const bool odd = h & 1;
    const int lsrc = (lane & ~3) | (odd ? 0 : 2);
    const float i0 = 1.f / __shfl_sync(~0u, o[8], lsrc), i1 = 1.f / __shfl_sync(~0u, o[10], lsrc);
    __nv_bfloat16* dst = g_o + (size_t)(rbase + g) * DM + h * 20;
    const int d0 = (odd ? 4 : 0) + 2 * c, d1 = d0 + 8, d2 = odd ? 2 * c - 4 : 16 + 2 * c;
    *(uint32_t*)(dst + d0) = pack_bf16(o[0] * i0, o[1] * i0);
    *(uint32_t*)(dst + d1) = pack_bf16(o[4] * i0, o[5] * i0);
    *(uint32_t*)(dst + 8 * DM + d0) = pack_bf16(o[2] * i1, o[3] * i1);
    *(uint32_t*)(dst + 8 * DM + d1) = pack_bf16(o[6] * i1, o[7] * i1);
    if (odd ? (c >= 2) : (c < 2)) {
        *(uint32_t*)(dst + d2) = pack_bf16(o[8] * i0, o[9] * i0);
        *(uint32_t*)(dst + 8 * DM + d2) = pack_bf16(o[10] * i1, o[11] * i1);
    }
}

__device__ __forceinline__ void attn_rows_maxshift(uint32_t sK, uint32_t barKV, uint64_t dQ, uint64_t dQ2, int h, int rbase) {
    const int lane = threadIdx.x & 31;
    const uint64_t dK0 = make_desc(sK, 128, 384, 0), dV0 = make_desc(sK + IMG_BYTES, 384, 128, 0);
    float o[12], s[32];
    uint32_t p[16];
#pragma unroll
    for (int i = 0; i < 12; i++) o[i] = 0.f;
    float m0 = -3.0e38f, m1 = -3.0e38f;
    mbar_wait(barKV + 128, 0);
#pragma unroll 1
    for (int t = 0; t < 32; t++) {
        mbar_wait(barKV + (t >> 1) * 8, 0);
        qk_tile(s, dQ, dQ2, dK0 + t * 192);
        wg_wait<0>();
        fence_regs(s);
        const uint32_t mask = EMU_MASK >> ((t & 1) * 8);
        float n0 = m0, n1 = m1;
#pragma unroll
        for (int b = 0; b < 8; b++) {
            const bool emu = (mask >> b) & 1;
            const float f = emu ? 0.5f : 1.f, off = emu ? -383.00390625f : 0.f;
#pragma unroll
            for (int i = 0; i < 4; i++) s[4 * b + i] = fmaf(s[4 * b + i], f, off);
            n0 = fmaxf(n0, fmaxf(s[4 * b], s[4 * b + 1]));
            n1 = fmaxf(n1, fmaxf(s[4 * b + 2], s[4 * b + 3]));
        }
        n0 = fmaxf(n0, __shfl_xor_sync(~0u, n0, 1)); n0 = fmaxf(n0, __shfl_xor_sync(~0u, n0, 2));
        n1 = fmaxf(n1, __shfl_xor_sync(~0u, n1, 1)); n1 = fmaxf(n1, __shfl_xor_sync(~0u, n1, 2));
        const float c0 = ex2(m0 - n0), c1 = ex2(m1 - n1);
        m0 = n0; m1 = n1;
#pragma unroll
        for (int b = 0; b < 3; b++) { o[4 * b] *= c0; o[4 * b + 1] *= c0; o[4 * b + 2] *= c1; o[4 * b + 3] *= c1; }
#pragma unroll
        for (int b = 0; b < 8; b++) {
            p[2 * b] = pack_bf16(ex2(s[4 * b] - m0), ex2(s[4 * b + 1] - m0));
            p[2 * b + 1] = pack_bf16(ex2(s[4 * b + 2] - m1), ex2(s[4 * b + 3] - m1));
        }
        pv_tile(o, p, dV0 + t * 192);
        wg_wait<0>();
        fence_regs(o);
    }
    store_o(o, h, rbase, lane);
}

__global__ void __launch_bounds__(512, 1) __cluster_dims__(2, 1, 1)
k_fused(const __grid_constant__ Maps tm, const __nv_bfloat16* __restrict__ x, const uint8_t* __restrict__ wqkv,
        const uint8_t* __restrict__ w1, const uint8_t* __restrict__ w2, const uint8_t* __restrict__ wo,
        const __nv_bfloat16* __restrict__ b1, const __nv_bfloat16* __restrict__ b2, __nv_bfloat16* __restrict__ out) {
    extern __shared__ __align__(1024) uint8_t smem[];
    const uint32_t sb = smem_u32(smem);
    const uint32_t bar = sb + SM_BAR;
    const int warp = __shfl_sync(~0u, threadIdx.x >> 5, 0), lane = threadIdx.x & 31;
    const int wgi = warp >> 2, w4 = warp & 3, g = lane >> 2, c = lane & 3;
    const uint32_t rank = blockIdx.x & 1, peer = rank ^ 1;
    const int cl = blockIdx.x >> 1;
    const int cg = cl & 7, rb = (cl >> 3) * 2 + rank;

    if (elect_one()) {
#pragma unroll
        for (int j = 0; j < 5; j++) {
            const int i = warp * 5 + j;
            const int cnt = (i >= B_E1 && i < B_F2) || (i >= B_E2 && i < B_KV) ? 16
                          : (i >= B_E3 && i <= B_ST) || i == B_STAT ? 8 : i == B_ST + 1 ? 2 : i >= B_AUX ? 7 : 1;
            if (i < B_COUNT) mbar_init(bar + i * 8, cnt);
        }
        fence_barrier_init();
    }
    __syncthreads();
    cluster_arrive_relaxed();
    if (warp == 15 && elect_one()) {
        prefetch_map(&tm.x); prefetch_map(&tm.wqkv);
        for (int kb = 0; kb < 3; kb++) tma_prefetch_l2(&tm.x, kb * 64, rb * 128);
        for (int it = 0; it < 4; it++) {
            tma_prefetch_l2(&tm.wqkv, cg * 240 + rank * 120, it * 32);
            tma_prefetch_l2(&tm.wqkv, cg * 240 + rank * 120 + 64, it * 32);
        }
        prefetch_map(&tm.w1); prefetch_map(&tm.h);
    }
    cluster_wait();

    {
        const uint32_t sB = sb + SM_RING;
        if (threadIdx.x == 0) TL(1, 0);
        if (wgi < 2) {
            reg_dealloc<40>();
            if (warp == 0) {
#pragma unroll 1
                for (int it = 0; it < 20; it++) {
                    const int s = it & 3;
                    if (it >= 4) mbar_wait(bar + (B_E1 + s) * 8, ((it >> 2) - 1) & 1);
                    if (elect_one()) {
                        const uint32_t dst = sB + s * 16384 + rank * 8192, fb = bar + (B_F1 + s) * 8;
                        const int c0 = cg * 240 + rank * 120;
                        mbar_expect_tx(fb, 16384);
                        tma_load_mc(dst, &tm.wqkv, c0, it * 32, fb, 3);
                        tma_load_mc(dst + 4096, &tm.wqkv, c0 + 64, it * 32, fb, 3);
                    }
                    __syncwarp();
                    const int kb = it < 3 ? it : (it & 1) ? 10 : (it >> 1) + 1;
                    if (kb < 10 && elect_one()) {
                        mbar_expect_tx(bar + (B_A + kb) * 8, 16384);
                        tma_load(sb + kb * 16384, &tm.x, kb * 64, rb * 128, bar + (B_A + kb) * 8);
                    }
                    __syncwarp();
                }
#pragma unroll 1
                for (int it = 0; it < 20; it++) {
                    const int s = it % 5;
                    if (it < 5) { if (it != 3) mbar_wait(bar + (B_E1 + (it == 4 ? 3 : it)) * 8, 0); }
                    else mbar_wait(bar + (B_E2 + s) * 8, ((it / 5) - 1) & 1);
                    if (elect_one()) {
                        const uint32_t dst = sB + s * 12288, fb = bar + (B_F2 + s) * 8;
                        mbar_expect_tx(fb, 12288);
                        if ((it & 1) == (int)rank) {
                            tma_load_mc(dst, &tm.w1, cg * 192, it * 32, fb, 3);
                            tma_load_mc(dst + 4096, &tm.w1, cg * 192 + 64, it * 32, fb, 3);
                        } else {
                            tma_load_mc(dst + 8192, &tm.w1, cg * 192 + 128, it * 32, fb, 3);
                        }
                    }
                    __syncwarp();
                }
            } else {
                const int ht = threadIdx.x - 32;
                if (ht == 192) *reinterpret_cast<volatile uint32_t*>(smem + SM_EPOCH) = *(volatile uint32_t*)&g_epoch;
                auto slab_sum = [&](const uint32_t* src, int pitch) {
                    float s0 = 0.f, s1 = 0.f;
#pragma unroll
                    for (int h2 = 0; h2 < 2; h2++) {
                        uint32_t v[20];
#pragma unroll
                        for (int k = 0; k < 20; k++) v[k] = __ldg(src + (h2 * 20 + k) * pitch);
#pragma unroll
                        for (int k = 0; k < 20; k++) { s0 += bf_lo(v[k]); s1 += bf_hi(v[k]); }
                    }
                    return make_float2(s0, s1);
                };
                auto gather = [&](int idx) {
                    float s0 = 0.f, s1 = 0.f;
#pragma unroll
                    for (int r = 0; r < 16; r++) {
                        const float2 v = __ldcg(g_csp + r * 1728 + cg * 216 + idx);
                        s0 += v.x; s1 += v.y;
                    }
                    reinterpret_cast<float2*>(smem + SM_CS)[idx] = make_float2(s0, s1);
                };
                if (ht < 120)
                    g_csp[rb * 1728 + cg * 216 + ht] = slab_sum(reinterpret_cast<const uint32_t*>(wqkv) + rb * 40 * 960 + cg * 120 + ht, 960);
                if (threadIdx.x == 64) IT(3, 0);
                asm volatile("bar.sync 8, 224;" ::: "memory");
                const uint32_t epoch = *reinterpret_cast<volatile uint32_t*>(smem + SM_EPOCH);
                if (warp == 6) { if (elect_one()) cnt_signal(CNT_CS + cg); __syncwarp(); }
                if (warp == 7) {
                    mbar_wait(bar + B_STAT * 8, 0);
                    if (elect_one()) cnt_signal(CNT_ST + rb);
                    __syncwarp();
                }
                if (ht < 96) {
                    g_csp[rb * 1728 + cg * 216 + 120 + ht] = slab_sum(reinterpret_cast<const uint32_t*>(w1) + rb * 40 * 768 + cg * 96 + ht, 768);
                    reinterpret_cast<uint32_t*>(smem + SM_BIAS)[ht] = __ldg(reinterpret_cast<const uint32_t*>(b1 + cg * 192) + ht);
                }
                asm volatile("bar.sync 8, 224;" ::: "memory");
                if (warp == 6) { if (elect_one()) cnt_signal(CNT_CS2 + cg); __syncwarp(); }
                if (threadIdx.x == 64) IT(3, 2);
                if (lane == 0) { cnt_wait(CNT_CS + cg, (epoch + 1) * 16); cnt_wait(CNT_ST + rb, (epoch + 1) * 8); }
                __syncwarp();
                if (threadIdx.x == 64) IT(3, 4);
                if (ht < 120) gather(ht);
                __syncwarp();
                if (threadIdx.x == 64) IT(3, 5);
                if (lane == 0) mbar_arrive(bar + B_AUX * 8);
                if (warp == 3 && elect_one()) {
                    prefetch_l2(w2 + blockIdx.x * 15360, 15360);
                    prefetch_l2(wo + blockIdx.x * 6400, 6400);
                }
                if (lane == 0) cnt_wait(CNT_CS2 + cg, (epoch + 1) * 16);
                __syncwarp();
                if (ht < 96) gather(120 + ht);
                __syncwarp();
                if (lane == 0) mbar_arrive(bar + B_AUX2 * 8);
                if (warp == 4) {
                    mbar_wait(bar + B_ST * 8, 0);
                    if (elect_one()) cnt_signal(CNT_QKV + cg);
                    __syncwarp();
                }
            }
            asm volatile("bar.sync %0, 128;" ::"r"(wgi + 3) : "memory");
            reg_alloc<128>();
        } else {
            reg_alloc<216>();
            const int wi = wgi - 2;
            const int row0 = rb * 128 + wi * 64 + w4 * 16 + g;
            const uint32_t sAw = sb + wi * 8192;
            const int rbk = row0 >> 3, hs0 = cg * 12;
            const int srow = rb * 128 + cg * 16 + (warp - 8) * 2 + (lane >> 4);
            uint4 xv[5];
#pragma unroll
            for (int i = 0; i < 5; i++) xv[i] = __ldg(reinterpret_cast<const uint4*>(x + (size_t)srow * DM) + (lane & 15) + 16 * i);
            float acc1[2][60];
#pragma unroll 1
            for (int it = 0; it < 20; it++) {
                const int s = it & 3;
                if (!(it & 1)) mbar_wait(bar + (B_A + (it >> 1)) * 8, 0);
                if (threadIdx.x == 256 && it == 0) TL(0, 2);
                if (threadIdx.x == 256) IT(0, it);
                mbar_wait(bar + (B_F1 + s) * 8, (it >> 2) & 1);
                if (threadIdx.x == 256) IT(1, it);
                wg_fence();
                const uint64_t dA = make_desc(sAw + (it >> 1) * 16384 + (it & 1) * 64, 16, 1024, 1);
                const uint64_t dB = make_desc(sB + s * 16384, 4096, 1024, 1);
                wgmma_n120_ss_tb(acc1[0], dA, dB, it > 0);
                wgmma_n120_ss_tb(acc1[1], dA, dB + 512, it > 0);
                wgmma_n120_ss_tb(acc1[0], dA + 2, dB + 128, 1);
                wgmma_n120_ss_tb(acc1[1], dA + 2, dB + 640, 1);
                wg_commit();
                if (it > 0) { wg_wait<1>(); release_stage(bar + (B_E1 + ((it - 1) & 3)) * 8, peer, lane); }
                if (it == 5) {
                    float sm = 0.f;
#pragma unroll
                    for (int i = 0; i < 5; i++)
                        sm += (bf_lo(xv[i].x) + bf_hi(xv[i].x)) + (bf_lo(xv[i].y) + bf_hi(xv[i].y)) +
                              (bf_lo(xv[i].z) + bf_hi(xv[i].z)) + (bf_lo(xv[i].w) + bf_hi(xv[i].w));
#pragma unroll
                    for (int o = 8; o; o >>= 1) sm += __shfl_xor_sync(~0u, sm, o);
                    const float mu = sm * (1.f / DM);
                    float q = 0.f;
#pragma unroll
                    for (int i = 0; i < 5; i++) {
                        const uint32_t w[4] = {xv[i].x, xv[i].y, xv[i].z, xv[i].w};
#pragma unroll
                        for (int j = 0; j < 4; j++) {
                            const float d0 = bf_lo(w[j]) - mu, d1 = bf_hi(w[j]) - mu;
                            q = fmaf(d0, d0, fmaf(d1, d1, q));
                        }
                    }
#pragma unroll
                    for (int o = 8; o; o >>= 1) q += __shfl_xor_sync(~0u, q, o);
                    const float var = q * (1.f / DM);
                    const float r1 = 1.f / sqrtf(var + LN_EPS);
                    const float r2 = 1.f / sqrtf(var * r1 * r1 + LN_EPS);
                    if ((lane & 15) == 0) g_stat[srow] = make_float4(mu, r1, r1 * r2, 0.f);
                    __syncwarp();
                    if (lane == 0) mbar_arrive(bar + B_STAT * 8);
                }
            }
            if (threadIdx.x == 256) IT(2, 0);
            mbar_wait(bar + B_AUX * 8, 0);
            if (threadIdx.x == 256) IT(2, 1);
            const float4 st0 = __ldcg(g_stat + row0), st1 = __ldcg(g_stat + row0 + 8);
            wg_wait<0>();
            release_stage(bar + (B_E1 + 3) * 8, peer, lane);
            fence_regs(acc1[0]);
            fence_regs(acc1[1]);
            if (threadIdx.x == 256) TL(1, 1);
            const float2* cs = reinterpret_cast<const float2*>(smem + SM_CS) + c;
            uint8_t* img = g_img + (size_t)hs0 * IMG_BYTES + rbk * 384 + g * 16 + c * 4;
            const bool emu0 = (EMU_MASK >> (rbk & 15)) & 1, emu1 = (EMU_MASK >> ((rbk + 1) & 15)) & 1;
            const bool low = c < 2;
            uint32_t pk[60];
#pragma unroll
            for (int m = 0; m < 6; m++) {
                const int which = (hs0 + 2 * m) >> 5;
                const float m0 = st0.y * (which == 0 ? QSCALE : (which == 1 && emu0) ? 2.f : 1.f);
                const float m1 = st1.y * (which == 0 ? QSCALE : (which == 1 && emu1) ? 2.f : 1.f);
                const float d0 = -st0.x * m0, d1 = -st1.x * m1;
                const float* a = &acc1[m / 3][20 * (m % 3)];
#pragma unroll
                for (int b = 0; b < 5; b++) {
                    const float2 cv = cs[(5 * m + b) * 4];
                    pk[10 * m + 2 * b] = pack_bf16(fmaf(a[4 * b], m0, d0 * cv.x), fmaf(a[4 * b + 1], m0, d0 * cv.y));
                    pk[10 * m + 2 * b + 1] = pack_bf16(fmaf(a[4 * b + 2], m1, d1 * cv.x), fmaf(a[4 * b + 3], m1, d1 * cv.y));
                }
            }
            const float r20 = st0.z, r21 = st1.z, e20 = -st0.x * st0.z, e21 = -st1.x * st1.z;
            if (threadIdx.x == 256) IT(2, 2);
            float acc2[96];
#pragma unroll
            for (int it = 0; it < 20; it++) {
                const int s = it % 5;
                if (threadIdx.x == 256) IT(0, 20 + it);
                mbar_wait(bar + (B_F2 + s) * 8, (it / 5) & 1);
                if (threadIdx.x == 256) IT(1, 20 + it);
                wg_fence();
                const uint64_t dA = make_desc(sAw + (it >> 1) * 16384 + (it & 1) * 64, 16, 1024, 1);
                const uint64_t dB = make_desc(sB + s * 12288, 4096, 1024, 1);
                if (it == 0) wgmma_n192_ss_tb_z(acc2, dA, dB); else wgmma_n192_ss_tb(acc2, dA, dB, 1);
                wgmma_n192_ss_tb(acc2, dA + 2, dB + 128, 1);
                wg_commit();
                if (it > 0) {
                    wg_wait<1>();
                    if (it <= 15) release_stage(bar + (B_E2 + (it - 1) % 5) * 8, peer, lane);
                }
                if (it < 12) {
                    const int m = it / 2, part = it % 2;
                    const int hs = hs0 + 2 * m, which = hs >> 5;
                    const uint32_t* a = pk + 10 * m;
                    uint8_t* pe = img + (2 * m) * IMG_BYTES;
                    uint8_t* po = pe + IMG_BYTES;
                    if (part == 0) {
                        const uint32_t padv = which == 0 ? 0x3F803F80u : which == 1 ? 0xBFFF4440u : 0x00003F80u;
                        const uint32_t p0 = ((c & 1) || (which == 1 && !emu0)) ? 0u : padv;
                        const uint32_t p1 = ((c & 1) || (which == 1 && !emu1)) ? 0u : padv;
                        *(uint32_t*)(pe) = a[0];
                        *(uint32_t*)(pe + 128) = a[2];
                        *(uint32_t*)(pe + 256) = low ? a[4] : p0;
                        *(uint32_t*)(pe + 384) = a[1];
                        *(uint32_t*)(pe + 512) = a[3];
                        *(uint32_t*)(pe + 640) = low ? a[5] : p1;
                        *(uint32_t*)(po + 256) = low ? p0 : a[4];
                        *(uint32_t*)(po + 640) = low ? p1 : a[5];
                    } else {
                        *(uint32_t*)(po) = a[6];
                        *(uint32_t*)(po + 128) = a[8];
                        *(uint32_t*)(po + 384) = a[7];
                        *(uint32_t*)(po + 512) = a[9];
                        if (which < 2) {
                            const uint32_t u0 = bf2_fma(a[4], a[4], 0u), u1 = bf2_fma(a[5], a[5], 0u);
                            const uint32_t pe0 = bf2_fma(a[0], a[0], bf2_fma(a[2], a[2], low ? u0 : 0u));
                            const uint32_t pe1 = bf2_fma(a[1], a[1], bf2_fma(a[3], a[3], low ? u1 : 0u));
                            const uint32_t po0 = bf2_fma(a[6], a[6], bf2_fma(a[8], a[8], low ? 0u : u0));
                            const uint32_t po1 = bf2_fma(a[7], a[7], bf2_fma(a[9], a[9], low ? 0u : u1));
                            const float e0 = bf_lo(pe0) + bf_hi(pe0), e1 = bf_lo(pe1) + bf_hi(pe1);
                            const float o0 = bf_lo(po0) + bf_hi(po0), o1 = bf_lo(po1) + bf_hi(po1);
                            const bool b0 = c & 1, b1_ = c & 2;
                            const float x0 = (b0 ? e1 : e0) + __shfl_xor_sync(~0u, b0 ? e0 : e1, 1);
                            const float x1 = (b0 ? o1 : o0) + __shfl_xor_sync(~0u, b0 ? o0 : o1, 1);
                            float y = (b1_ ? x1 : x0) + __shfl_xor_sync(~0u, b1_ ? x0 : x1, 2);
                            if (which == 1 && (b0 ? emu1 : emu0)) y *= 0.25f;
                            g_nrm[(hs + (c >> 1)) * SEQ + row0 + (c & 1) * 8] = y;
                        }
                    }
                    if (it == 11) { __syncwarp(); if (lane == 0) mbar_arrive(bar + B_ST * 8); }
                }
            }
            wg_wait<0>();
            fence_regs(acc2);
            if (threadIdx.x == 256) TL(1, 2);
            mbar_wait(bar + B_AUX2 * 8, 0);
            const uint32_t* bias = reinterpret_cast<const uint32_t*>(smem + SM_BIAS) + c;
            const int mrow = w4 * 16 + (lane & 15);
            const uint32_t st_row = sAw + mrow * 128;
#pragma unroll
            for (int j = 0; j < 24; j += 2) {
                const uint32_t bA = bias[j * 4], bB = bias[j * 4 + 4];
                const float2 cA = cs[(30 + j) * 4], cB = cs[(31 + j) * 4];
                const float* a = acc2 + j * 4;
                const uint32_t r00 = pack_bf16(gelu_tanh(fmaf(a[0], r20, fmaf(e20, cA.x, bf_lo(bA)))), gelu_tanh(fmaf(a[1], r20, fmaf(e20, cA.y, bf_hi(bA)))));
                const uint32_t r10 = pack_bf16(gelu_tanh(fmaf(a[2], r21, fmaf(e21, cA.x, bf_lo(bA)))), gelu_tanh(fmaf(a[3], r21, fmaf(e21, cA.y, bf_hi(bA)))));
                const uint32_t r01 = pack_bf16(gelu_tanh(fmaf(a[4], r20, fmaf(e20, cB.x, bf_lo(bB)))), gelu_tanh(fmaf(a[5], r20, fmaf(e20, cB.y, bf_hi(bB)))));
                const uint32_t r11 = pack_bf16(gelu_tanh(fmaf(a[6], r21, fmaf(e21, cB.x, bf_lo(bB)))), gelu_tanh(fmaf(a[7], r21, fmaf(e21, cB.y, bf_hi(bB)))));
                const int chunk = (j & 7) + (lane >> 4);
                stmatrix_x4(st_row + (j >> 3) * 16384 + ((chunk ^ (mrow & 7)) << 4), r00, r10, r01, r11);
            }
            fence_proxy_async();
            asm volatile("bar.sync %0, 128;" ::"r"(wgi + 3) : "memory");
            if (w4 == 0 && lane == 0) {
#pragma unroll
                for (int b = 0; b < 3; b++) tma_store(&tm.h, sAw + b * 16384, cg * 192 + b * 64, rb * 128 + wi * 64);
                bulk_commit();
                bulk_wait_read();
            }
            __syncwarp();
            reg_dealloc<128>();
        }
        __syncthreads();
        if (threadIdx.x == 0) TL(1, 3);
    }

    {
        const uint32_t epoch = *reinterpret_cast<volatile uint32_t*>(smem + SM_EPOCH);
        const int h = blockIdx.x >> 2, qb = blockIdx.x & 3;
        const uint32_t sK = sb, sV = sb + IMG_BYTES, barKV = bar + B_KV * 8;
        if (threadIdx.x == 0) TL(2, 0);
        if (threadIdx.x < 192) *reinterpret_cast<uint4*>(smem + SM_ZERO + threadIdx.x * 16) = make_uint4(0, 0, 0, 0);
        fence_proxy_async();
        if (warp == 0) {
            if (elect_one()) {
                cnt_wait(CNT_QKV + h / 12, (epoch + 1) * 16);
                cnt_wait(CNT_QKV + (32 + h) / 12, (epoch + 1) * 16);
                cnt_wait(CNT_QKV + (64 + h) / 12, (epoch + 1) * 16);
                const uint8_t* gK = g_img + (size_t)(32 + h) * IMG_BYTES;
                const uint8_t* gV = g_img + (size_t)(64 + h) * IMG_BYTES;
                const uint8_t* gQ = g_img + (size_t)h * IMG_BYTES + qb * 64 * 384;
                mbar_expect_tx(barKV + 128, 6144);
                bulk_load(sK, gK, 6144, barKV + 128);
                for (int p = 0; p < 2; p++) {
                    mbar_expect_tx(bar + (B_Q + p) * 8, 12288);
                    bulk_load(sb + SM_Q + p * 12288, gQ + p * 12288, 12288, bar + (B_Q + p) * 8);
                }
                for (int i = 0; i < 16; i++) {
                    mbar_expect_tx(barKV + i * 8, i < 15 ? 12288 : 6144);
                    bulk_load(sV + i * 6144, gV + i * 6144, 6144, barKV + i * 8);
                    if (i < 15) bulk_load(sK + (i + 1) * 6144, gK + (i + 1) * 6144, 6144, barKV + i * 8);
                }
            }
            __syncwarp();
        }
        __syncthreads();
        if (threadIdx.x == 0) TL(2, 1);
        float* red = reinterpret_cast<float*>(smem + SM_RED);
        float kmax = 0.f, qmax = __ldcg(g_nrm + h * SEQ + qb * 512 + threadIdx.x);
#pragma unroll
        for (int i = 0; i < 4; i++) kmax = fmaxf(kmax, __ldcg(g_nrm + (32 + h) * SEQ + i * 512 + threadIdx.x));
#pragma unroll
        for (int o = 16; o; o >>= 1) {
            kmax = fmaxf(kmax, __shfl_xor_sync(~0u, kmax, o));
            qmax = fmaxf(qmax, __shfl_xor_sync(~0u, qmax, o));
        }
        if (lane == 0) { red[warp] = kmax; red[16 + warp] = qmax; }
        __syncthreads();
        kmax = red[lane & 15]; qmax = red[16 + (lane & 15)];
#pragma unroll
        for (int o = 8; o; o >>= 1) {
            kmax = fmaxf(kmax, __shfl_xor_sync(~0u, kmax, o));
            qmax = fmaxf(qmax, __shfl_xor_sync(~0u, qmax, o));
        }
        const bool safe = __all_sync(~0u, kmax * qmax * 1.1f <= SAFE_BOUND * SAFE_BOUND);
        const uint64_t dK0 = make_desc(sK, 128, 384, 0), dV0 = make_desc(sV, 384, 128, 0);
        auto publish_h = [&]() {
            if (warp == 8 || warp == 12) {
                if (lane == 0) { bulk_wait_all(); cnt_signal(CNT_H + rb); }
                __syncwarp();
            }
        };
        if (!safe) {
#pragma unroll 1
            for (int pass = 0; pass < 2; pass++) {
                const uint32_t sQ = sb + SM_Q + pass * 12288 + wgi * 3072;
                mbar_wait(bar + (B_Q + pass) * 8, 0);
                if (lane < 16) *reinterpret_cast<uint32_t*>(smem + (sQ - sb) + (w4 * 2 + (lane >> 3)) * 384 + 256 + (lane & 7) * 16 + ((h & 1) ? 0 : 8)) = 0u;
                fence_proxy_async();
                asm volatile("bar.sync %0, 128;" ::"r"(wgi + 3) : "memory");
                attn_rows_maxshift(sK, barKV, make_desc(sQ, 128, 384, 0), make_desc(sQ + 256, sb + SM_ZERO - (sQ + 256), 384, 0), h,
                                   qb * 512 + pass * 256 + wgi * 64 + w4 * 16);
                if (pass == 0) publish_h();
            }
        } else {
            const ExpConst kc = make_exp_const();
#pragma unroll 1
            for (int pass = 0; pass < 2; pass++) {
                const int rbase = qb * 512 + pass * 256 + wgi * 64 + w4 * 16;
                const uint32_t sQ = sb + SM_Q + pass * 12288 + wgi * 3072;
                const uint64_t dQ = make_desc(sQ, 128, 384, 0), dQ2 = make_desc(sQ + 256, sb + SM_ZERO - (sQ + 256), 384, 0);
                float o[12], sa[32], sc[32];
                uint32_t p[16];
#pragma unroll
                for (int i = 0; i < 12; i++) o[i] = 0.f;
                fence_regs(o);
                mbar_wait(bar + (B_Q + pass) * 8, 0);
                mbar_wait(barKV + 128, 0);
                qk_tile(sa, dQ, dQ2, dK0);
                wg_wait<0>();
                fence_regs(sa);
                uint64_t dK = dK0, dV = dV0;
                uint32_t bj = barKV;
#pragma unroll 1
                for (int j = 0; j < 16; j++) {
                    mbar_wait(bj, 0);
                    qk_tile(sc, dQ, dQ2, dK + 192);
                    wg_wait<1>();
                    exp_tile<0>(sa, p, kc);
                    pv_tile(o, p, dV);
                    wg_wait<1>();
                    fence_regs(sc);
                    mbar_wait(bj, 0);
                    qk_tile(sa, dQ, dQ2, dK + 384);
                    wg_wait<1>();
                    exp_tile<8>(sc, p, kc);
                    pv_tile(o, p, dV + 192);
                    wg_wait<1>();
                    fence_regs(sa);
                    dK += 384; dV += 384; bj += 8;
                }
                wg_wait<0>();
                fence_regs(o);
                store_o(o, h, rbase, lane);
                if (threadIdx.x == 0) TL(2, 2 + pass);
                if (pass == 0) publish_h();
            }
        }
        __syncthreads();
        if (threadIdx.x == 64) cnt_signal(CNT_O + qb);
        cluster_arrive_relaxed();
    }

    {
        const uint32_t epoch = *reinterpret_cast<volatile uint32_t*>(smem + SM_EPOCH);
        const int ct = cl & 3, rt = (cl >> 2) * 2 + rank;
        if (threadIdx.x == 0) TL(3, 0);
        const int orow = threadIdx.x >> 3, oseg = threadIdx.x & 7;
        const size_t ooff = (size_t)(rt * 64 + orow) * DM + ct * 160 + oseg * 20;
        uint2 xr[5], br[5];
#pragma unroll
        for (int i = 0; i < 5; i++) {
            xr[i] = __ldg(reinterpret_cast<const uint2*>(x + ooff) + i);
            br[i] = __ldg(reinterpret_cast<const uint2*>(b2 + ct * 160 + oseg * 20) + i);
        }
        cluster_wait();
        float* stg = reinterpret_cast<float*>(smem);
        if (warp == 4) {
            if (elect_one()) { prefetch_map(&tm.h); prefetch_map(&tm.o); prefetch_map(&tm.w2); prefetch_map(&tm.wo); cnt_wait(CNT_H + (rt >> 1), (epoch + 1) * 16); }
            __syncwarp();
#pragma unroll 1
            for (int kb = 0; kb < 34; kb++) {
                const int s = kb & 7;
                if (kb >= 8) mbar_wait(bar + (B_E3 + s) * 8, ((kb >> 3) - 1) & 1);
                if (elect_one()) {
                    if (kb == 24) { cnt_wait(CNT_O + (rt >> 3), (epoch + 1) * 32); TL(3, 1); }
                    const uint32_t dst = sb + s * G2_STAGE, fb = bar + (B_F3 + s) * 8;
                    const CUtensorMap* mA = kb < 24 ? &tm.h : &tm.o;
                    const CUtensorMap* mB = kb < 24 ? &tm.w2 : &tm.wo;
                    const int k0 = (kb < 24 ? kb : kb - 24) * 64;
                    mbar_expect_tx(fb, G2_STAGE);
                    tma_load(dst, mA, k0, rt * 64, fb);
                    const int first = ((kb & 1) == (int)rank) ? 0 : 3, last = ((kb & 1) == (int)rank) ? 3 : 5;
                    for (int b = first; b < last; b++) tma_load_mc(dst + 8192 + b * 4096, mB, ct * 160 + b * 32, k0, fb, 3);
                }
                __syncwarp();
            }
        } else if (wgi == 0) {
            float acc[80];
#pragma unroll 1
            for (int kb = 0; kb < 34; kb++) {
                const int s = kb & 7;
                mbar_wait(bar + (B_F3 + s) * 8, (kb >> 3) & 1);
                wg_fence();
                const uint64_t dA = make_desc(sb + s * G2_STAGE, 16, 1024, 1);
                const uint64_t dB = make_desc(sb + s * G2_STAGE + 8192, 4096, 512, 2);
#pragma unroll
                for (int kk = 0; kk < 4; kk++) wgmma_n160_ss_tb(acc, dA + kk * 2, dB + kk * 64, (kb | kk) != 0);
                wg_commit();
                if (kb > 0) {
                    wg_wait<1>();
                    if (kb <= 26) release_stage(bar + (B_E3 + ((kb - 1) & 7)) * 8, peer, lane);
                }
            }
            wg_wait<0>();
            fence_regs(acc);
            if (threadIdx.x == 0) TL(3, 2);
            const int r = w4 * 16 + g;
#pragma unroll
            for (int j = 0; j < 20; j++) {
                *reinterpret_cast<float2*>(stg + r * 168 + j * 8 + 2 * c) = make_float2(acc[4 * j], acc[4 * j + 1]);
                *reinterpret_cast<float2*>(stg + (r + 8) * 168 + j * 8 + 2 * c) = make_float2(acc[4 * j + 2], acc[4 * j + 3]);
            }
        }
        __syncthreads();
        const float4* sp = reinterpret_cast<const float4*>(stg + orow * 168 + oseg * 20);
#pragma unroll
        for (int i = 0; i < 5; i++) {
            const float4 a = sp[i];
            uint2 w;
            w.x = pack_bf16(a.x + bf_lo(br[i].x) + bf_lo(xr[i].x), a.y + bf_hi(br[i].x) + bf_hi(xr[i].x));
            w.y = pack_bf16(a.z + bf_lo(br[i].y) + bf_lo(xr[i].y), a.w + bf_hi(br[i].y) + bf_hi(xr[i].y));
            reinterpret_cast<uint2*>(out + ooff)[i] = w;
        }
        if (blockIdx.x == 0 && threadIdx.x == 0) g_epoch = epoch + 1;
        if (threadIdx.x == 0) TL(3, 3);
    }
    cluster_arrive_relaxed();
    cluster_wait();
}

typedef CUresult (*EncodeTiledFn)(CUtensorMap*, CUtensorMapDataType, cuuint32_t, void*, const cuuint64_t*,
                                  const cuuint64_t*, const cuuint32_t*, const cuuint32_t*, CUtensorMapInterleave,
                                  CUtensorMapSwizzle, CUtensorMapL2promotion, CUtensorMapFloatOOBfill);

CUtensorMap make_map(EncodeTiledFn enc, const void* ptr, int rows, int cols, int box_rows, int box_cols,
                     CUtensorMapSwizzle swz) {
    CUtensorMap m;
    cuuint64_t gd[2] = {(cuuint64_t)cols, (cuuint64_t)rows};
    cuuint64_t gs[1] = {(cuuint64_t)cols * 2};
    cuuint32_t bd[2] = {(cuuint32_t)box_cols, (cuuint32_t)box_rows};
    cuuint32_t es[2] = {1, 1};
    enc(&m, CU_TENSOR_MAP_DATA_TYPE_BFLOAT16, 2, const_cast<void*>(ptr), gd, gs, bd, es, CU_TENSOR_MAP_INTERLEAVE_NONE,
        swz, CU_TENSOR_MAP_L2_PROMOTION_L2_128B, CU_TENSOR_MAP_FLOAT_OOB_FILL_NONE);
    return m;
}

}

extern "C" void kernel_launch(void* const* d_in, const int* in_sizes, int n_in, void* d_out, int out_size) {
    (void)in_sizes; (void)n_in; (void)out_size;
    const __nv_bfloat16* x = (const __nv_bfloat16*)d_in[0];
    const __nv_bfloat16* wqkv = (const __nv_bfloat16*)d_in[1];
    const __nv_bfloat16* wo = (const __nv_bfloat16*)d_in[2];
    const __nv_bfloat16* w1 = (const __nv_bfloat16*)d_in[4];
    const __nv_bfloat16* b1 = (const __nv_bfloat16*)d_in[5];
    const __nv_bfloat16* w2 = (const __nv_bfloat16*)d_in[6];
    const __nv_bfloat16* b2 = (const __nv_bfloat16*)d_in[7];
    __nv_bfloat16* out = (__nv_bfloat16*)d_out;

    static EncodeTiledFn enc = nullptr;
    static void *p_h, *p_o;
    if (!enc) {
        cudaDriverEntryPointQueryResult qr;
        cudaGetDriverEntryPoint("cuTensorMapEncodeTiled", (void**)&enc, cudaEnableDefault, &qr);
        cudaGetSymbolAddress(&p_h, g_h);
        cudaGetSymbolAddress(&p_o, g_o);
        cudaFuncSetAttribute(k_fused, cudaFuncAttributeMaxDynamicSharedMemorySize, SM_TOTAL);
    }
    Maps tm;
    tm.x = make_map(enc, x, SEQ, DM, 128, 64, CU_TENSOR_MAP_SWIZZLE_128B);
    tm.wqkv = make_map(enc, wqkv, DM, 3 * DM, 32, 64, CU_TENSOR_MAP_SWIZZLE_128B);
    tm.w1 = make_map(enc, w1, DM, FF, 32, 64, CU_TENSOR_MAP_SWIZZLE_128B);
    tm.h = make_map(enc, p_h, SEQ, FF, 64, 64, CU_TENSOR_MAP_SWIZZLE_128B);
    tm.o = make_map(enc, p_o, SEQ, DM, 64, 64, CU_TENSOR_MAP_SWIZZLE_128B);
    tm.wo = make_map(enc, wo, DM, DM, 64, 32, CU_TENSOR_MAP_SWIZZLE_64B);
    tm.w2 = make_map(enc, w2, FF, DM, 64, 32, CU_TENSOR_MAP_SWIZZLE_64B);
    k_fused<<<128, 512, SM_TOTAL, cudaStreamPerThread>>>(tm, x, (const uint8_t*)wqkv, (const uint8_t*)w1, (const uint8_t*)w2,
                                                         (const uint8_t*)wo, b1, b2, out);
}
```

```cpp
#include <cuda_runtime.h>
#include <cuda_bf16.h>
#include <cuda.h>
#include <stdint.h>

namespace {

constexpr int SEQ = 2048, DM = 640, FF = 1536;
constexpr float LN_EPS = 1e-5f;

constexpr int IMG_BYTES = 256 * 384;
constexpr uint32_t EMU_MASK = 0xD5D5u;
constexpr float SAFE_BOUND = 80.0f;
#define PACE_NS 200
constexpr float QSCALE = 0.22360679774997896f * 1.4426950408889634f;

__device__ float4 g_stat[SEQ];
__device__ float2 g_csp[16 * 1728];
__device__ __align__(1024) uint8_t g_img[96 * IMG_BYTES + 1024];
__device__ float g_nrm[64 * SEQ];
__device__ __align__(1024) __nv_bfloat16 g_h[SEQ * FF];
__device__ __align__(1024) __nv_bfloat16 g_o[SEQ * DM];
constexpr int CNT_ST = 0, CNT_QKV = 16, CNT_H = 24, CNT_O = 40, CNT_CS = 44, CNT_CS2 = 52;
__device__ uint32_t g_cnt[60 * 32];
__device__ uint32_t g_epoch;

#define TL(kern, slot) do { } while (0)
#define IT(row, i) do { } while (0)

__device__ __forceinline__ uint32_t smem_u32(const void* p) { return (uint32_t)__cvta_generic_to_shared(p); }
__device__ __forceinline__ void mbar_init(uint32_t bar, int cnt) {
    asm volatile("mbarrier.init.shared::cta.b64 [%0], %1;" ::"r"(bar), "r"(cnt));
}
__device__ __forceinline__ void mbar_expect_tx(uint32_t bar, uint32_t bytes) {
    asm volatile("mbarrier.arrive.expect_tx.shared::cta.b64 _, [%0], %1;" ::"r"(bar), "r"(bytes) : "memory");
}
__device__ __forceinline__ void mbar_wait(uint32_t bar, uint32_t parity) {
    asm volatile("{\n.reg .pred p;\n.reg .u32 n;\nmov.u32 n, 0;\n"
                 "WAIT_LOOP:\nmbarrier.try_wait.parity.shared::cta.b64 p, [%0], %1;\n@p bra WAIT_DONE;\n"
                 "add.u32 n, n, 1;\nsetp.lt.u32 p, n, 4194304;\n@p bra WAIT_LOOP;\nWAIT_DONE:\n}"
                 ::"r"(bar), "r"(parity) : "memory");
}
__device__ __forceinline__ void mbar_arrive(uint32_t bar) {
    asm volatile("mbarrier.arrive.shared::cta.b64 _, [%0];" ::"r"(bar) : "memory");
}
__device__ __forceinline__ void mbar_arrive_cluster(uint32_t bar, uint32_t cta) {
    asm volatile("{\n.reg .b32 ra;\nmapa.shared::cluster.u32 ra, %0, %1;\n"
                 "mbarrier.arrive.shared::cluster.b64 _, [ra];\n}" ::"r"(bar), "r"(cta) : "memory");
}
__device__ __forceinline__ void fence_barrier_init() { asm volatile("fence.mbarrier_init.release.cluster;" ::: "memory"); }
__device__ __forceinline__ void fence_proxy_async() { asm volatile("fence.proxy.async.shared::cta;" ::: "memory"); }
__device__ __forceinline__ void cluster_sync() {
    asm volatile("barrier.cluster.arrive.release.aligned;\nbarrier.cluster.wait.acquire.aligned;" ::: "memory");
}
__device__ __forceinline__ bool elect_one() {
    uint32_t pred;
    asm volatile("{\n.reg .pred p;\nelect.sync _|p, 0xFFFFFFFF;\nselp.b32 %0, 1, 0, p;\n}" : "=r"(pred));
    return pred != 0;
}
__device__ __forceinline__ void pdl_launch() { asm volatile("griddepcontrol.launch_dependents;" ::: "memory"); }
__device__ __forceinline__ void pdl_wait() { asm volatile("griddepcontrol.wait;" ::: "memory"); }
__device__ __forceinline__ void prefetch_map(const CUtensorMap* m) {
    asm volatile("prefetch.tensormap [%0];" ::"l"(m) : "memory");
}
__device__ __forceinline__ void tma_load(uint32_t dst, const CUtensorMap* m, int c0, int c1, uint32_t bar) {
    asm volatile("cp.async.bulk.tensor.2d.shared::cluster.global.mbarrier::complete_tx::bytes [%0], [%1, {%3, %4}], [%2];"
                 ::"r"(dst), "l"(m), "r"(bar), "r"(c0), "r"(c1) : "memory");
}
__device__ __forceinline__ void tma_load_mc(uint32_t dst, const CUtensorMap* m, int c0, int c1, uint32_t bar, uint16_t mask) {
    asm volatile("cp.async.bulk.tensor.2d.shared::cluster.global.mbarrier::complete_tx::bytes.multicast::cluster"
                 " [%0], [%1, {%3, %4}], [%2], %5;"
                 ::"r"(dst), "l"(m), "r"(bar), "r"(c0), "r"(c1), "h"(mask) : "memory");
}
__device__ __forceinline__ void tma_store(const CUtensorMap* m, uint32_t src, int c0, int c1) {
    asm volatile("cp.async.bulk.tensor.2d.global.shared::cta.bulk_group [%0, {%2, %3}], [%1];"
                 ::"l"(m), "r"(src), "r"(c0), "r"(c1) : "memory");
}
__device__ __forceinline__ void bulk_commit() { asm volatile("cp.async.bulk.commit_group;" ::: "memory"); }
__device__ __forceinline__ void bulk_wait_all() { asm volatile("cp.async.bulk.wait_group 0;" ::: "memory"); }
__device__ __forceinline__ void bulk_load(uint32_t dst, const void* src, uint32_t bytes, uint32_t bar) {
    asm volatile("cp.async.bulk.shared::cluster.global.mbarrier::complete_tx::bytes [%0], [%1], %2, [%3];"
                 ::"r"(dst), "l"(src), "r"(bytes), "r"(bar) : "memory");
}
__device__ __forceinline__ void prefetch_l2(const void* p, uint32_t bytes) {
    asm volatile("cp.async.bulk.prefetch.L2.global [%0], %1;" ::"l"(p), "r"(bytes) : "memory");
}
__device__ __forceinline__ void tma_prefetch_l2(const CUtensorMap* m, int c0, int c1) {
    asm volatile("cp.async.bulk.prefetch.tensor.2d.L2.global.tile [%0, {%1, %2}];" ::"l"(m), "r"(c0), "r"(c1) : "memory");
}
__device__ __forceinline__ void wg_fence() { asm volatile("wgmma.fence.sync.aligned;" ::: "memory"); }
__device__ __forceinline__ void wg_commit() { asm volatile("wgmma.commit_group.sync.aligned;" ::: "memory"); }
template <int N> __device__ __forceinline__ void wg_wait() {
    asm volatile("wgmma.wait_group.sync.aligned %0;" ::"n"(N) : "memory");
}
template <int N> __device__ __forceinline__ void reg_alloc() { asm volatile("setmaxnreg.inc.sync.aligned.u32 %0;" ::"n"(N)); }
template <int N> __device__ __forceinline__ void reg_dealloc() { asm volatile("setmaxnreg.dec.sync.aligned.u32 %0;" ::"n"(N)); }
template <int N> __device__ __forceinline__ void fence_regs(float (&d)[N]) {
#pragma unroll
    for (int i = 0; i < N; i++) asm volatile("" : "+f"(d[i])::"memory");
}
__device__ __forceinline__ uint64_t make_desc(uint32_t addr, uint32_t lbo, uint32_t sbo, uint32_t swz) {
    return (uint64_t)((addr & 0x3FFFF) >> 4) | ((uint64_t)(lbo >> 4) << 16) | ((uint64_t)(sbo >> 4) << 32) |
           ((uint64_t)swz << 62);
}
__device__ __forceinline__ uint32_t pack_bf16(float lo, float hi) {
    uint32_t r;
    asm("cvt.rn.bf16x2.f32 %0, %1, %2;" : "=r"(r) : "f"(hi), "f"(lo));
    return r;
}
__device__ __forceinline__ float ex2(float x) {
    float r;
    asm("ex2.approx.ftz.f32 %0, %1;" : "=f"(r) : "f"(x));
    return r;
}
__device__ __forceinline__ float bf_lo(uint32_t v) { return __uint_as_float(v << 16); }
__device__ __forceinline__ float bf_hi(uint32_t v) { return __uint_as_float(v & 0xFFFF0000u); }
__device__ __forceinline__ void stmatrix_x4(uint32_t addr, uint32_t r0, uint32_t r1, uint32_t r2, uint32_t r3) {
    asm volatile("stmatrix.sync.aligned.m8n8.x4.shared.b16 [%0], {%1, %2, %3, %4};"
                 ::"r"(addr), "r"(r0), "r"(r1), "r"(r2), "r"(r3) : "memory");
}

__device__ __forceinline__ void wgmma_n120_ss_tb(float (&d)[60], uint64_t descA, uint64_t descB, int scaleD) {
    asm volatile("{\n.reg .pred p;\nsetp.ne.b32 p, %62, 0;\n"
        "wgmma.mma_async.sync.aligned.m64n120k16.f32.bf16.bf16 {"
        "%0, %1, %2, %3, %4, %5, %6, %7, %8, %9, %10, %11, %12, %13, %14, %15, "
        "%16, %17, %18, %19, %20, %21, %22, %23, %24, %25, %26, %27, %28, %29, %30, %31, "
        "%32, %33, %34, %35, %36, %37, %38, %39, %40, %41, %42, %43, %44, %45, %46, %47, "
        "%48, %49, %50, %51, %52, %53, %54, %55, %56, %57, %58, %59}, "
        "%60, %61, p, 1, 1, 0, 1;\n}\n"
        : "+f"(d[0]), "+f"(d[1]), "+f"(d[2]), "+f"(d[3]), "+f"(d[4]), "+f"(d[5]), "+f"(d[6]), "+f"(d[7]),
          "+f"(d[8]), "+f"(d[9]), "+f"(d[10]), "+f"(d[11]), "+f"(d[12]), "+f"(d[13]), "+f"(d[14]), "+f"(d[15]),
          "+f"(d[16]), "+f"(d[17]), "+f"(d[18]), "+f"(d[19]), "+f"(d[20]), "+f"(d[21]), "+f"(d[22]), "+f"(d[23]),
          "+f"(d[24]), "+f"(d[25]), "+f"(d[26]), "+f"(d[27]), "+f"(d[28]), "+f"(d[29]), "+f"(d[30]), "+f"(d[31]),
          "+f"(d[32]), "+f"(d[33]), "+f"(d[34]), "+f"(d[35]), "+f"(d[36]), "+f"(d[37]), "+f"(d[38]), "+f"(d[39]),
          "+f"(d[40]), "+f"(d[41]), "+f"(d[42]), "+f"(d[43]), "+f"(d[44]), "+f"(d[45]), "+f"(d[46]), "+f"(d[47]),
          "+f"(d[48]), "+f"(d[49]), "+f"(d[50]), "+f"(d[51]), "+f"(d[52]), "+f"(d[53]), "+f"(d[54]), "+f"(d[55]),
          "+f"(d[56]), "+f"(d[57]), "+f"(d[58]), "+f"(d[59])
        : "l"(descA), "l"(descB), "r"(scaleD));
}

__device__ __forceinline__ void wgmma_n192_ss_tb(float (&d)[96], uint64_t descA, uint64_t descB, int scaleD) {
    asm volatile("{\n.reg .pred p;\nsetp.ne.b32 p, %98, 0;\n"
        "wgmma.mma_async.sync.aligned.m64n192k16.f32.bf16.bf16 {"
        "%0, %1, %2, %3, %4, %5, %6, %7, %8, %9, %10, %11, %12, %13, %14, %15, "
        "%16, %17, %18, %19, %20, %21, %22, %23, %24, %25, %26, %27, %28, %29, %30, %31, "
        "%32, %33, %34, %35, %36, %37, %38, %39, %40, %41, %42, %43, %44, %45, %46, %47, "
        "%48, %49, %50, %51, %52, %53, %54, %55, %56, %57, %58, %59, %60, %61, %62, %63, "
        "%64, %65, %66, %67, %68, %69, %70, %71, %72, %73, %74, %75, %76, %77, %78, %79, "
        "%80, %81, %82, %83, %84, %85, %86, %87, %88, %89, %90, %91, %92, %93, %94, %95}, "
        "%96, %97, p, 1, 1, 0, 1;\n}\n"
        : "+f"(d[0]), "+f"(d[1]), "+f"(d[2]), "+f"(d[3]), "+f"(d[4]), "+f"(d[5]), "+f"(d[6]), "+f"(d[7]),
          "+f"(d[8]), "+f"(d[9]), "+f"(d[10]), "+f"(d[11]), "+f"(d[12]), "+f"(d[13]), "+f"(d[14]), "+f"(d[15]),
          "+f"(d[16]), "+f"(d[17]), "+f"(d[18]), "+f"(d[19]), "+f"(d[20]), "+f"(d[21]), "+f"(d[22]), "+f"(d[23]),
          "+f"(d[24]), "+f"(d[25]), "+f"(d[26]), "+f"(d[27]), "+f"(d[28]), "+f"(d[29]), "+f"(d[30]), "+f"(d[31]),
          "+f"(d[32]), "+f"(d[33]), "+f"(d[34]), "+f"(d[35]), "+f"(d[36]), "+f"(d[37]), "+f"(d[38]), "+f"(d[39]),
          "+f"(d[40]), "+f"(d[41]), "+f"(d[42]), "+f"(d[43]), "+f"(d[44]), "+f"(d[45]), "+f"(d[46]), "+f"(d[47]),
          "+f"(d[48]), "+f"(d[49]), "+f"(d[50]), "+f"(d[51]), "+f"(d[52]), "+f"(d[53]), "+f"(d[54]), "+f"(d[55]),
          "+f"(d[56]), "+f"(d[57]), "+f"(d[58]), "+f"(d[59]), "+f"(d[60]), "+f"(d[61]), "+f"(d[62]), "+f"(d[63]),
          "+f"(d[64]), "+f"(d[65]), "+f"(d[66]), "+f"(d[67]), "+f"(d[68]), "+f"(d[69]), "+f"(d[70]), "+f"(d[71]),
          "+f"(d[72]), "+f"(d[73]), "+f"(d[74]), "+f"(d[75]), "+f"(d[76]), "+f"(d[77]), "+f"(d[78]), "+f"(d[79]),
          "+f"(d[80]), "+f"(d[81]), "+f"(d[82]), "+f"(d[83]), "+f"(d[84]), "+f"(d[85]), "+f"(d[86]), "+f"(d[87]),
          "+f"(d[88]), "+f"(d[89]), "+f"(d[90]), "+f"(d[91]), "+f"(d[92]), "+f"(d[93]), "+f"(d[94]), "+f"(d[95])
        : "l"(descA), "l"(descB), "r"(scaleD));
}

__device__ __forceinline__ void wgmma_n192_ss_tb_z(float (&d)[96], uint64_t descA, uint64_t descB) {
    asm volatile("{\n.reg .pred p;\nsetp.ne.b32 p, 0, 0;\n"
        "wgmma.mma_async.sync.aligned.m64n192k16.f32.bf16.bf16 {"
        "%0, %1, %2, %3, %4, %5, %6, %7, %8, %9, %10, %11, %12, %13, %14, %15, "
        "%16, %17, %18, %19, %20, %21, %22, %23, %24, %25, %26, %27, %28, %29, %30, %31, "
        "%32, %33, %34, %35, %36, %37, %38, %39, %40, %41, %42, %43, %44, %45, %46, %47, "
        "%48, %49, %50, %51, %52, %53, %54, %55, %56, %57, %58, %59, %60, %61, %62, %63, "
        "%64, %65, %66, %67, %68, %69, %70, %71, %72, %73, %74, %75, %76, %77, %78, %79, "
        "%80, %81, %82, %83, %84, %85, %86, %87, %88, %89, %90, %91, %92, %93, %94, %95}, "
        "%96, %97, p, 1, 1, 0, 1;\n}\n"
        : "=f"(d[0]), "=f"(d[1]), "=f"(d[2]), "=f"(d[3]), "=f"(d[4]), "=f"(d[5]), "=f"(d[6]), "=f"(d[7]),
          "=f"(d[8]), "=f"(d[9]), "=f"(d[10]), "=f"(d[11]), "=f"(d[12]), "=f"(d[13]), "=f"(d[14]), "=f"(d[15]),
          "=f"(d[16]), "=f"(d[17]), "=f"(d[18]), "=f"(d[19]), "=f"(d[20]), "=f"(d[21]), "=f"(d[22]), "=f"(d[23]),
          "=f"(d[24]), "=f"(d[25]), "=f"(d[26]), "=f"(d[27]), "=f"(d[28]), "=f"(d[29]), "=f"(d[30]), "=f"(d[31]),
          "=f"(d[32]), "=f"(d[33]), "=f"(d[34]), "=f"(d[35]), "=f"(d[36]), "=f"(d[37]), "=f"(d[38]), "=f"(d[39]),
          "=f"(d[40]), "=f"(d[41]), "=f"(d[42]), "=f"(d[43]), "=f"(d[44]), "=f"(d[45]), "=f"(d[46]), "=f"(d[47]),
          "=f"(d[48]), "=f"(d[49]), "=f"(d[50]), "=f"(d[51]), "=f"(d[52]), "=f"(d[53]), "=f"(d[54]), "=f"(d[55]),
          "=f"(d[56]), "=f"(d[57]), "=f"(d[58]), "=f"(d[59]), "=f"(d[60]), "=f"(d[61]), "=f"(d[62]), "=f"(d[63]),
          "=f"(d[64]), "=f"(d[65]), "=f"(d[66]), "=f"(d[67]), "=f"(d[68]), "=f"(d[69]), "=f"(d[70]), "=f"(d[71]),
          "=f"(d[72]), "=f"(d[73]), "=f"(d[74]), "=f"(d[75]), "=f"(d[76]), "=f"(d[77]), "=f"(d[78]), "=f"(d[79]),
          "=f"(d[80]), "=f"(d[81]), "=f"(d[82]), "=f"(d[83]), "=f"(d[84]), "=f"(d[85]), "=f"(d[86]), "=f"(d[87]),
          "=f"(d[88]), "=f"(d[89]), "=f"(d[90]), "=f"(d[91]), "=f"(d[92]), "=f"(d[93]), "=f"(d[94]), "=f"(d[95])
        : "l"(descA), "l"(descB));
}

__device__ __forceinline__ void wgmma_n160_ss_tb(float (&d)[80], uint64_t descA, uint64_t descB, int scaleD) {
    asm volatile("{\n.reg .pred p;\nsetp.ne.b32 p, %82, 0;\n"
        "wgmma.mma_async.sync.aligned.m64n160k16.f32.bf16.bf16 {"
        "%0, %1, %2, %3, %4, %5, %6, %7, %8, %9, %10, %11, %12, %13, %14, %15, "
        "%16, %17, %18, %19, %20, %21, %22, %23, %24, %25, %26, %27, %28, %29, %30, %31, "
        "%32, %33, %34, %35, %36, %37, %38, %39, %40, %41, %42, %43, %44, %45, %46, %47, "
        "%48, %49, %50, %51, %52, %53, %54, %55, %56, %57, %58, %59, %60, %61, %62, %63, "
        "%64, %65, %66, %67, %68, %69, %70, %71, %72, %73, %74, %75, %76, %77, %78, %79}, "
        "%80, %81, p, 1, 1, 0, 1;\n}\n"
        : "+f"(d[0]), "+f"(d[1]), "+f"(d[2]), "+f"(d[3]), "+f"(d[4]), "+f"(d[5]), "+f"(d[6]), "+f"(d[7]),
          "+f"(d[8]), "+f"(d[9]), "+f"(d[10]), "+f"(d[11]), "+f"(d[12]), "+f"(d[13]), "+f"(d[14]), "+f"(d[15]),
          "+f"(d[16]), "+f"(d[17]), "+f"(d[18]), "+f"(d[19]), "+f"(d[20]), "+f"(d[21]), "+f"(d[22]), "+f"(d[23]),
          "+f"(d[24]), "+f"(d[25]), "+f"(d[26]), "+f"(d[27]), "+f"(d[28]), "+f"(d[29]), "+f"(d[30]), "+f"(d[31]),
          "+f"(d[32]), "+f"(d[33]), "+f"(d[34]), "+f"(d[35]), "+f"(d[36]), "+f"(d[37]), "+f"(d[38]), "+f"(d[39]),
          "+f"(d[40]), "+f"(d[41]), "+f"(d[42]), "+f"(d[43]), "+f"(d[44]), "+f"(d[45]), "+f"(d[46]), "+f"(d[47]),
          "+f"(d[48]), "+f"(d[49]), "+f"(d[50]), "+f"(d[51]), "+f"(d[52]), "+f"(d[53]), "+f"(d[54]), "+f"(d[55]),
          "+f"(d[56]), "+f"(d[57]), "+f"(d[58]), "+f"(d[59]), "+f"(d[60]), "+f"(d[61]), "+f"(d[62]), "+f"(d[63]),
          "+f"(d[64]), "+f"(d[65]), "+f"(d[66]), "+f"(d[67]), "+f"(d[68]), "+f"(d[69]), "+f"(d[70]), "+f"(d[71]),
          "+f"(d[72]), "+f"(d[73]), "+f"(d[74]), "+f"(d[75]), "+f"(d[76]), "+f"(d[77]), "+f"(d[78]), "+f"(d[79])
        : "l"(descA), "l"(descB), "r"(scaleD));
}

__device__ __forceinline__ void wgmma_n64_ss(float (&d)[32], uint64_t descA, uint64_t descB, int scaleD) {
    asm volatile("{\n.reg .pred p;\nsetp.ne.b32 p, %34, 0;\n"
        "wgmma.mma_async.sync.aligned.m64n64k16.f32.bf16.bf16 {"
        "%0, %1, %2, %3, %4, %5, %6, %7, %8, %9, %10, %11, %12, %13, %14, %15, "
        "%16, %17, %18, %19, %20, %21, %22, %23, %24, %25, %26, %27, %28, %29, %30, %31}, "
        "%32, %33, p, 1, 1, 0, 0;\n}\n"
        : "+f"(d[0]), "+f"(d[1]), "+f"(d[2]), "+f"(d[3]), "+f"(d[4]), "+f"(d[5]), "+f"(d[6]), "+f"(d[7]),
          "+f"(d[8]), "+f"(d[9]), "+f"(d[10]), "+f"(d[11]), "+f"(d[12]), "+f"(d[13]), "+f"(d[14]), "+f"(d[15]),
          "+f"(d[16]), "+f"(d[17]), "+f"(d[18]), "+f"(d[19]), "+f"(d[20]), "+f"(d[21]), "+f"(d[22]), "+f"(d[23]),
          "+f"(d[24]), "+f"(d[25]), "+f"(d[26]), "+f"(d[27]), "+f"(d[28]), "+f"(d[29]), "+f"(d[30]), "+f"(d[31])
        : "l"(descA), "l"(descB), "r"(scaleD));
}

__device__ __forceinline__ void wgmma_n64_ss_z(float (&d)[32], uint64_t descA, uint64_t descB) {
    asm volatile("{\n.reg .pred p;\nsetp.ne.b32 p, 0, 0;\n"
        "wgmma.mma_async.sync.aligned.m64n64k16.f32.bf16.bf16 {"
        "%0, %1, %2, %3, %4, %5, %6, %7, %8, %9, %10, %11, %12, %13, %14, %15, "
        "%16, %17, %18, %19, %20, %21, %22, %23, %24, %25, %26, %27, %28, %29, %30, %31}, "
        "%32, %33, p, 1, 1, 0, 0;\n}\n"
        : "=f"(d[0]), "=f"(d[1]), "=f"(d[2]), "=f"(d[3]), "=f"(d[4]), "=f"(d[5]), "=f"(d[6]), "=f"(d[7]),
          "=f"(d[8]), "=f"(d[9]), "=f"(d[10]), "=f"(d[11]), "=f"(d[12]), "=f"(d[13]), "=f"(d[14]), "=f"(d[15]),
          "=f"(d[16]), "=f"(d[17]), "=f"(d[18]), "=f"(d[19]), "=f"(d[20]), "=f"(d[21]), "=f"(d[22]), "=f"(d[23]),
          "=f"(d[24]), "=f"(d[25]), "=f"(d[26]), "=f"(d[27]), "=f"(d[28]), "=f"(d[29]), "=f"(d[30]), "=f"(d[31])
        : "l"(descA), "l"(descB));
}

__device__ __forceinline__ void wgmma_n24_rs_tb(float (&d)[12], uint32_t a0, uint32_t a1, uint32_t a2, uint32_t a3, uint64_t descB, int scaleD) {
    asm volatile("{\n.reg .pred p;\nsetp.ne.b32 p, %17, 0;\n"
        "wgmma.mma_async.sync.aligned.m64n24k16.f32.bf16.bf16 {"
        "%0, %1, %2, %3, %4, %5, %6, %7, %8, %9, %10, %11}, "
        "{%12, %13, %14, %15}, %16, p, 1, 1, 1;\n}\n"
        : "+f"(d[0]), "+f"(d[1]), "+f"(d[2]), "+f"(d[3]), "+f"(d[4]), "+f"(d[5]), "+f"(d[6]), "+f"(d[7]),
          "+f"(d[8]), "+f"(d[9]), "+f"(d[10]), "+f"(d[11])
        : "r"(a0), "r"(a1), "r"(a2), "r"(a3), "l"(descB), "r"(scaleD));
}

__device__ __forceinline__ void cnt_signal(int idx) {
    asm volatile("fence.acq_rel.gpu;\nred.relaxed.gpu.global.add.u32 [%0], 1;"
                 ::"l"(g_cnt + idx * 32) : "memory");
}
__device__ __forceinline__ void cnt_wait(int idx, uint32_t target) {
    const uint32_t* p = g_cnt + idx * 32;
#pragma unroll 1
    for (uint32_t i = 0; i < (1u << 22); i++) {
        uint32_t v;
        asm volatile("ld.acquire.gpu.global.u32 %0, [%1];" : "=r"(v) : "l"(p) : "memory");
        if ((int32_t)(v - target) >= 0) break;
    }
    asm volatile("fence.proxy.async.global;" ::: "memory");
}
__device__ __forceinline__ void cluster_arrive() { asm volatile("barrier.cluster.arrive.release.aligned;" ::: "memory"); }
__device__ __forceinline__ void cluster_arrive_relaxed() { asm volatile("barrier.cluster.arrive.relaxed.aligned;" ::: "memory"); }
__device__ __forceinline__ void cluster_wait() { asm volatile("barrier.cluster.wait.acquire.aligned;" ::: "memory"); }
__device__ __forceinline__ void bulk_wait_read() { asm volatile("cp.async.bulk.wait_group.read 0;" ::: "memory"); }

__device__ __forceinline__ float gelu_tanh(float x) {
    const float u = x * (0.7978845608028654f + 0.035677408136300125f * x * x);
    float t;
    asm("tanh.approx.f32 %0, %1;" : "=f"(t) : "f"(u));
    const float h = 0.5f * x;
    return fmaf(h, t, h);
}
__device__ __forceinline__ void release_stage(uint32_t bar, uint32_t peer, int lane) {
    if (lane == 0) { mbar_arrive(bar); mbar_arrive_cluster(bar, peer); }
}

constexpr int SM_RING = 163840;
constexpr int SM_Q = 2 * IMG_BYTES, SM_ZERO = SM_Q + 24576;
constexpr int G2_STAGE = 8192 + 20480;
constexpr int SM_MISC = 229376;
constexpr int SM_BIAS = SM_MISC, SM_RED = SM_BIAS + 384, SM_BAR = SM_RED + 128;
constexpr int B_A = 0, B_F1 = 10, B_E1 = 14, B_F2 = 18, B_E2 = 23, B_KV = 28, B_Q = 45, B_F3 = 47, B_E3 = 55, B_ST = 63, B_STAT = 65, B_AUX = 66, B_AUX2 = 67, B_COUNT = 68;
constexpr int SM_EPOCH = SM_BAR + 544;
constexpr int SM_CS = SM_EPOCH + 16;
constexpr int SM_DBG = SM_CS + 1728;
constexpr int SM_TOTAL = SM_DBG + 64;
static_assert(SM_TOTAL <= 232448, "shared memory budget");

struct Maps { CUtensorMap x, wqkv, w1, h, o, wo, w2; };

__device__ __forceinline__ uint32_t bf2_fma(uint32_t a, uint32_t b, uint32_t c) {
    uint32_t r;
    asm("fma.rn.bf16x2 %0, %1, %2, %3;" : "=r"(r) : "r"(a), "r"(b), "r"(c));
    return r;
}
__device__ __forceinline__ uint32_t lop_and_or(uint32_t a, uint32_t m, uint32_t o) {
    uint32_t r;
    asm("lop3.b32 %0, %1, %2, %3, 0xEA;" : "=r"(r) : "r"(a), "r"(m), "r"(o));
    return r;
}
struct ExpConst { uint32_t mask, slope; };
__device__ __forceinline__ ExpConst make_exp_const() {
    ExpConst k;
    asm volatile("mov.b32 %0, 0x007F007F;" : "=r"(k.mask));
    asm volatile("mov.b32 %0, 0x3EF83EF8;" : "=r"(k.slope));
    return k;
}
__device__ __forceinline__ uint32_t exp2_pair_fma(float t0, float t1, const ExpConst& k) {
    const uint32_t L = __byte_perm(__float_as_uint(t0), __float_as_uint(t1), 0x6521);
    const uint32_t g = lop_and_or(L, k.mask, 0x3F803F80u);
    const uint32_t u = bf2_fma(g, k.slope, 0xBF37BF37u);
    const uint32_t e = bf2_fma(u, u, 0xBD71BD71u);
    return bf2_fma(L, e, L);
}
template <int SHIFT>
__device__ __forceinline__ void exp_tile(const float (&s)[32], uint32_t (&p)[16], const ExpConst& k) {
#pragma unroll
    for (int b = 0; b < 8; b++) {
        if ((EMU_MASK >> (b + SHIFT)) & 1) {
            p[2 * b] = exp2_pair_fma(s[4 * b], s[4 * b + 1], k);
            p[2 * b + 1] = exp2_pair_fma(s[4 * b + 2], s[4 * b + 3], k);
        } else {
            p[2 * b] = pack_bf16(ex2(s[4 * b]), ex2(s[4 * b + 1]));
            p[2 * b + 1] = pack_bf16(ex2(s[4 * b + 2]), ex2(s[4 * b + 3]));
        }
    }
}

__device__ __forceinline__ void qk_tile(float (&s)[32], uint64_t dQ, uint64_t dQ2, uint64_t dK) {
    wg_fence();
    wgmma_n64_ss_z(s, dQ, dK);
    wgmma_n64_ss(s, dQ2, dK + 16, 1);
    wg_commit();
}
__device__ __forceinline__ void pv_tile(float (&o)[12], const uint32_t (&p)[16], uint64_t dV) {
    wg_fence();
#pragma unroll
    for (int ks = 0; ks < 4; ks++)
        wgmma_n24_rs_tb(o, p[4 * ks], p[4 * ks + 1], p[4 * ks + 2], p[4 * ks + 3], dV + ks * 48, 1);
    wg_commit();
}
__device__ __forceinline__ void store_o(const float (&o)[12], int h, int rbase, int lane) {
    const int g = lane >> 2, c = lane & 3;
    const bool odd = h & 1;
    const int lsrc = (lane & ~3) | (odd ? 0 : 2);
    const float i0 = 1.f / __shfl_sync(~0u, o[8], lsrc), i1 = 1.f / __shfl_sync(~0u, o[10], lsrc);
    __nv_bfloat16* dst = g_o + (size_t)(rbase + g) * DM + h * 20;
    const int d0 = (odd ? 4 : 0) + 2 * c, d1 = d0 + 8, d2 = odd ? 2 * c - 4 : 16 + 2 * c;
    *(uint32_t*)(dst + d0) = pack_bf16(o[0] * i0, o[1] * i0);
    *(uint32_t*)(dst + d1) = pack_bf16(o[4] * i0, o[5] * i0);
    *(uint32_t*)(dst + 8 * DM + d0) = pack_bf16(o[2] * i1, o[3] * i1);
    *(uint32_t*)(dst + 8 * DM + d1) = pack_bf16(o[6] * i1, o[7] * i1);
    if (odd ? (c >= 2) : (c < 2)) {
        *(uint32_t*)(dst + d2) = pack_bf16(o[8] * i0, o[9] * i0);
        *(uint32_t*)(dst + 8 * DM + d2) = pack_bf16(o[10] * i1, o[11] * i1);
    }
}

__device__ __forceinline__ void attn_rows_maxshift(uint32_t sK, uint32_t barKV, uint64_t dQ, uint64_t dQ2, int h, int rbase) {
    const int lane = threadIdx.x & 31;
    const uint64_t dK0 = make_desc(sK, 128, 384, 0), dV0 = make_desc(sK + IMG_BYTES, 384, 128, 0);
    float o[12], s[32];
    uint32_t p[16];
#pragma unroll
    for (int i = 0; i < 12; i++) o[i] = 0.f;
    float m0 = -3.0e38f, m1 = -3.0e38f;
    mbar_wait(barKV + 128, 0);
#pragma unroll 1
    for (int t = 0; t < 32; t++) {
        mbar_wait(barKV + (t >> 1) * 8, 0);
        qk_tile(s, dQ, dQ2, dK0 + t * 192);
        wg_wait<0>();
        fence_regs(s);
        const uint32_t mask = EMU_MASK >> ((t & 1) * 8);
        float n0 = m0, n1 = m1;
#pragma unroll
        for (int b = 0; b < 8; b++) {
            const bool emu = (mask >> b) & 1;
            const float f = emu ? 0.5f : 1.f, off = emu ? -383.00390625f : 0.f;
#pragma unroll
            for (int i = 0; i < 4; i++) s[4 * b + i] = fmaf(s[4 * b + i], f, off);
            n0 = fmaxf(n0, fmaxf(s[4 * b], s[4 * b + 1]));
            n1 = fmaxf(n1, fmaxf(s[4 * b + 2], s[4 * b + 3]));
        }
        n0 = fmaxf(n0, __shfl_xor_sync(~0u, n0, 1)); n0 = fmaxf(n0, __shfl_xor_sync(~0u, n0, 2));
        n1 = fmaxf(n1, __shfl_xor_sync(~0u, n1, 1)); n1 = fmaxf(n1, __shfl_xor_sync(~0u, n1, 2));
        const float c0 = ex2(m0 - n0), c1 = ex2(m1 - n1);
        m0 = n0; m1 = n1;
#pragma unroll
        for (int b = 0; b < 3; b++) { o[4 * b] *= c0; o[4 * b + 1] *= c0; o[4 * b + 2] *= c1; o[4 * b + 3] *= c1; }
#pragma unroll
        for (int b = 0; b < 8; b++) {
            p[2 * b] = pack_bf16(ex2(s[4 * b] - m0), ex2(s[4 * b + 1] - m0));
            p[2 * b + 1] = pack_bf16(ex2(s[4 * b + 2] - m1), ex2(s[4 * b + 3] - m1));
        }
        pv_tile(o, p, dV0 + t * 192);
        wg_wait<0>();
        fence_regs(o);
    }
    store_o(o, h, rbase, lane);
}

__global__ void __launch_bounds__(512, 1) __cluster_dims__(2, 1, 1)
k_fused(const __grid_constant__ Maps tm, const __nv_bfloat16* __restrict__ x, const uint8_t* __restrict__ wqkv,
        const uint8_t* __restrict__ w1, const uint8_t* __restrict__ w2, const uint8_t* __restrict__ wo,
        const __nv_bfloat16* __restrict__ b1, const __nv_bfloat16* __restrict__ b2, __nv_bfloat16* __restrict__ out) {
    extern __shared__ __align__(1024) uint8_t smem[];
    const uint32_t sb = smem_u32(smem);
    const uint32_t bar = sb + SM_BAR;
    const int warp = __shfl_sync(~0u, threadIdx.x >> 5, 0), lane = threadIdx.x & 31;
    const int wgi = warp >> 2, w4 = warp & 3, g = lane >> 2, c = lane & 3;
    const uint32_t rank = blockIdx.x & 1, peer = rank ^ 1;
    const int cl = blockIdx.x >> 1;
    const int cg = cl >> 3, rb = (cl & 7) * 2 + rank;

    if (threadIdx.x == 0) TL(0, 0);
    if (elect_one()) {
#pragma unroll
        for (int j = 0; j < 5; j++) {
            const int i = warp * 5 + j;
            const int cnt = (i >= B_E1 && i < B_F2) || (i >= B_E2 && i < B_KV) ? 16
                          : (i >= B_E3 && i <= B_ST) || i == B_STAT ? 8 : i == B_ST + 1 ? 2 : i >= B_AUX ? 7 : 1;
            if (i < B_COUNT) mbar_init(bar + i * 8, cnt);
        }
        fence_barrier_init();
    }
    __syncthreads();
    if (threadIdx.x == 0) TL(0, 1);
    cluster_arrive_relaxed();
    if (warp == 15 && elect_one()) {
        prefetch_map(&tm.x); prefetch_map(&tm.wqkv);
        for (int kb = 0; kb < 3; kb++) tma_prefetch_l2(&tm.x, kb * 64, rb * 128);
        for (int it = 0; it < 4; it++) {
            tma_prefetch_l2(&tm.wqkv, cg * 240 + rank * 120, it * 32);
            tma_prefetch_l2(&tm.wqkv, cg * 240 + rank * 120 + 64, it * 32);
        }
        prefetch_map(&tm.w1); prefetch_map(&tm.h);
    }
    cluster_wait();
    if (threadIdx.x == 0) TL(0, 3);

    {
        const uint32_t sB = sb + SM_RING;
        if (threadIdx.x == 0) TL(1, 0);
        if (wgi < 2) {
            reg_dealloc<40>();
            if (threadIdx.x == 0) IT(4, 0);
            if (warp == 0) {
#pragma unroll 1
                for (int it = 0; it < 20; it++) {
                    const int s = it & 3;
                    const int kb = it < 2 ? it : (it & 1) ? (it + 1) >> 1 : 10;
                    if (it >= 4) mbar_wait(bar + (B_E1 + s) * 8, ((it >> 2) - 1) & 1);
                    else if (it > 0) __nanosleep(PACE_NS);
                    if (elect_one()) {
                        if (kb < 10) {
                            mbar_expect_tx(bar + (B_A + kb) * 8, 16384);
                            tma_load(sb + kb * 16384, &tm.x, kb * 64, rb * 128, bar + (B_A + kb) * 8);
                        }
                        const uint32_t dst = sB + s * 16384 + rank * 8192, fb = bar + (B_F1 + s) * 8;
                        const int c0 = cg * 240 + rank * 120;
                        mbar_expect_tx(fb, 16384);
                        tma_load_mc(dst, &tm.wqkv, c0, it * 32, fb, 3);
                        tma_load_mc(dst + 4096, &tm.wqkv, c0 + 64, it * 32, fb, 3);
                    }
                    __syncwarp();
                    if (lane == 0 && it < 8) IT(4, 1 + it);
                }
#pragma unroll 1
                for (int it = 0; it < 20; it++) {
                    const int s = it % 5;
                    if (it < 5) { if (it != 3) mbar_wait(bar + (B_E1 + (it == 4 ? 3 : it)) * 8, 0); }
                    else mbar_wait(bar + (B_E2 + s) * 8, ((it / 5) - 1) & 1);
                    if (elect_one()) {
                        const uint32_t dst = sB + s * 12288, fb = bar + (B_F2 + s) * 8;
                        mbar_expect_tx(fb, 12288);
                        if ((it & 1) == (int)rank) {
                            tma_load_mc(dst, &tm.w1, cg * 192, it * 32, fb, 3);
                            tma_load_mc(dst + 4096, &tm.w1, cg * 192 + 64, it * 32, fb, 3);
                        } else {
                            tma_load_mc(dst + 8192, &tm.w1, cg * 192 + 128, it * 32, fb, 3);
                        }
                    }
                    __syncwarp();
                }
            } else {
                const int ht = threadIdx.x - 32;
                if (ht == 192) *reinterpret_cast<volatile uint32_t*>(smem + SM_EPOCH) = *(volatile uint32_t*)&g_epoch;
                auto slab_sum = [&](const uint32_t* src, int pitch) {
                    float s0 = 0.f, s1 = 0.f;
#pragma unroll
                    for (int h2 = 0; h2 < 2; h2++) {
                        uint32_t v[20];
#pragma unroll
                        for (int k = 0; k < 20; k++) v[k] = __ldg(src + (h2 * 20 + k) * pitch);
#pragma unroll
                        for (int k = 0; k < 20; k++) { s0 += bf_lo(v[k]); s1 += bf_hi(v[k]); }
                    }
                    return make_float2(s0, s1);
                };
                auto gather = [&](int idx) {
                    float s0 = 0.f, s1 = 0.f;
#pragma unroll
                    for (int r = 0; r < 16; r++) {
                        const float2 v = __ldcg(g_csp + r * 1728 + cg * 216 + idx);
                        s0 += v.x; s1 += v.y;
                    }
                    reinterpret_cast<float2*>(smem + SM_CS)[idx] = make_float2(s0, s1);
                };
                if (ht < 120)
                    g_csp[rb * 1728 + cg * 216 + ht] = slab_sum(reinterpret_cast<const uint32_t*>(wqkv) + rb * 40 * 960 + cg * 120 + ht, 960);
                if (threadIdx.x == 64) IT(3, 0);
                asm volatile("bar.sync 8, 224;" ::: "memory");
                const uint32_t epoch = *reinterpret_cast<volatile uint32_t*>(smem + SM_EPOCH);
                if (warp == 6) { if (elect_one()) cnt_signal(CNT_CS + cg); __syncwarp(); }
                if (warp == 7) {
                    mbar_wait(bar + B_STAT * 8, 0);
                    if (elect_one()) cnt_signal(CNT_ST + rb);
                    __syncwarp();
                }
                if (ht < 96) {
                    g_csp[rb * 1728 + cg * 216 + 120 + ht] = slab_sum(reinterpret_cast<const uint32_t*>(w1) + rb * 40 * 768 + cg * 96 + ht, 768);
                    reinterpret_cast<uint32_t*>(smem + SM_BIAS)[ht] = __ldg(reinterpret_cast<const uint32_t*>(b1 + cg * 192) + ht);
                }
                asm volatile("bar.sync 8, 224;" ::: "memory");
                if (warp == 6) { if (elect_one()) cnt_signal(CNT_CS2 + cg); __syncwarp(); }
                if (threadIdx.x == 64) IT(3, 2);
                if (lane == 0) { cnt_wait(CNT_CS + cg, (epoch + 1) * 16); cnt_wait(CNT_ST + rb, (epoch + 1) * 8); }
                __syncwarp();
                if (threadIdx.x == 64) IT(3, 4);
                if (ht < 120) gather(ht);
                __syncwarp();
                if (threadIdx.x == 64) IT(3, 5);
                if (lane == 0) mbar_arrive(bar + B_AUX * 8);
                if (warp == 3 && elect_one()) {
                    prefetch_l2(w2 + blockIdx.x * 15360, 15360);
                    prefetch_l2(wo + blockIdx.x * 6400, 6400);
                }
                if (lane == 0) cnt_wait(CNT_CS2 + cg, (epoch + 1) * 16);
                __syncwarp();
                if (ht < 96) gather(120 + ht);
                __syncwarp();
                if (lane == 0) mbar_arrive(bar + B_AUX2 * 8);
                if (warp == 4) {
                    mbar_wait(bar + B_ST * 8, 0);
                    if (elect_one()) cnt_signal(CNT_QKV + cg);
                    __syncwarp();
                }
            }
            asm volatile("bar.sync %0, 128;" ::"r"(wgi + 3) : "memory");
            reg_alloc<128>();
        } else {
            reg_alloc<216>();
            if (threadIdx.x == 256) IT(5, 0);
            const int wi = wgi - 2;
            const int row0 = rb * 128 + wi * 64 + w4 * 16 + g;
            const uint32_t sAw = sb + wi * 8192;
            const int rbk = row0 >> 3, hs0 = cg * 12;
            const int srow = rb * 128 + cg * 16 + (warp - 8) * 2 + (lane >> 4);
            uint4 xv[5];
#pragma unroll
            for (int i = 0; i < 5; i++) xv[i] = __ldg(reinterpret_cast<const uint4*>(x + (size_t)srow * DM) + (lane & 15) + 16 * i);
            if (threadIdx.x == 256) IT(5, 1);
            float acc1[2][60];
#pragma unroll 1
            for (int it = 0; it < 20; it++) {
                const int s = it & 3;
                if (!(it & 1)) mbar_wait(bar + (B_A + (it >> 1)) * 8, 0);
                if (threadIdx.x == 256 && it == 0) TL(0, 2);
                if (threadIdx.x == 256) IT(0, it);
                mbar_wait(bar + (B_F1 + s) * 8, (it >> 2) & 1);
                if (threadIdx.x == 256) IT(1, it);
                wg_fence();
                const uint64_t dA = make_desc(sAw + (it >> 1) * 16384 + (it & 1) * 64, 16, 1024, 1);
                const uint64_t dB = make_desc(sB + s * 16384, 4096, 1024, 1);
                wgmma_n120_ss_tb(acc1[0], dA, dB, it > 0);
                wgmma_n120_ss_tb(acc1[1], dA, dB + 512, it > 0);
                wgmma_n120_ss_tb(acc1[0], dA + 2, dB + 128, 1);
                wgmma_n120_ss_tb(acc1[1], dA + 2, dB + 640, 1);
                wg_commit();
                if (it > 0) { wg_wait<1>(); release_stage(bar + (B_E1 + ((it - 1) & 3)) * 8, peer, lane); }
                if (it == 5) {
                    float sm = 0.f;
#pragma unroll
                    for (int i = 0; i < 5; i++)
                        sm += (bf_lo(xv[i].x) + bf_hi(xv[i].x)) + (bf_lo(xv[i].y) + bf_hi(xv[i].y)) +
                              (bf_lo(xv[i].z) + bf_hi(xv[i].z)) + (bf_lo(xv[i].w) + bf_hi(xv[i].w));
#pragma unroll
                    for (int o = 8; o; o >>= 1) sm += __shfl_xor_sync(~0u, sm, o);
                    const float mu = sm * (1.f / DM);
                    float q = 0.f;
#pragma unroll
                    for (int i = 0; i < 5; i++) {
                        const uint32_t w[4] = {xv[i].x, xv[i].y, xv[i].z, xv[i].w};
#pragma unroll
                        for (int j = 0; j < 4; j++) {
                            const float d0 = bf_lo(w[j]) - mu, d1 = bf_hi(w[j]) - mu;
                            q = fmaf(d0, d0, fmaf(d1, d1, q));
                        }
                    }
#pragma unroll
                    for (int o = 8; o; o >>= 1) q += __shfl_xor_sync(~0u, q, o);
                    const float var = q * (1.f / DM);
                    const float r1 = 1.f / sqrtf(var + LN_EPS);
                    const float r2 = 1.f / sqrtf(var * r1 * r1 + LN_EPS);
                    if ((lane & 15) == 0) g_stat[srow] = make_float4(mu, r1, r1 * r2, 0.f);
                    __syncwarp();
                    if (lane == 0) mbar_arrive(bar + B_STAT * 8);
                }
            }
            if (threadIdx.x == 256) IT(2, 0);
            mbar_wait(bar + B_AUX * 8, 0);
            if (threadIdx.x == 256) IT(2, 1);
            const float4 st0 = __ldcg(g_stat + row0), st1 = __ldcg(g_stat + row0 + 8);
            wg_wait<0>();
            release_stage(bar + (B_E1 + 3) * 8, peer, lane);
            fence_regs(acc1[0]);
            fence_regs(acc1[1]);
            if (threadIdx.x == 256) TL(1, 1);
            const float2* cs = reinterpret_cast<const float2*>(smem + SM_CS) + c;
            uint8_t* img = g_img + (size_t)hs0 * IMG_BYTES + rbk * 384 + g * 16 + c * 4;
            const bool emu0 = (EMU_MASK >> (rbk & 15)) & 1, emu1 = (EMU_MASK >> ((rbk + 1) & 15)) & 1;
            const bool low = c < 2;
            uint32_t pk[60];
#pragma unroll
            for (int m = 0; m < 6; m++) {
                const int which = (hs0 + 2 * m) >> 5;
                const float m0 = st0.y * (which == 0 ? QSCALE : (which == 1 && emu0) ? 2.f : 1.f);
                const float m1 = st1.y * (which == 0 ? QSCALE : (which == 1 && emu1) ? 2.f : 1.f);
                const float d0 = -st0.x * m0, d1 = -st1.x * m1;
                const float* a = &acc1[m / 3][20 * (m % 3)];
#pragma unroll
                for (int b = 0; b < 5; b++) {
                    const float2 cv = cs[(5 * m + b) * 4];
                    pk[10 * m + 2 * b] = pack_bf16(fmaf(a[4 * b], m0, d0 * cv.x), fmaf(a[4 * b + 1], m0, d0 * cv.y));
                    pk[10 * m + 2 * b + 1] = pack_bf16(fmaf(a[4 * b + 2], m1, d1 * cv.x), fmaf(a[4 * b + 3], m1, d1 * cv.y));
                }
            }
            const float r20 = st0.z, r21 = st1.z, e20 = -st0.x * st0.z, e21 = -st1.x * st1.z;
            if (threadIdx.x == 256) IT(2, 2);
            float acc2[96];
#pragma unroll
            for (int it = 0; it < 20; it++) {
                const int s = it % 5;
                if (threadIdx.x == 256) IT(0, 20 + it);
                mbar_wait(bar + (B_F2 + s) * 8, (it / 5) & 1);
                if (threadIdx.x == 256) IT(1, 20 + it);
                wg_fence();
                const uint64_t dA = make_desc(sAw + (it >> 1) * 16384 + (it & 1) * 64, 16, 1024, 1);
                const uint64_t dB = make_desc(sB + s * 12288, 4096, 1024, 1);
                if (it == 0) wgmma_n192_ss_tb_z(acc2, dA, dB); else wgmma_n192_ss_tb(acc2, dA, dB, 1);
                wgmma_n192_ss_tb(acc2, dA + 2, dB + 128, 1);
                wg_commit();
                if (it > 0) {
                    wg_wait<1>();
                    if (it <= 15) release_stage(bar + (B_E2 + (it - 1) % 5) * 8, peer, lane);
                }
                if (it < 12) {
                    const int m = it / 2, part = it % 2;
                    const int hs = hs0 + 2 * m, which = hs >> 5;
                    const uint32_t* a = pk + 10 * m;
                    uint8_t* pe = img + (2 * m) * IMG_BYTES;
                    uint8_t* po = pe + IMG_BYTES;
                    if (part == 0) {
                        const uint32_t padv = which == 0 ? 0x3F803F80u : which == 1 ? 0xBFFF4440u : 0x00003F80u;
                        const uint32_t p0 = ((c & 1) || (which == 1 && !emu0)) ? 0u : padv;
                        const uint32_t p1 = ((c & 1) || (which == 1 && !emu1)) ? 0u : padv;
                        *(uint32_t*)(pe) = a[0];
                        *(uint32_t*)(pe + 128) = a[2];
                        *(uint32_t*)(pe + 256) = low ? a[4] : p0;
                        *(uint32_t*)(pe + 384) = a[1];
                        *(uint32_t*)(pe + 512) = a[3];
                        *(uint32_t*)(pe + 640) = low ? a[5] : p1;
                        *(uint32_t*)(po + 256) = low ? p0 : a[4];
                        *(uint32_t*)(po + 640) = low ? p1 : a[5];
                    } else {
                        *(uint32_t*)(po) = a[6];
                        *(uint32_t*)(po + 128) = a[8];
                        *(uint32_t*)(po + 384) = a[7];
                        *(uint32_t*)(po + 512) = a[9];
                        if (which < 2) {
                            const uint32_t u0 = bf2_fma(a[4], a[4], 0u), u1 = bf2_fma(a[5], a[5], 0u);
                            const uint32_t pe0 = bf2_fma(a[0], a[0], bf2_fma(a[2], a[2], low ? u0 : 0u));
                            const uint32_t pe1 = bf2_fma(a[1], a[1], bf2_fma(a[3], a[3], low ? u1 : 0u));
                            const uint32_t po0 = bf2_fma(a[6], a[6], bf2_fma(a[8], a[8], low ? 0u : u0));
                            const uint32_t po1 = bf2_fma(a[7], a[7], bf2_fma(a[9], a[9], low ? 0u : u1));
                            const float e0 = bf_lo(pe0) + bf_hi(pe0), e1 = bf_lo(pe1) + bf_hi(pe1);
                            const float o0 = bf_lo(po0) + bf_hi(po0), o1 = bf_lo(po1) + bf_hi(po1);
                            const bool b0 = c & 1, b1_ = c & 2;
                            const float x0 = (b0 ? e1 : e0) + __shfl_xor_sync(~0u, b0 ? e0 : e1, 1);
                            const float x1 = (b0 ? o1 : o0) + __shfl_xor_sync(~0u, b0 ? o0 : o1, 1);
                            float y = (b1_ ? x1 : x0) + __shfl_xor_sync(~0u, b1_ ? x0 : x1, 2);
                            if (which == 1 && (b0 ? emu1 : emu0)) y *= 0.25f;
                            g_nrm[(hs + (c >> 1)) * SEQ + row0 + (c & 1) * 8] = y;
                        }
                    }
                    if (it == 11) { __syncwarp(); if (lane == 0) mbar_arrive(bar + B_ST * 8); }
                }
            }
            wg_wait<0>();
            fence_regs(acc2);
            if (threadIdx.x == 256) TL(1, 2);
            mbar_wait(bar + B_AUX2 * 8, 0);
            const uint32_t* bias = reinterpret_cast<const uint32_t*>(smem + SM_BIAS) + c;
            const int mrow = w4 * 16 + (lane & 15);
            const uint32_t st_row = sAw + mrow * 128;
#pragma unroll
            for (int j = 0; j < 24; j += 2) {
                const uint32_t bA = bias[j * 4], bB = bias[j * 4 + 4];
                const float2 cA = cs[(30 + j) * 4], cB = cs[(31 + j) * 4];
                const float* a = acc2 + j * 4;
                const uint32_t r00 = pack_bf16(gelu_tanh(fmaf(a[0], r20, fmaf(e20, cA.x, bf_lo(bA)))), gelu_tanh(fmaf(a[1], r20, fmaf(e20, cA.y, bf_hi(bA)))));
                const uint32_t r10 = pack_bf16(gelu_tanh(fmaf(a[2], r21, fmaf(e21, cA.x, bf_lo(bA)))), gelu_tanh(fmaf(a[3], r21, fmaf(e21, cA.y, bf_hi(bA)))));
                const uint32_t r01 = pack_bf16(gelu_tanh(fmaf(a[4], r20, fmaf(e20, cB.x, bf_lo(bB)))), gelu_tanh(fmaf(a[5], r20, fmaf(e20, cB.y, bf_hi(bB)))));
                const uint32_t r11 = pack_bf16(gelu_tanh(fmaf(a[6], r21, fmaf(e21, cB.x, bf_lo(bB)))), gelu_tanh(fmaf(a[7], r21, fmaf(e21, cB.y, bf_hi(bB)))));
                const int chunk = (j & 7) + (lane >> 4);
                stmatrix_x4(st_row + (j >> 3) * 16384 + ((chunk ^ (mrow & 7)) << 4), r00, r10, r01, r11);
            }
            fence_proxy_async();
            asm volatile("bar.sync %0, 128;" ::"r"(wgi + 3) : "memory");
            if (w4 == 0 && lane == 0) {
#pragma unroll
                for (int b = 0; b < 3; b++) tma_store(&tm.h, sAw + b * 16384, cg * 192 + b * 64, rb * 128 + wi * 64);
                bulk_commit();
                bulk_wait_read();
            }
            __syncwarp();
            reg_dealloc<128>();
        }
        __syncthreads();
        if (threadIdx.x == 0) TL(1, 3);
    }

    {
        const uint32_t epoch = *reinterpret_cast<volatile uint32_t*>(smem + SM_EPOCH);
        const int h = blockIdx.x >> 2, qb = blockIdx.x & 3;
        const uint32_t sK = sb, sV = sb + IMG_BYTES, barKV = bar + B_KV * 8;
        if (threadIdx.x == 0) TL(2, 0);
        if (threadIdx.x < 192) *reinterpret_cast<uint4*>(smem + SM_ZERO + threadIdx.x * 16) = make_uint4(0, 0, 0, 0);
        fence_proxy_async();
        if (warp == 0) {
            if (elect_one()) {
                cnt_wait(CNT_QKV + h / 12, (epoch + 1) * 16);
                cnt_wait(CNT_QKV + (32 + h) / 12, (epoch + 1) * 16);
                cnt_wait(CNT_QKV + (64 + h) / 12, (epoch + 1) * 16);
                const uint8_t* gK = g_img + (size_t)(32 + h) * IMG_BYTES;
                const uint8_t* gV = g_img + (size_t)(64 + h) * IMG_BYTES;
                const uint8_t* gQ = g_img + (size_t)h * IMG_BYTES + qb * 64 * 384;
                mbar_expect_tx(barKV + 128, 6144);
                bulk_load(sK, gK, 6144, barKV + 128);
                for (int p = 0; p < 2; p++) {
                    mbar_expect_tx(bar + (B_Q + p) * 8, 12288);
                    bulk_load(sb + SM_Q + p * 12288, gQ + p * 12288, 12288, bar + (B_Q + p) * 8);
                }
                for (int i = 0; i < 16; i++) {
                    mbar_expect_tx(barKV + i * 8, i < 15 ? 12288 : 6144);
                    bulk_load(sV + i * 6144, gV + i * 6144, 6144, barKV + i * 8);
                    if (i < 15) bulk_load(sK + (i + 1) * 6144, gK + (i + 1) * 6144, 6144, barKV + i * 8);
                }
            }
            __syncwarp();
        }
        __syncthreads();
        if (threadIdx.x == 0) TL(2, 1);
        float* red = reinterpret_cast<float*>(smem + SM_RED);
        float kmax = 0.f, qmax = __ldcg(g_nrm + h * SEQ + qb * 512 + threadIdx.x);
#pragma unroll
        for (int i = 0; i < 4; i++) kmax = fmaxf(kmax, __ldcg(g_nrm + (32 + h) * SEQ + i * 512 + threadIdx.x));
#pragma unroll
        for (int o = 16; o; o >>= 1) {
            kmax = fmaxf(kmax, __shfl_xor_sync(~0u, kmax, o));
            qmax = fmaxf(qmax, __shfl_xor_sync(~0u, qmax, o));
        }
        if (lane == 0) { red[warp] = kmax; red[16 + warp] = qmax; }
        __syncthreads();
        kmax = red[lane & 15]; qmax = red[16 + (lane & 15)];
#pragma unroll
        for (int o = 8; o; o >>= 1) {
            kmax = fmaxf(kmax, __shfl_xor_sync(~0u, kmax, o));
            qmax = fmaxf(qmax, __shfl_xor_sync(~0u, qmax, o));
        }
        const bool safe = __all_sync(~0u, kmax * qmax * 1.1f <= SAFE_BOUND * SAFE_BOUND);
        const uint64_t dK0 = make_desc(sK, 128, 384, 0), dV0 = make_desc(sV, 384, 128, 0);
        auto publish_h = [&]() {
            if (warp == 8 || warp == 12) {
                if (lane == 0) { bulk_wait_all(); cnt_signal(CNT_H + rb); }
                __syncwarp();
            }
        };
        if (!safe) {
#pragma unroll 1
            for (int pass = 0; pass < 2; pass++) {
                const uint32_t sQ = sb + SM_Q + pass * 12288 + wgi * 3072;
                mbar_wait(bar + (B_Q + pass) * 8, 0);
                if (lane < 16) *reinterpret_cast<uint32_t*>(smem + (sQ - sb) + (w4 * 2 + (lane >> 3)) * 384 + 256 + (lane & 7) * 16 + ((h & 1) ? 0 : 8)) = 0u;
                fence_proxy_async();
                asm volatile("bar.sync %0, 128;" ::"r"(wgi + 3) : "memory");
                attn_rows_maxshift(sK, barKV, make_desc(sQ, 128, 384, 0), make_desc(sQ + 256, sb + SM_ZERO - (sQ + 256), 384, 0), h,
                                   qb * 512 + pass * 256 + wgi * 64 + w4 * 16);
                if (pass == 0) publish_h();
            }
        } else {
            const ExpConst kc = make_exp_const();
#pragma unroll 1
            for (int pass = 0; pass < 2; pass++) {
                const int rbase = qb * 512 + pass * 256 + wgi * 64 + w4 * 16;
                const uint32_t sQ = sb + SM_Q + pass * 12288 + wgi * 3072;
                const uint64_t dQ = make_desc(sQ, 128, 384, 0), dQ2 = make_desc(sQ + 256, sb + SM_ZERO - (sQ + 256), 384, 0);
                float o[12], sa[32], sc[32];
                uint32_t p[16];
#pragma unroll
                for (int i = 0; i < 12; i++) o[i] = 0.f;
                fence_regs(o);
                mbar_wait(bar + (B_Q + pass) * 8, 0);
                mbar_wait(barKV + 128, 0);
                qk_tile(sa, dQ, dQ2, dK0);
                wg_wait<0>();
                fence_regs(sa);
                uint64_t dK = dK0, dV = dV0;
                uint32_t bj = barKV;
#pragma unroll 1
                for (int j = 0; j < 16; j++) {
                    mbar_wait(bj, 0);
                    qk_tile(sc, dQ, dQ2, dK + 192);
                    wg_wait<1>();
                    exp_tile<0>(sa, p, kc);
                    pv_tile(o, p, dV);
                    wg_wait<1>();
                    fence_regs(sc);
                    mbar_wait(bj, 0);
                    qk_tile(sa, dQ, dQ2, dK + 384);
                    wg_wait<1>();
                    exp_tile<8>(sc, p, kc);
                    pv_tile(o, p, dV + 192);
                    wg_wait<1>();
                    fence_regs(sa);
                    dK += 384; dV += 384; bj += 8;
                }
                wg_wait<0>();
                fence_regs(o);
                store_o(o, h, rbase, lane);
                if (threadIdx.x == 0) TL(2, 2 + pass);
                if (pass == 0) publish_h();
            }
        }
        __syncthreads();
        if (threadIdx.x == 64) cnt_signal(CNT_O + qb);
        cluster_arrive_relaxed();
    }

    {
        const uint32_t epoch = *reinterpret_cast<volatile uint32_t*>(smem + SM_EPOCH);
        const int ct = cl & 3, rt = (cl >> 2) * 2 + rank;
        if (threadIdx.x == 0) TL(3, 0);
        const int orow = threadIdx.x >> 3, oseg = threadIdx.x & 7;
        const size_t ooff = (size_t)(rt * 64 + orow) * DM + ct * 160 + oseg * 20;
        uint2 xr[5], br[5];
#pragma unroll
        for (int i = 0; i < 5; i++) {
            xr[i] = __ldg(reinterpret_cast<const uint2*>(x + ooff) + i);
            br[i] = __ldg(reinterpret_cast<const uint2*>(b2 + ct * 160 + oseg * 20) + i);
        }
        cluster_wait();
        float* stg = reinterpret_cast<float*>(smem);
        if (warp == 4) {
            if (elect_one()) { prefetch_map(&tm.h); prefetch_map(&tm.o); prefetch_map(&tm.w2); prefetch_map(&tm.wo); cnt_wait(CNT_H + (rt >> 1), (epoch + 1) * 16); }
            __syncwarp();
#pragma unroll 1
            for (int kb = 0; kb < 34; kb++) {
                const int s = kb & 7;
                if (kb >= 8) mbar_wait(bar + (B_E3 + s) * 8, ((kb >> 3) - 1) & 1);
                if (elect_one()) {
                    if (kb == 24) { cnt_wait(CNT_O + (rt >> 3), (epoch + 1) * 32); TL(3, 1); }
                    const uint32_t dst = sb + s * G2_STAGE, fb = bar + (B_F3 + s) * 8;
                    const CUtensorMap* mA = kb < 24 ? &tm.h : &tm.o;
                    const CUtensorMap* mB = kb < 24 ? &tm.w2 : &tm.wo;
                    const int k0 = (kb < 24 ? kb : kb - 24) * 64;
                    mbar_expect_tx(fb, G2_STAGE);
                    tma_load(dst, mA, k0, rt * 64, fb);
                    const int first = ((kb & 1) == (int)rank) ? 0 : 3, last = ((kb & 1) == (int)rank) ? 3 : 5;
                    for (int b = first; b < last; b++) tma_load_mc(dst + 8192 + b * 4096, mB, ct * 160 + b * 32, k0, fb, 3);
                }
                __syncwarp();
            }
        } else if (wgi == 0) {
            float acc[80];
#pragma unroll 1
            for (int kb = 0; kb < 34; kb++) {
                const int s = kb & 7;
                mbar_wait(bar + (B_F3 + s) * 8, (kb >> 3) & 1);
                wg_fence();
                const uint64_t dA = make_desc(sb + s * G2_STAGE, 16, 1024, 1);
                const uint64_t dB = make_desc(sb + s * G2_STAGE + 8192, 4096, 512, 2);
#pragma unroll
                for (int kk = 0; kk < 4; kk++) wgmma_n160_ss_tb(acc, dA + kk * 2, dB + kk * 64, (kb | kk) != 0);
                wg_commit();
                if (kb > 0) {
                    wg_wait<1>();
                    if (kb <= 26) release_stage(bar + (B_E3 + ((kb - 1) & 7)) * 8, peer, lane);
                }
            }
            wg_wait<0>();
            fence_regs(acc);
            if (threadIdx.x == 0) TL(3, 2);
            const int r = w4 * 16 + g;
#pragma unroll
            for (int j = 0; j < 20; j++) {
                *reinterpret_cast<float2*>(stg + r * 168 + j * 8 + 2 * c) = make_float2(acc[4 * j], acc[4 * j + 1]);
                *reinterpret_cast<float2*>(stg + (r + 8) * 168 + j * 8 + 2 * c) = make_float2(acc[4 * j + 2], acc[4 * j + 3]);
            }
        }
        __syncthreads();
        const float4* sp = reinterpret_cast<const float4*>(stg + orow * 168 + oseg * 20);
#pragma unroll
        for (int i = 0; i < 5; i++) {
            const float4 a = sp[i];
            uint2 w;
            w.x = pack_bf16(a.x + bf_lo(br[i].x) + bf_lo(xr[i].x), a.y + bf_hi(br[i].x) + bf_hi(xr[i].x));
            w.y = pack_bf16(a.z + bf_lo(br[i].y) + bf_lo(xr[i].y), a.w + bf_hi(br[i].y) + bf_hi(xr[i].y));
            reinterpret_cast<uint2*>(out + ooff)[i] = w;
        }
        if (blockIdx.x == 0 && threadIdx.x == 0) g_epoch = epoch + 1;
        if (threadIdx.x == 0) TL(3, 3);
    }
    cluster_arrive_relaxed();
    cluster_wait();
}

typedef CUresult (*EncodeTiledFn)(CUtensorMap*, CUtensorMapDataType, cuuint32_t, void*, const cuuint64_t*,
                                  const cuuint64_t*, const cuuint32_t*, const cuuint32_t*, CUtensorMapInterleave,
                                  CUtensorMapSwizzle, CUtensorMapL2promotion, CUtensorMapFloatOOBfill);

CUtensorMap make_map(EncodeTiledFn enc, const void* ptr, int rows, int cols, int box_rows, int box_cols,
                     CUtensorMapSwizzle swz) {
    CUtensorMap m;
    cuuint64_t gd[2] = {(cuuint64_t)cols, (cuuint64_t)rows};
    cuuint64_t gs[1] = {(cuuint64_t)cols * 2};
    cuuint32_t bd[2] = {(cuuint32_t)box_cols, (cuuint32_t)box_rows};
    cuuint32_t es[2] = {1, 1};
    enc(&m, CU_TENSOR_MAP_DATA_TYPE_BFLOAT16, 2, const_cast<void*>(ptr), gd, gs, bd, es, CU_TENSOR_MAP_INTERLEAVE_NONE,
        swz, CU_TENSOR_MAP_L2_PROMOTION_L2_128B, CU_TENSOR_MAP_FLOAT_OOB_FILL_NONE);
    return m;
}

}

extern "C" void kernel_launch(void* const* d_in, const int* in_sizes, int n_in, void* d_out, int out_size) {
    (void)in_sizes; (void)n_in; (void)out_size;
    const __nv_bfloat16* x = (const __nv_bfloat16*)d_in[0];
    const __nv_bfloat16* wqkv = (const __nv_bfloat16*)d_in[1];
    const __nv_bfloat16* wo = (const __nv_bfloat16*)d_in[2];
    const __nv_bfloat16* w1 = (const __nv_bfloat16*)d_in[4];
    const __nv_bfloat16* b1 = (const __nv_bfloat16*)d_in[5];
    const __nv_bfloat16* w2 = (const __nv_bfloat16*)d_in[6];
    const __nv_bfloat16* b2 = (const __nv_bfloat16*)d_in[7];
    __nv_bfloat16* out = (__nv_bfloat16*)d_out;

    static EncodeTiledFn enc = nullptr;
    static void *p_h, *p_o;
    if (!enc) {
        cudaDriverEntryPointQueryResult qr;
        cudaGetDriverEntryPoint("cuTensorMapEncodeTiled", (void**)&enc, cudaEnableDefault, &qr);
        cudaGetSymbolAddress(&p_h, g_h);
        cudaGetSymbolAddress(&p_o, g_o);
        cudaFuncSetAttribute(k_fused, cudaFuncAttributeMaxDynamicSharedMemorySize, SM_TOTAL);
    }
    Maps tm;
    tm.x = make_map(enc, x, SEQ, DM, 128, 64, CU_TENSOR_MAP_SWIZZLE_128B);
    tm.wqkv = make_map(enc, wqkv, DM, 3 * DM, 32, 64, CU_TENSOR_MAP_SWIZZLE_128B);
    tm.w1 = make_map(enc, w1, DM, FF, 32, 64, CU_TENSOR_MAP_SWIZZLE_128B);
    tm.h = make_map(enc, p_h, SEQ, FF, 64, 64, CU_TENSOR_MAP_SWIZZLE_128B);
    tm.o = make_map(enc, p_o, SEQ, DM, 64, 64, CU_TENSOR_MAP_SWIZZLE_128B);
    tm.wo = make_map(enc, wo, DM, DM, 64, 32, CU_TENSOR_MAP_SWIZZLE_64B);
    tm.w2 = make_map(enc, w2, FF, DM, 64, 32, CU_TENSOR_MAP_SWIZZLE_64B);
    k_fused<<<128, 512, SM_TOTAL, cudaStreamPerThread>>>(tm, x, (const uint8_t*)wqkv, (const uint8_t*)w1, (const uint8_t*)w2,
                                                         (const uint8_t*)wo, b1, b2, out);
}
```

```cpp
#include <cuda_runtime.h>
#include <cuda_bf16.h>
#include <cuda.h>
#include <stdint.h>

namespace {

constexpr int SEQ = 2048, DM = 640, FF = 1536;
constexpr float LN_EPS = 1e-5f;

constexpr int IMG_BYTES = 256 * 384;
constexpr uint32_t EMU_MASK = 0xD5D5u;
constexpr float SAFE_BOUND = 80.0f;
#define XV_IT 1
#define HELP_WAIT 0
#define PACE_NS 200
constexpr float QSCALE = 0.22360679774997896f * 1.4426950408889634f;

__device__ float4 g_stat[SEQ];
__device__ float2 g_csp[16 * 1728];
__device__ __align__(1024) uint8_t g_img[96 * IMG_BYTES + 1024];
__device__ float g_nrm[64 * SEQ];
__device__ __align__(1024) __nv_bfloat16 g_h[SEQ * FF];
__device__ __align__(1024) __nv_bfloat16 g_o[SEQ * DM];
constexpr int CNT_ST = 0, CNT_QKV = 16, CNT_H = 24, CNT_O = 40, CNT_CS = 44, CNT_CS2 = 52;
__device__ uint32_t g_cnt[60 * 32];
__device__ uint32_t g_epoch;

#define TL(kern, slot) do { } while (0)
#define IT(row, i) do { } while (0)

__device__ __forceinline__ uint32_t smem_u32(const void* p) { return (uint32_t)__cvta_generic_to_shared(p); }
__device__ __forceinline__ void mbar_init(uint32_t bar, int cnt) {
    asm volatile("mbarrier.init.shared::cta.b64 [%0], %1;" ::"r"(bar), "r"(cnt));
}
__device__ __forceinline__ void mbar_expect_tx(uint32_t bar, uint32_t bytes) {
    asm volatile("mbarrier.arrive.expect_tx.shared::cta.b64 _, [%0], %1;" ::"r"(bar), "r"(bytes) : "memory");
}
__device__ __forceinline__ void mbar_wait(uint32_t bar, uint32_t parity) {
    asm volatile("{\n.reg .pred p;\n.reg .u32 n;\nmov.u32 n, 0;\n"
                 "WAIT_LOOP:\nmbarrier.try_wait.parity.shared::cta.b64 p, [%0], %1;\n@p bra WAIT_DONE;\n"
                 "add.u32 n, n, 1;\nsetp.lt.u32 p, n, 4194304;\n@p bra WAIT_LOOP;\nWAIT_DONE:\n}"
                 ::"r"(bar), "r"(parity) : "memory");
}
__device__ __forceinline__ void mbar_arrive(uint32_t bar) {
    asm volatile("mbarrier.arrive.shared::cta.b64 _, [%0];" ::"r"(bar) : "memory");
}
__device__ __forceinline__ void mbar_arrive_cluster(uint32_t bar, uint32_t cta) {
    asm volatile("{\n.reg .b32 ra;\nmapa.shared::cluster.u32 ra, %0, %1;\n"
                 "mbarrier.arrive.shared::cluster.b64 _, [ra];\n}" ::"r"(bar), "r"(cta) : "memory");
}
__device__ __forceinline__ void fence_barrier_init() { asm volatile("fence.mbarrier_init.release.cluster;" ::: "memory"); }
__device__ __forceinline__ void fence_proxy_async() { asm volatile("fence.proxy.async.shared::cta;" ::: "memory"); }
__device__ __forceinline__ void cluster_sync() {
    asm volatile("barrier.cluster.arrive.release.aligned;\nbarrier.cluster.wait.acquire.aligned;" ::: "memory");
}
__device__ __forceinline__ bool elect_one() {
    uint32_t pred;
    asm volatile("{\n.reg .pred p;\nelect.sync _|p, 0xFFFFFFFF;\nselp.b32 %0, 1, 0, p;\n}" : "=r"(pred));
    return pred != 0;
}
__device__ __forceinline__ void pdl_launch() { asm volatile("griddepcontrol.launch_dependents;" ::: "memory"); }
__device__ __forceinline__ void pdl_wait() { asm volatile("griddepcontrol.wait;" ::: "memory"); }
__device__ __forceinline__ void prefetch_map(const CUtensorMap* m) {
    asm volatile("prefetch.tensormap [%0];" ::"l"(m) : "memory");
}
__device__ __forceinline__ void tma_load(uint32_t dst, const CUtensorMap* m, int c0, int c1, uint32_t bar) {
    asm volatile("cp.async.bulk.tensor.2d.shared::cluster.global.mbarrier::complete_tx::bytes [%0], [%1, {%3, %4}], [%2];"
                 ::"r"(dst), "l"(m), "r"(bar), "r"(c0), "r"(c1) : "memory");
}
__device__ __forceinline__ void tma_load_mc(uint32_t dst, const CUtensorMap* m, int c0, int c1, uint32_t bar, uint16_t mask) {
    asm volatile("cp.async.bulk.tensor.2d.shared::cluster.global.mbarrier::complete_tx::bytes.multicast::cluster"
                 " [%0], [%1, {%3, %4}], [%2], %5;"
                 ::"r"(dst), "l"(m), "r"(bar), "r"(c0), "r"(c1), "h"(mask) : "memory");
}
__device__ __forceinline__ void tma_store(const CUtensorMap* m, uint32_t src, int c0, int c1) {
    asm volatile("cp.async.bulk.tensor.2d.global.shared::cta.bulk_group [%0, {%2, %3}], [%1];"
                 ::"l"(m), "r"(src), "r"(c0), "r"(c1) : "memory");
}
__device__ __forceinline__ void bulk_commit() { asm volatile("cp.async.bulk.commit_group;" ::: "memory"); }
__device__ __forceinline__ void bulk_wait_all() { asm volatile("cp.async.bulk.wait_group 0;" ::: "memory"); }
__device__ __forceinline__ void bulk_load(uint32_t dst, const void* src, uint32_t bytes, uint32_t bar) {
    asm volatile("cp.async.bulk.shared::cluster.global.mbarrier::complete_tx::bytes [%0], [%1], %2, [%3];"
                 ::"r"(dst), "l"(src), "r"(bytes), "r"(bar) : "memory");
}
__device__ __forceinline__ void prefetch_l2(const void* p, uint32_t bytes) {
    asm volatile("cp.async.bulk.prefetch.L2.global [%0], %1;" ::"l"(p), "r"(bytes) : "memory");
}
__device__ __forceinline__ void tma_prefetch_l2(const CUtensorMap* m, int c0, int c1) {
    asm volatile("cp.async.bulk.prefetch.tensor.2d.L2.global.tile [%0, {%1, %2}];" ::"l"(m), "r"(c0), "r"(c1) : "memory");
}
__device__ __forceinline__ void wg_fence() { asm volatile("wgmma.fence.sync.aligned;" ::: "memory"); }
__device__ __forceinline__ void wg_commit() { asm volatile("wgmma.commit_group.sync.aligned;" ::: "memory"); }
template <int N> __device__ __forceinline__ void wg_wait() {
    asm volatile("wgmma.wait_group.sync.aligned %0;" ::"n"(N) : "memory");
}
template <int N> __device__ __forceinline__ void reg_alloc() { asm volatile("setmaxnreg.inc.sync.aligned.u32 %0;" ::"n"(N)); }
template <int N> __device__ __forceinline__ void reg_dealloc() { asm volatile("setmaxnreg.dec.sync.aligned.u32 %0;" ::"n"(N)); }
template <int N> __device__ __forceinline__ void fence_regs(float (&d)[N]) {
#pragma unroll
    for (int i = 0; i < N; i++) asm volatile("" : "+f"(d[i])::"memory");
}
__device__ __forceinline__ uint64_t make_desc(uint32_t addr, uint32_t lbo, uint32_t sbo, uint32_t swz) {
    return (uint64_t)((addr & 0x3FFFF) >> 4) | ((uint64_t)(lbo >> 4) << 16) | ((uint64_t)(sbo >> 4) << 32) |
           ((uint64_t)swz << 62);
}
__device__ __forceinline__ uint32_t pack_bf16(float lo, float hi) {
    uint32_t r;
    asm("cvt.rn.bf16x2.f32 %0, %1, %2;" : "=r"(r) : "f"(hi), "f"(lo));
    return r;
}
__device__ __forceinline__ float ex2(float x) {
    float r;
    asm("ex2.approx.ftz.f32 %0, %1;" : "=f"(r) : "f"(x));
    return r;
}
__device__ __forceinline__ float bf_lo(uint32_t v) { return __uint_as_float(v << 16); }
__device__ __forceinline__ float bf_hi(uint32_t v) { return __uint_as_float(v & 0xFFFF0000u); }
__device__ __forceinline__ void stmatrix_x4(uint32_t addr, uint32_t r0, uint32_t r1, uint32_t r2, uint32_t r3) {
    asm volatile("stmatrix.sync.aligned.m8n8.x4.shared.b16 [%0], {%1, %2, %3, %4};"
                 ::"r"(addr), "r"(r0), "r"(r1), "r"(r2), "r"(r3) : "memory");
}

__device__ __forceinline__ void wgmma_n200_ss_tb(float (&d)[100], uint64_t descA, uint64_t descB, int scaleD) {
    asm volatile("{\n.reg .pred p;\nsetp.ne.b32 p, %102, 0;\n"
        "wgmma.mma_async.sync.aligned.m64n200k16.f32.bf16.bf16 {"
        "%0, %1, %2, %3, %4, %5, %6, %7, %8, %9, %10, %11, %12, %13, %14, %15, "
        "%16, %17, %18, %19, %20, %21, %22, %23, %24, %25, %26, %27, %28, %29, %30, %31, "
        "%32, %33, %34, %35, %36, %37, %38, %39, %40, %41, %42, %43, %44, %45, %46, %47, "
        "%48, %49, %50, %51, %52, %53, %54, %55, %56, %57, %58, %59, %60, %61, %62, %63, "
        "%64, %65, %66, %67, %68, %69, %70, %71, %72, %73, %74, %75, %76, %77, %78, %79, "
        "%80, %81, %82, %83, %84, %85, %86, %87, %88, %89, %90, %91, %92, %93, %94, %95, "
        "%96, %97, %98, %99}, "
        "%100, %101, p, 1, 1, 0, 1;\n}\n"
        : "+f"(d[0]), "+f"(d[1]), "+f"(d[2]), "+f"(d[3]), "+f"(d[4]), "+f"(d[5]), "+f"(d[6]), "+f"(d[7]),
          "+f"(d[8]), "+f"(d[9]), "+f"(d[10]), "+f"(d[11]), "+f"(d[12]), "+f"(d[13]), "+f"(d[14]), "+f"(d[15]),
          "+f"(d[16]), "+f"(d[17]), "+f"(d[18]), "+f"(d[19]), "+f"(d[20]), "+f"(d[21]), "+f"(d[22]), "+f"(d[23]),
          "+f"(d[24]), "+f"(d[25]), "+f"(d[26]), "+f"(d[27]), "+f"(d[28]), "+f"(d[29]), "+f"(d[30]), "+f"(d[31]),
          "+f"(d[32]), "+f"(d[33]), "+f"(d[34]), "+f"(d[35]), "+f"(d[36]), "+f"(d[37]), "+f"(d[38]), "+f"(d[39]),
          "+f"(d[40]), "+f"(d[41]), "+f"(d[42]), "+f"(d[43]), "+f"(d[44]), "+f"(d[45]), "+f"(d[46]), "+f"(d[47]),
          "+f"(d[48]), "+f"(d[49]), "+f"(d[50]), "+f"(d[51]), "+f"(d[52]), "+f"(d[53]), "+f"(d[54]), "+f"(d[55]),
          "+f"(d[56]), "+f"(d[57]), "+f"(d[58]), "+f"(d[59]), "+f"(d[60]), "+f"(d[61]), "+f"(d[62]), "+f"(d[63]),
          "+f"(d[64]), "+f"(d[65]), "+f"(d[66]), "+f"(d[67]), "+f"(d[68]), "+f"(d[69]), "+f"(d[70]), "+f"(d[71]),
          "+f"(d[72]), "+f"(d[73]), "+f"(d[74]), "+f"(d[75]), "+f"(d[76]), "+f"(d[77]), "+f"(d[78]), "+f"(d[79]),
          "+f"(d[80]), "+f"(d[81]), "+f"(d[82]), "+f"(d[83]), "+f"(d[84]), "+f"(d[85]), "+f"(d[86]), "+f"(d[87]),
          "+f"(d[88]), "+f"(d[89]), "+f"(d[90]), "+f"(d[91]), "+f"(d[92]), "+f"(d[93]), "+f"(d[94]), "+f"(d[95]),
          "+f"(d[96]), "+f"(d[97]), "+f"(d[98]), "+f"(d[99])
        : "l"(descA), "l"(descB), "r"(scaleD));
}

__device__ __forceinline__ void wgmma_n40_ss_tb(float (&d)[20], uint64_t descA, uint64_t descB, int scaleD) {
    asm volatile("{\n.reg .pred p;\nsetp.ne.b32 p, %22, 0;\n"
        "wgmma.mma_async.sync.aligned.m64n40k16.f32.bf16.bf16 {"
        "%0, %1, %2, %3, %4, %5, %6, %7, %8, %9, %10, %11, %12, %13, %14, %15, "
        "%16, %17, %18, %19}, "
        "%20, %21, p, 1, 1, 0, 1;\n}\n"
        : "+f"(d[0]), "+f"(d[1]), "+f"(d[2]), "+f"(d[3]), "+f"(d[4]), "+f"(d[5]), "+f"(d[6]), "+f"(d[7]),
          "+f"(d[8]), "+f"(d[9]), "+f"(d[10]), "+f"(d[11]), "+f"(d[12]), "+f"(d[13]), "+f"(d[14]), "+f"(d[15]),
          "+f"(d[16]), "+f"(d[17]), "+f"(d[18]), "+f"(d[19])
        : "l"(descA), "l"(descB), "r"(scaleD));
}

__device__ __forceinline__ void wgmma_n192_ss_tb(float (&d)[96], uint64_t descA, uint64_t descB, int scaleD) {
    asm volatile("{\n.reg .pred p;\nsetp.ne.b32 p, %98, 0;\n"
        "wgmma.mma_async.sync.aligned.m64n192k16.f32.bf16.bf16 {"
        "%0, %1, %2, %3, %4, %5, %6, %7, %8, %9, %10, %11, %12, %13, %14, %15, "
        "%16, %17, %18, %19, %20, %21, %22, %23, %24, %25, %26, %27, %28, %29, %30, %31, "
        "%32, %33, %34, %35, %36, %37, %38, %39, %40, %41, %42, %43, %44, %45, %46, %47, "
        "%48, %49, %50, %51, %52, %53, %54, %55, %56, %57, %58, %59, %60, %61, %62, %63, "
        "%64, %65, %66, %67, %68, %69, %70, %71, %72, %73, %74, %75, %76, %77, %78, %79, "
        "%80, %81, %82, %83, %84, %85, %86, %87, %88, %89, %90, %91, %92, %93, %94, %95}, "
        "%96, %97, p, 1, 1, 0, 1;\n}\n"
        : "+f"(d[0]), "+f"(d[1]), "+f"(d[2]), "+f"(d[3]), "+f"(d[4]), "+f"(d[5]), "+f"(d[6]), "+f"(d[7]),
          "+f"(d[8]), "+f"(d[9]), "+f"(d[10]), "+f"(d[11]), "+f"(d[12]), "+f"(d[13]), "+f"(d[14]), "+f"(d[15]),
          "+f"(d[16]), "+f"(d[17]), "+f"(d[18]), "+f"(d[19]), "+f"(d[20]), "+f"(d[21]), "+f"(d[22]), "+f"(d[23]),
          "+f"(d[24]), "+f"(d[25]), "+f"(d[26]), "+f"(d[27]), "+f"(d[28]), "+f"(d[29]), "+f"(d[30]), "+f"(d[31]),
          "+f"(d[32]), "+f"(d[33]), "+f"(d[34]), "+f"(d[35]), "+f"(d[36]), "+f"(d[37]), "+f"(d[38]), "+f"(d[39]),
          "+f"(d[40]), "+f"(d[41]), "+f"(d[42]), "+f"(d[43]), "+f"(d[44]), "+f"(d[45]), "+f"(d[46]), "+f"(d[47]),
          "+f"(d[48]), "+f"(d[49]), "+f"(d[50]), "+f"(d[51]), "+f"(d[52]), "+f"(d[53]), "+f"(d[54]), "+f"(d[55]),
          "+f"(d[56]), "+f"(d[57]), "+f"(d[58]), "+f"(d[59]), "+f"(d[60]), "+f"(d[61]), "+f"(d[62]), "+f"(d[63]),
          "+f"(d[64]), "+f"(d[65]), "+f"(d[66]), "+f"(d[67]), "+f"(d[68]), "+f"(d[69]), "+f"(d[70]), "+f"(d[71]),
          "+f"(d[72]), "+f"(d[73]), "+f"(d[74]), "+f"(d[75]), "+f"(d[76]), "+f"(d[77]), "+f"(d[78]), "+f"(d[79]),
          "+f"(d[80]), "+f"(d[81]), "+f"(d[82]), "+f"(d[83]), "+f"(d[84]), "+f"(d[85]), "+f"(d[86]), "+f"(d[87]),
          "+f"(d[88]), "+f"(d[89]), "+f"(d[90]), "+f"(d[91]), "+f"(d[92]), "+f"(d[93]), "+f"(d[94]), "+f"(d[95])
        : "l"(descA), "l"(descB), "r"(scaleD));
}

__device__ __forceinline__ void wgmma_n192_ss_tb_z(float (&d)[96], uint64_t descA, uint64_t descB) {
    asm volatile("{\n.reg .pred p;\nsetp.ne.b32 p, 0, 0;\n"
        "wgmma.mma_async.sync.aligned.m64n192k16.f32.bf16.bf16 {"
        "%0, %1, %2, %3, %4, %5, %6, %7, %8, %9, %10, %11, %12, %13, %14, %15, "
        "%16, %17, %18, %19, %20, %21, %22, %23, %24, %25, %26, %27, %28, %29, %30, %31, "
        "%32, %33, %34, %35, %36, %37, %38, %39, %40, %41, %42, %43, %44, %45, %46, %47, "
        "%48, %49, %50, %51, %52, %53, %54, %55, %56, %57, %58, %59, %60, %61, %62, %63, "
        "%64, %65, %66, %67, %68, %69, %70, %71, %72, %73, %74, %75, %76, %77, %78, %79, "
        "%80, %81, %82, %83, %84, %85, %86, %87, %88, %89, %90, %91, %92, %93, %94, %95}, "
        "%96, %97, p, 1, 1, 0, 1;\n}\n"
        : "=f"(d[0]), "=f"(d[1]), "=f"(d[2]), "=f"(d[3]), "=f"(d[4]), "=f"(d[5]), "=f"(d[6]), "=f"(d[7]),
          "=f"(d[8]), "=f"(d[9]), "=f"(d[10]), "=f"(d[11]), "=f"(d[12]), "=f"(d[13]), "=f"(d[14]), "=f"(d[15]),
          "=f"(d[16]), "=f"(d[17]), "=f"(d[18]), "=f"(d[19]), "=f"(d[20]), "=f"(d[21]), "=f"(d[22]), "=f"(d[23]),
          "=f"(d[24]), "=f"(d[25]), "=f"(d[26]), "=f"(d[27]), "=f"(d[28]), "=f"(d[29]), "=f"(d[30]), "=f"(d[31]),
          "=f"(d[32]), "=f"(d[33]), "=f"(d[34]), "=f"(d[35]), "=f"(d[36]), "=f"(d[37]), "=f"(d[38]), "=f"(d[39]),
          "=f"(d[40]), "=f"(d[41]), "=f"(d[42]), "=f"(d[43]), "=f"(d[44]), "=f"(d[45]), "=f"(d[46]), "=f"(d[47]),
          "=f"(d[48]), "=f"(d[49]), "=f"(d[50]), "=f"(d[51]), "=f"(d[52]), "=f"(d[53]), "=f"(d[54]), "=f"(d[55]),
          "=f"(d[56]), "=f"(d[57]), "=f"(d[58]), "=f"(d[59]), "=f"(d[60]), "=f"(d[61]), "=f"(d[62]), "=f"(d[63]),
          "=f"(d[64]), "=f"(d[65]), "=f"(d[66]), "=f"(d[67]), "=f"(d[68]), "=f"(d[69]), "=f"(d[70]), "=f"(d[71]),
          "=f"(d[72]), "=f"(d[73]), "=f"(d[74]), "=f"(d[75]), "=f"(d[76]), "=f"(d[77]), "=f"(d[78]), "=f"(d[79]),
          "=f"(d[80]), "=f"(d[81]), "=f"(d[82]), "=f"(d[83]), "=f"(d[84]), "=f"(d[85]), "=f"(d[86]), "=f"(d[87]),
          "=f"(d[88]), "=f"(d[89]), "=f"(d[90]), "=f"(d[91]), "=f"(d[92]), "=f"(d[93]), "=f"(d[94]), "=f"(d[95])
        : "l"(descA), "l"(descB));
}

__device__ __forceinline__ void wgmma_n160_ss_tb(float (&d)[80], uint64_t descA, uint64_t descB, int scaleD) {
    asm volatile("{\n.reg .pred p;\nsetp.ne.b32 p, %82, 0;\n"
        "wgmma.mma_async.sync.aligned.m64n160k16.f32.bf16.bf16 {"
        "%0, %1, %2, %3, %4, %5, %6, %7, %8, %9, %10, %11, %12, %13, %14, %15, "
        "%16, %17, %18, %19, %20, %21, %22, %23, %24, %25, %26, %27, %28, %29, %30, %31, "
        "%32, %33, %34, %35, %36, %37, %38, %39, %40, %41, %42, %43, %44, %45, %46, %47, "
        "%48, %49, %50, %51, %52, %53, %54, %55, %56, %57, %58, %59, %60, %61, %62, %63, "
        "%64, %65, %66, %67, %68, %69, %70, %71, %72, %73, %74, %75, %76, %77, %78, %79}, "
        "%80, %81, p, 1, 1, 0, 1;\n}\n"
        : "+f"(d[0]), "+f"(d[1]), "+f"(d[2]), "+f"(d[3]), "+f"(d[4]), "+f"(d[5]), "+f"(d[6]), "+f"(d[7]),
          "+f"(d[8]), "+f"(d[9]), "+f"(d[10]), "+f"(d[11]), "+f"(d[12]), "+f"(d[13]), "+f"(d[14]), "+f"(d[15]),
          "+f"(d[16]), "+f"(d[17]), "+f"(d[18]), "+f"(d[19]), "+f"(d[20]), "+f"(d[21]), "+f"(d[22]), "+f"(d[23]),
          "+f"(d[24]), "+f"(d[25]), "+f"(d[26]), "+f"(d[27]), "+f"(d[28]), "+f"(d[29]), "+f"(d[30]), "+f"(d[31]),
          "+f"(d[32]), "+f"(d[33]), "+f"(d[34]), "+f"(d[35]), "+f"(d[36]), "+f"(d[37]), "+f"(d[38]), "+f"(d[39]),
          "+f"(d[40]), "+f"(d[41]), "+f"(d[42]), "+f"(d[43]), "+f"(d[44]), "+f"(d[45]), "+f"(d[46]), "+f"(d[47]),
          "+f"(d[48]), "+f"(d[49]), "+f"(d[50]), "+f"(d[51]), "+f"(d[52]), "+f"(d[53]), "+f"(d[54]), "+f"(d[55]),
          "+f"(d[56]), "+f"(d[57]), "+f"(d[58]), "+f"(d[59]), "+f"(d[60]), "+f"(d[61]), "+f"(d[62]), "+f"(d[63]),
          "+f"(d[64]), "+f"(d[65]), "+f"(d[66]), "+f"(d[67]), "+f"(d[68]), "+f"(d[69]), "+f"(d[70]), "+f"(d[71]),
          "+f"(d[72]), "+f"(d[73]), "+f"(d[74]), "+f"(d[75]), "+f"(d[76]), "+f"(d[77]), "+f"(d[78]), "+f"(d[79])
        : "l"(descA), "l"(descB), "r"(scaleD));
}

__device__ __forceinline__ void wgmma_n64_ss(float (&d)[32], uint64_t descA, uint64_t descB, int scaleD) {
    asm volatile("{\n.reg .pred p;\nsetp.ne.b32 p, %34, 0;\n"
        "wgmma.mma_async.sync.aligned.m64n64k16.f32.bf16.bf16 {"
        "%0, %1, %2, %3, %4, %5, %6, %7, %8, %9, %10, %11, %12, %13, %14, %15, "
        "%16, %17, %18, %19, %20, %21, %22, %23, %24, %25, %26, %27, %28, %29, %30, %31}, "
        "%32, %33, p, 1, 1, 0, 0;\n}\n"
        : "+f"(d[0]), "+f"(d[1]), "+f"(d[2]), "+f"(d[3]), "+f"(d[4]), "+f"(d[5]), "+f"(d[6]), "+f"(d[7]),
          "+f"(d[8]), "+f"(d[9]), "+f"(d[10]), "+f"(d[11]), "+f"(d[12]), "+f"(d[13]), "+f"(d[14]), "+f"(d[15]),
          "+f"(d[16]), "+f"(d[17]), "+f"(d[18]), "+f"(d[19]), "+f"(d[20]), "+f"(d[21]), "+f"(d[22]), "+f"(d[23]),
          "+f"(d[24]), "+f"(d[25]), "+f"(d[26]), "+f"(d[27]), "+f"(d[28]), "+f"(d[29]), "+f"(d[30]), "+f"(d[31])
        : "l"(descA), "l"(descB), "r"(scaleD));
}

__device__ __forceinline__ void wgmma_n64_ss_z(float (&d)[32], uint64_t descA, uint64_t descB) {
    asm volatile("{\n.reg .pred p;\nsetp.ne.b32 p, 0, 0;\n"
        "wgmma.mma_async.sync.aligned.m64n64k16.f32.bf16.bf16 {"
        "%0, %1, %2, %3, %4, %5, %6, %7, %8, %9, %10, %11, %12, %13, %14, %15, "
        "%16, %17, %18, %19, %20, %21, %22, %23, %24, %25, %26, %27, %28, %29, %30, %31}, "
        "%32, %33, p, 1, 1, 0, 0;\n}\n"
        : "=f"(d[0]), "=f"(d[1]), "=f"(d[2]), "=f"(d[3]), "=f"(d[4]), "=f"(d[5]), "=f"(d[6]), "=f"(d[7]),
          "=f"(d[8]), "=f"(d[9]), "=f"(d[10]), "=f"(d[11]), "=f"(d[12]), "=f"(d[13]), "=f"(d[14]), "=f"(d[15]),
          "=f"(d[16]), "=f"(d[17]), "=f"(d[18]), "=f"(d[19]), "=f"(d[20]), "=f"(d[21]), "=f"(d[22]), "=f"(d[23]),
          "=f"(d[24]), "=f"(d[25]), "=f"(d[26]), "=f"(d[27]), "=f"(d[28]), "=f"(d[29]), "=f"(d[30]), "=f"(d[31])
        : "l"(descA), "l"(descB));
}

__device__ __forceinline__ void wgmma_n24_rs_tb(float (&d)[12], uint32_t a0, uint32_t a1, uint32_t a2, uint32_t a3, uint64_t descB, int scaleD) {
    asm volatile("{\n.reg .pred p;\nsetp.ne.b32 p, %17, 0;\n"
        "wgmma.mma_async.sync.aligned.m64n24k16.f32.bf16.bf16 {"
        "%0, %1, %2, %3, %4, %5, %6, %7, %8, %9, %10, %11}, "
        "{%12, %13, %14, %15}, %16, p, 1, 1, 1;\n}\n"
        : "+f"(d[0]), "+f"(d[1]), "+f"(d[2]), "+f"(d[3]), "+f"(d[4]), "+f"(d[5]), "+f"(d[6]), "+f"(d[7]),
          "+f"(d[8]), "+f"(d[9]), "+f"(d[10]), "+f"(d[11])
        : "r"(a0), "r"(a1), "r"(a2), "r"(a3), "l"(descB), "r"(scaleD));
}

__device__ __forceinline__ void cnt_signal(int idx) {
    asm volatile("fence.acq_rel.gpu;\nred.relaxed.gpu.global.add.u32 [%0], 1;"
                 ::"l"(g_cnt + idx * 32) : "memory");
}
__device__ __forceinline__ void cnt_wait(int idx, uint32_t target) {
    const uint32_t* p = g_cnt + idx * 32;
#pragma unroll 1
    for (uint32_t i = 0; i < (1u << 22); i++) {
        uint32_t v;
        asm volatile("ld.acquire.gpu.global.u32 %0, [%1];" : "=r"(v) : "l"(p) : "memory");
        if ((int32_t)(v - target) >= 0) break;
    }
    asm volatile("fence.proxy.async.global;" ::: "memory");
}
__device__ __forceinline__ void cluster_arrive() { asm volatile("barrier.cluster.arrive.release.aligned;" ::: "memory"); }
__device__ __forceinline__ void cluster_arrive_relaxed() { asm volatile("barrier.cluster.arrive.relaxed.aligned;" ::: "memory"); }
__device__ __forceinline__ void cluster_wait() { asm volatile("barrier.cluster.wait.acquire.aligned;" ::: "memory"); }
__device__ __forceinline__ void bulk_wait_read() { asm volatile("cp.async.bulk.wait_group.read 0;" ::: "memory"); }

__device__ __forceinline__ float gelu_tanh(float x) {
    const float u = x * (0.7978845608028654f + 0.035677408136300125f * x * x);
    float t;
    asm("tanh.approx.f32 %0, %1;" : "=f"(t) : "f"(u));
    const float h = 0.5f * x;
    return fmaf(h, t, h);
}
__device__ __forceinline__ void release_stage(uint32_t bar, uint32_t peer, int lane) {
    if (lane == 0) { mbar_arrive(bar); mbar_arrive_cluster(bar, peer); }
}

constexpr int SM_RING = 163840;
constexpr int SM_Q = 2 * IMG_BYTES, SM_ZERO = SM_Q + 24576;
constexpr int G2_STAGE = 8192 + 20480;
constexpr int SM_MISC = 229376;
constexpr int SM_BIAS = SM_MISC, SM_RED = SM_BIAS + 384, SM_BAR = SM_RED + 128;
constexpr int B_A = 0, B_F1 = 10, B_E1 = 14, B_F2 = 18, B_E2 = 23, B_KV = 28, B_Q = 45, B_F3 = 47, B_E3 = 55, B_ST = 63, B_STAT = 65, B_AUX = 66, B_AUX2 = 67, B_COUNT = 68;
constexpr int SM_EPOCH = SM_BAR + 544;
constexpr int SM_CS = SM_EPOCH + 16;
constexpr int SM_DBG = SM_CS + 1728;
constexpr int SM_TOTAL = SM_DBG + 128;
static_assert(SM_TOTAL <= 232448, "shared memory budget");

struct Maps { CUtensorMap x, wqkv, w1, h, o, wo, w2; };

__device__ __forceinline__ uint32_t bf2_fma(uint32_t a, uint32_t b, uint32_t c) {
    uint32_t r;
    asm("fma.rn.bf16x2 %0, %1, %2, %3;" : "=r"(r) : "r"(a), "r"(b), "r"(c));
    return r;
}
__device__ __forceinline__ uint32_t lop_and_or(uint32_t a, uint32_t m, uint32_t o) {
    uint32_t r;
    asm("lop3.b32 %0, %1, %2, %3, 0xEA;" : "=r"(r) : "r"(a), "r"(m), "r"(o));
    return r;
}
struct ExpConst { uint32_t mask, slope; };
__device__ __forceinline__ ExpConst make_exp_const() {
    ExpConst k;
    asm volatile("mov.b32 %0, 0x007F007F;" : "=r"(k.mask));
    asm volatile("mov.b32 %0, 0x3EF83EF8;" : "=r"(k.slope));
    return k;
}
__device__ __forceinline__ uint32_t exp2_pair_fma(float t0, float t1, const ExpConst& k) {
    const uint32_t L = __byte_perm(__float_as_uint(t0), __float_as_uint(t1), 0x6521);
    const uint32_t g = lop_and_or(L, k.mask, 0x3F803F80u);
    const uint32_t u = bf2_fma(g, k.slope, 0xBF37BF37u);
    const uint32_t e = bf2_fma(u, u, 0xBD71BD71u);
    return bf2_fma(L, e, L);
}
template <int SHIFT>
__device__ __forceinline__ void exp_tile(const float (&s)[32], uint32_t (&p)[16], const ExpConst& k) {
#pragma unroll
    for (int b = 0; b < 8; b++) {
        if ((EMU_MASK >> (b + SHIFT)) & 1) {
            p[2 * b] = exp2_pair_fma(s[4 * b], s[4 * b + 1], k);
            p[2 * b + 1] = exp2_pair_fma(s[4 * b + 2], s[4 * b + 3], k);
        } else {
            p[2 * b] = pack_bf16(ex2(s[4 * b]), ex2(s[4 * b + 1]));
            p[2 * b + 1] = pack_bf16(ex2(s[4 * b + 2]), ex2(s[4 * b + 3]));
        }
    }
}

__device__ __forceinline__ void qk_tile(float (&s)[32], uint64_t dQ, uint64_t dQ2, uint64_t dK) {
    wg_fence();
    wgmma_n64_ss_z(s, dQ, dK);
    wgmma_n64_ss(s, dQ2, dK + 16, 1);
    wg_commit();
}
__device__ __forceinline__ void pv_tile(float (&o)[12], const uint32_t (&p)[16], uint64_t dV) {
    wg_fence();
#pragma unroll
    for (int ks = 0; ks < 4; ks++)
        wgmma_n24_rs_tb(o, p[4 * ks], p[4 * ks + 1], p[4 * ks + 2], p[4 * ks + 3], dV + ks * 48, 1);
    wg_commit();
}
__device__ __forceinline__ void store_o(const float (&o)[12], int h, int rbase, int lane) {
    const int g = lane >> 2, c = lane & 3;
    const bool odd = h & 1;
    const int lsrc = (lane & ~3) | (odd ? 0 : 2);
    const float i0 = 1.f / __shfl_sync(~0u, o[8], lsrc), i1 = 1.f / __shfl_sync(~0u, o[10], lsrc);
    __nv_bfloat16* dst = g_o + (size_t)(rbase + g) * DM + h * 20;
    const int d0 = (odd ? 4 : 0) + 2 * c, d1 = d0 + 8, d2 = odd ? 2 * c - 4 : 16 + 2 * c;
    *(uint32_t*)(dst + d0) = pack_bf16(o[0] * i0, o[1] * i0);
    *(uint32_t*)(dst + d1) = pack_bf16(o[4] * i0, o[5] * i0);
    *(uint32_t*)(dst + 8 * DM + d0) = pack_bf16(o[2] * i1, o[3] * i1);
    *(uint32_t*)(dst + 8 * DM + d1) = pack_bf16(o[6] * i1, o[7] * i1);
    if (odd ? (c >= 2) : (c < 2)) {
        *(uint32_t*)(dst + d2) = pack_bf16(o[8] * i0, o[9] * i0);
        *(uint32_t*)(dst + 8 * DM + d2) = pack_bf16(o[10] * i1, o[11] * i1);
    }
}

__device__ __forceinline__ void attn_rows_maxshift(uint32_t sK, uint32_t barKV, uint64_t dQ, uint64_t dQ2, int h, int rbase) {
    const int lane = threadIdx.x & 31;
    const uint64_t dK0 = make_desc(sK, 128, 384, 0), dV0 = make_desc(sK + IMG_BYTES, 384, 128, 0);
    float o[12], s[32];
    uint32_t p[16];
#pragma unroll
    for (int i = 0; i < 12; i++) o[i] = 0.f;
    float m0 = -3.0e38f, m1 = -3.0e38f;
    mbar_wait(barKV + 128, 0);
#pragma unroll 1
    for (int t = 0; t < 32; t++) {
        mbar_wait(barKV + (t >> 1) * 8, 0);
        qk_tile(s, dQ, dQ2, dK0 + t * 192);
        wg_wait<0>();
        fence_regs(s);
        const uint32_t mask = EMU_MASK >> ((t & 1) * 8);
        float n0 = m0, n1 = m1;
#pragma unroll
        for (int b = 0; b < 8; b++) {
            const bool emu = (mask >> b) & 1;
            const float f = emu ? 0.5f : 1.f, off = emu ? -383.00390625f : 0.f;
#pragma unroll
            for (int i = 0; i < 4; i++) s[4 * b + i] = fmaf(s[4 * b + i], f, off);
            n0 = fmaxf(n0, fmaxf(s[4 * b], s[4 * b + 1]));
            n1 = fmaxf(n1, fmaxf(s[4 * b + 2], s[4 * b + 3]));
        }
        n0 = fmaxf(n0, __shfl_xor_sync(~0u, n0, 1)); n0 = fmaxf(n0, __shfl_xor_sync(~0u, n0, 2));
        n1 = fmaxf(n1, __shfl_xor_sync(~0u, n1, 1)); n1 = fmaxf(n1, __shfl_xor_sync(~0u, n1, 2));
        const float c0 = ex2(m0 - n0), c1 = ex2(m1 - n1);
        m0 = n0; m1 = n1;
#pragma unroll
        for (int b = 0; b < 3; b++) { o[4 * b] *= c0; o[4 * b + 1] *= c0; o[4 * b + 2] *= c1; o[4 * b + 3] *= c1; }
#pragma unroll
        for (int b = 0; b < 8; b++) {
            p[2 * b] = pack_bf16(ex2(s[4 * b] - m0), ex2(s[4 * b + 1] - m0));
            p[2 * b + 1] = pack_bf16(ex2(s[4 * b + 2] - m1), ex2(s[4 * b + 3] - m1));
        }
        pv_tile(o, p, dV0 + t * 192);
        wg_wait<0>();
        fence_regs(o);
    }
    store_o(o, h, rbase, lane);
}

__global__ void __launch_bounds__(512, 1) __cluster_dims__(2, 1, 1)
k_fused(const __grid_constant__ Maps tm, const __nv_bfloat16* __restrict__ x, const uint8_t* __restrict__ wqkv,
        const uint8_t* __restrict__ w1, const uint8_t* __restrict__ w2, const uint8_t* __restrict__ wo,
        const __nv_bfloat16* __restrict__ b1, const __nv_bfloat16* __restrict__ b2, __nv_bfloat16* __restrict__ out) {
    extern __shared__ __align__(1024) uint8_t smem[];
    const uint32_t sb = smem_u32(smem);
    const uint32_t bar = sb + SM_BAR;
    const int warp = __shfl_sync(~0u, threadIdx.x >> 5, 0), lane = threadIdx.x & 31;
    const int wgi = warp >> 2, w4 = warp & 3, g = lane >> 2, c = lane & 3;
    const uint32_t rank = blockIdx.x & 1, peer = rank ^ 1;
    const int cl = blockIdx.x >> 1;
    const int cg = cl >> 3, rb = (cl & 7) * 2 + rank;

    if (threadIdx.x == 0) TL(0, 0);
    if (warp == 15 && lane < 4) prefetch_map(lane == 0 ? &tm.x : lane == 1 ? &tm.wqkv : lane == 2 ? &tm.w1 : &tm.h);
    if (elect_one()) {
#pragma unroll
        for (int j = 0; j < 5; j++) {
            const int i = warp * 5 + j;
            const int cnt = (i >= B_E1 && i < B_F2) || (i >= B_E2 && i < B_KV) ? 16
                          : (i >= B_E3 && i <= B_ST) || i == B_STAT ? 8 : i == B_ST + 1 ? 2 : i >= B_AUX ? 7 : 1;
            if (i < B_COUNT) mbar_init(bar + i * 8, cnt);
        }
        fence_barrier_init();
    }
    __syncthreads();
    if (threadIdx.x == 0) TL(0, 1);
    cluster_arrive_relaxed();
    cluster_wait();
    if (threadIdx.x == 0) TL(0, 3);

    {
        const uint32_t sB = sb + SM_RING;
        if (threadIdx.x == 0) TL(1, 0);
        if (wgi < 2) {
            reg_dealloc<40>();
            if (threadIdx.x == 0) TL(4, 2);
            if (warp == 0) {
#pragma unroll 1
                for (int it = 0; it < 20; it++) {
                    const int s = it & 3;
                    const int kb = it < 2 ? it : (it & 1) ? (it + 1) >> 1 : 10;
                    if (it >= 4) mbar_wait(bar + (B_E1 + s) * 8, ((it >> 2) - 1) & 1);
                    else if (it > 0) __nanosleep(PACE_NS);
                    if (elect_one()) {
                        if (kb < 10) {
                            mbar_expect_tx(bar + (B_A + kb) * 8, 16384);
                            tma_load(sb + kb * 16384, &tm.x, kb * 64, rb * 128, bar + (B_A + kb) * 8);
                        }
                        const uint32_t dst = sB + s * 16384 + rank * 8192, fb = bar + (B_F1 + s) * 8;
                        const int c0 = cg * 240 + rank * 128;
                        mbar_expect_tx(fb, 16384);
                        tma_load_mc(dst, &tm.wqkv, c0, it * 32, fb, 3);
                        tma_load_mc(dst + 4096, &tm.wqkv, c0 + 64, it * 32, fb, 3);
                    }
                    __syncwarp();
                    if (lane == 0 && it < 8) TL(5, it) ;
                }
#pragma unroll 1
                for (int it = 0; it < 20; it++) {
                    const int s = it % 5;
                    if (it < 5) { if (it != 3) mbar_wait(bar + (B_E1 + (it == 4 ? 3 : it)) * 8, 0); }
                    else mbar_wait(bar + (B_E2 + s) * 8, ((it / 5) - 1) & 1);
                    if (elect_one()) {
                        const uint32_t dst = sB + s * 12288, fb = bar + (B_F2 + s) * 8;
                        mbar_expect_tx(fb, 12288);
                        if ((it & 1) == (int)rank) {
                            tma_load_mc(dst, &tm.w1, cg * 192, it * 32, fb, 3);
                            tma_load_mc(dst + 4096, &tm.w1, cg * 192 + 64, it * 32, fb, 3);
                        } else {
                            tma_load_mc(dst + 8192, &tm.w1, cg * 192 + 128, it * 32, fb, 3);
                        }
                    }
                    __syncwarp();
                }
            } else {
                const int ht = threadIdx.x - 32;
                if (ht == 192) *reinterpret_cast<volatile uint32_t*>(smem + SM_EPOCH) = *(volatile uint32_t*)&g_epoch;
                auto slab_sum = [&](const uint32_t* src, int pitch) {
                    float s0 = 0.f, s1 = 0.f;
#pragma unroll
                    for (int h2 = 0; h2 < 2; h2++) {
                        uint32_t v[20];
#pragma unroll
                        for (int k = 0; k < 20; k++) v[k] = __ldg(src + (h2 * 20 + k) * pitch);
#pragma unroll
                        for (int k = 0; k < 20; k++) { s0 += bf_lo(v[k]); s1 += bf_hi(v[k]); }
                    }
                    return make_float2(s0, s1);
                };
                auto gather = [&](int idx) {
                    float s0 = 0.f, s1 = 0.f;
#pragma unroll
                    for (int r = 0; r < 16; r++) {
                        const float2 v = __ldcg(g_csp + r * 1728 + cg * 216 + idx);
                        s0 += v.x; s1 += v.y;
                    }
                    reinterpret_cast<float2*>(smem + SM_CS)[idx] = make_float2(s0, s1);
                };
                mbar_wait(bar + (B_F1 + HELP_WAIT) * 8, 0);
#pragma unroll 1
                for (int r = warp - 1; r < 16; r += 7) {
                    const int srow = rb * 128 + cg * 16 + r;
                    uint2 xv[5];
#pragma unroll
                    for (int i = 0; i < 5; i++) xv[i] = __ldg(reinterpret_cast<const uint2*>(x + (size_t)srow * DM) + lane + 32 * i);
                    float sm = 0.f;
#pragma unroll
                    for (int i = 0; i < 5; i++) sm += (bf_lo(xv[i].x) + bf_hi(xv[i].x)) + (bf_lo(xv[i].y) + bf_hi(xv[i].y));
#pragma unroll
                    for (int o = 16; o; o >>= 1) sm += __shfl_xor_sync(~0u, sm, o);
                    const float mu = sm * (1.f / DM);
                    float q = 0.f;
#pragma unroll
                    for (int i = 0; i < 5; i++) {
                        const float d0 = bf_lo(xv[i].x) - mu, d1 = bf_hi(xv[i].x) - mu, d2 = bf_lo(xv[i].y) - mu, d3 = bf_hi(xv[i].y) - mu;
                        q = fmaf(d0, d0, fmaf(d1, d1, fmaf(d2, d2, fmaf(d3, d3, q))));
                    }
#pragma unroll
                    for (int o = 16; o; o >>= 1) q += __shfl_xor_sync(~0u, q, o);
                    const float var = q * (1.f / DM);
                    const float r1 = 1.f / sqrtf(var + LN_EPS);
                    const float r2 = 1.f / sqrtf(var * r1 * r1 + LN_EPS);
                    if (lane == 0) g_stat[srow] = make_float4(mu, r1, r1 * r2, 0.f);
                }
                if (ht < 120)
                    g_csp[rb * 1728 + cg * 216 + ht] = slab_sum(reinterpret_cast<const uint32_t*>(wqkv) + rb * 40 * 960 + cg * 120 + ht, 960);
                if (threadIdx.x == 64) IT(3, 0);
                asm volatile("bar.sync 8, 224;" ::: "memory");
                const uint32_t epoch = *reinterpret_cast<volatile uint32_t*>(smem + SM_EPOCH);
                if (warp == 6) { if (elect_one()) cnt_signal(CNT_CS + cg); __syncwarp(); }
                if (warp == 7) { if (elect_one()) cnt_signal(CNT_ST + rb); __syncwarp(); }
                if (ht < 96) {
                    g_csp[rb * 1728 + cg * 216 + 120 + ht] = slab_sum(reinterpret_cast<const uint32_t*>(w1) + rb * 40 * 768 + cg * 96 + ht, 768);
                    reinterpret_cast<uint32_t*>(smem + SM_BIAS)[ht] = __ldg(reinterpret_cast<const uint32_t*>(b1 + cg * 192) + ht);
                }
                asm volatile("bar.sync 8, 224;" ::: "memory");
                if (warp == 6) { if (elect_one()) cnt_signal(CNT_CS2 + cg); __syncwarp(); }
                if (threadIdx.x == 64) IT(3, 2);
                if (lane == 0) { cnt_wait(CNT_CS + cg, (epoch + 1) * 16); cnt_wait(CNT_ST + rb, (epoch + 1) * 8); }
                __syncwarp();
                if (threadIdx.x == 64) IT(3, 4);
                if (ht < 120) gather(ht);
                __syncwarp();
                if (threadIdx.x == 64) IT(3, 5);
                if (lane == 0) mbar_arrive(bar + B_AUX * 8);
                if (warp == 3 && elect_one()) {
                    prefetch_l2(w2 + blockIdx.x * 15360, 15360);
                    prefetch_l2(wo + blockIdx.x * 6400, 6400);
                }
                if (lane == 0) cnt_wait(CNT_CS2 + cg, (epoch + 1) * 16);
                __syncwarp();
                if (ht < 96) gather(120 + ht);
                __syncwarp();
                if (lane == 0) mbar_arrive(bar + B_AUX2 * 8);
                if (warp == 4) {
                    mbar_wait(bar + B_ST * 8, 0);
                    if (elect_one()) cnt_signal(CNT_QKV + cg);
                    __syncwarp();
                }
            }
            asm volatile("bar.sync %0, 128;" ::"r"(wgi + 3) : "memory");
            reg_alloc<128>();
        } else {
            reg_alloc<216>();
            if (threadIdx.x == 256) TL(4, 0);
            const int wi = wgi - 2;
            const int row0 = rb * 128 + wi * 64 + w4 * 16 + g;
            const uint32_t sAw = sb + wi * 8192;
            const int rbk = row0 >> 3, hs0 = cg * 12;
            if (threadIdx.x == 256) TL(4, 1);
            float accA[100], accB[20];
            const uint64_t dA0 = make_desc(sAw, 16, 1024, 1), dB0 = make_desc(sB, 4096, 1024, 1);
#pragma unroll 2
            for (int it = 0; it < 20; it++) {
                const int s = it & 3;
                if (!(it & 1)) mbar_wait(bar + (B_A + (it >> 1)) * 8, 0);
                if (threadIdx.x == 256 && it == 0) TL(0, 2);
                if (threadIdx.x == 256 && it == 2) TL(4, 3);
                if (threadIdx.x == 256) IT(0, it);
                mbar_wait(bar + (B_F1 + s) * 8, (it >> 2) & 1);
                if (threadIdx.x == 256) IT(1, it);
                const uint64_t dA = dA0 + (it >> 1) * 1024 + (it & 1) * 4, dB = dB0 + s * 1024;
                wg_fence();
                wgmma_n40_ss_tb(accB, dA, dB + 769, it > 0);
                wgmma_n40_ss_tb(accB, dA + 2, dB + 769 + 128, 1);
                wgmma_n200_ss_tb(accA, dA, dB, it > 0);
                wgmma_n200_ss_tb(accA, dA + 2, dB + 128, 1);
                wg_commit();
                if (it > 0) { wg_wait<1>(); release_stage(bar + (B_E1 + ((it - 1) & 3)) * 8, peer, lane); }
            }
            if (threadIdx.x == 256) IT(2, 0);
            mbar_wait(bar + B_AUX * 8, 0);
            if (threadIdx.x == 256) IT(2, 1);
            const float4 st0 = __ldcg(g_stat + row0), st1 = __ldcg(g_stat + row0 + 8);
            wg_wait<0>();
            release_stage(bar + (B_E1 + 3) * 8, peer, lane);
            fence_regs(accA);
            fence_regs(accB);
            if (threadIdx.x == 256) TL(1, 1);
            const float2* cs = reinterpret_cast<const float2*>(smem + SM_CS) + c;
            uint8_t* img = g_img + (size_t)hs0 * IMG_BYTES + rbk * 384 + g * 16 + c * 4;
            const bool emu0 = (EMU_MASK >> (rbk & 15)) & 1, emu1 = (EMU_MASK >> ((rbk + 1) & 15)) & 1;
            const bool low = c < 2;
            uint32_t pk[60];
#pragma unroll
            for (int m = 0; m < 6; m++) {
                const int which = (hs0 + 2 * m) >> 5;
                const float m0 = st0.y * (which == 0 ? QSCALE : (which == 1 && emu0) ? 2.f : 1.f);
                const float m1 = st1.y * (which == 0 ? QSCALE : (which == 1 && emu1) ? 2.f : 1.f);
                const float d0 = -st0.x * m0, d1 = -st1.x * m1;
                const float* a = m < 5 ? &accA[20 * m] : accB;
#pragma unroll
                for (int b = 0; b < 5; b++) {
                    const float2 cv = cs[(5 * m + b) * 4];
                    pk[10 * m + 2 * b] = pack_bf16(fmaf(a[4 * b], m0, d0 * cv.x), fmaf(a[4 * b + 1], m0, d0 * cv.y));
                    pk[10 * m + 2 * b + 1] = pack_bf16(fmaf(a[4 * b + 2], m1, d1 * cv.x), fmaf(a[4 * b + 3], m1, d1 * cv.y));
                }
            }
            const float r20 = st0.z, r21 = st1.z, e20 = -st0.x * st0.z, e21 = -st1.x * st1.z;
            if (threadIdx.x == 256) IT(2, 2);
            float acc2[96];
#pragma unroll
            for (int it = 0; it < 20; it++) {
                const int s = it % 5;
                if (threadIdx.x == 256) IT(0, 20 + it);
                mbar_wait(bar + (B_F2 + s) * 8, (it / 5) & 1);
                if (threadIdx.x == 256) IT(1, 20 + it);
                wg_fence();
                const uint64_t dA = make_desc(sAw + (it >> 1) * 16384 + (it & 1) * 64, 16, 1024, 1);
                const uint64_t dB = make_desc(sB + s * 12288, 4096, 1024, 1);
                if (it == 0) wgmma_n192_ss_tb_z(acc2, dA, dB); else wgmma_n192_ss_tb(acc2, dA, dB, 1);
                wgmma_n192_ss_tb(acc2, dA + 2, dB + 128, 1);
                wg_commit();
                if (it > 0) {
                    wg_wait<1>();
                    if (it <= 15) release_stage(bar + (B_E2 + (it - 1) % 5) * 8, peer, lane);
                }
                if (it < 12) {
                    const int m = it / 2, part = it % 2;
                    const int hs = hs0 + 2 * m, which = hs >> 5;
                    const uint32_t* a = pk + 10 * m;
                    uint8_t* pe = img + (2 * m) * IMG_BYTES;
                    uint8_t* po = pe + IMG_BYTES;
                    if (part == 0) {
                        const uint32_t padv = which == 0 ? 0x3F803F80u : which == 1 ? 0xBFFF4440u : 0x00003F80u;
                        const uint32_t p0 = ((c & 1) || (which == 1 && !emu0)) ? 0u : padv;
                        const uint32_t p1 = ((c & 1) || (which == 1 && !emu1)) ? 0u : padv;
                        *(uint32_t*)(pe) = a[0];
                        *(uint32_t*)(pe + 128) = a[2];
                        *(uint32_t*)(pe + 256) = low ? a[4] : p0;
                        *(uint32_t*)(pe + 384) = a[1];
                        *(uint32_t*)(pe + 512) = a[3];
                        *(uint32_t*)(pe + 640) = low ? a[5] : p1;
                        *(uint32_t*)(po + 256) = low ? p0 : a[4];
                        *(uint32_t*)(po + 640) = low ? p1 : a[5];
                    } else {
                        *(uint32_t*)(po) = a[6];
                        *(uint32_t*)(po + 128) = a[8];
                        *(uint32_t*)(po + 384) = a[7];
                        *(uint32_t*)(po + 512) = a[9];
                        if (which < 2) {
                            const uint32_t u0 = bf2_fma(a[4], a[4], 0u), u1 = bf2_fma(a[5], a[5], 0u);
                            const uint32_t pe0 = bf2_fma(a[0], a[0], bf2_fma(a[2], a[2], low ? u0 : 0u));
                            const uint32_t pe1 = bf2_fma(a[1], a[1], bf2_fma(a[3], a[3], low ? u1 : 0u));
                            const uint32_t po0 = bf2_fma(a[6], a[6], bf2_fma(a[8], a[8], low ? 0u : u0));
                            const uint32_t po1 = bf2_fma(a[7], a[7], bf2_fma(a[9], a[9], low ? 0u : u1));
                            const float e0 = bf_lo(pe0) + bf_hi(pe0), e1 = bf_lo(pe1) + bf_hi(pe1);
                            const float o0 = bf_lo(po0) + bf_hi(po0), o1 = bf_lo(po1) + bf_hi(po1);
                            const bool b0 = c & 1, b1_ = c & 2;
                            const float x0 = (b0 ? e1 : e0) + __shfl_xor_sync(~0u, b0 ? e0 : e1, 1);
                            const float x1 = (b0 ? o1 : o0) + __shfl_xor_sync(~0u, b0 ? o0 : o1, 1);
                            float y = (b1_ ? x1 : x0) + __shfl_xor_sync(~0u, b1_ ? x0 : x1, 2);
                            if (which == 1 && (b0 ? emu1 : emu0)) y *= 0.25f;
                            g_nrm[(hs + (c >> 1)) * SEQ + row0 + (c & 1) * 8] = y;
                        }
                    }
                    if (it == 11) { __syncwarp(); if (lane == 0) mbar_arrive(bar + B_ST * 8); }
                }
            }
            wg_wait<0>();
            fence_regs(acc2);
            if (threadIdx.x == 256) TL(1, 2);
            mbar_wait(bar + B_AUX2 * 8, 0);
            const uint32_t* bias = reinterpret_cast<const uint32_t*>(smem + SM_BIAS) + c;
            const int mrow = w4 * 16 + (lane & 15);
            const uint32_t st_row = sAw + mrow * 128;
#pragma unroll
            for (int j = 0; j < 24; j += 2) {
                const uint32_t bA = bias[j * 4], bB = bias[j * 4 + 4];
                const float2 cA = cs[(30 + j) * 4], cB = cs[(31 + j) * 4];
                const float* a = acc2 + j * 4;
                const uint32_t r00 = pack_bf16(gelu_tanh(fmaf(a[0], r20, fmaf(e20, cA.x, bf_lo(bA)))), gelu_tanh(fmaf(a[1], r20, fmaf(e20, cA.y, bf_hi(bA)))));
                const uint32_t r10 = pack_bf16(gelu_tanh(fmaf(a[2], r21, fmaf(e21, cA.x, bf_lo(bA)))), gelu_tanh(fmaf(a[3], r21, fmaf(e21, cA.y, bf_hi(bA)))));
                const uint32_t r01 = pack_bf16(gelu_tanh(fmaf(a[4], r20, fmaf(e20, cB.x, bf_lo(bB)))), gelu_tanh(fmaf(a[5], r20, fmaf(e20, cB.y, bf_hi(bB)))));
                const uint32_t r11 = pack_bf16(gelu_tanh(fmaf(a[6], r21, fmaf(e21, cB.x, bf_lo(bB)))), gelu_tanh(fmaf(a[7], r21, fmaf(e21, cB.y, bf_hi(bB)))));
                const int chunk = (j & 7) + (lane >> 4);
                stmatrix_x4(st_row + (j >> 3) * 16384 + ((chunk ^ (mrow & 7)) << 4), r00, r10, r01, r11);
            }
            fence_proxy_async();
            asm volatile("bar.sync %0, 128;" ::"r"(wgi + 3) : "memory");
            if (w4 == 0 && lane == 0) {
#pragma unroll
                for (int b = 0; b < 3; b++) tma_store(&tm.h, sAw + b * 16384, cg * 192 + b * 64, rb * 128 + wi * 64);
                bulk_commit();
                bulk_wait_read();
            }
            __syncwarp();
            reg_dealloc<128>();
        }
        __syncthreads();
        if (threadIdx.x == 0) TL(1, 3);
    }

    {
        const uint32_t epoch = *reinterpret_cast<volatile uint32_t*>(smem + SM_EPOCH);
        const int h = blockIdx.x >> 2, qb = blockIdx.x & 3;
        const uint32_t sK = sb, sV = sb + IMG_BYTES, barKV = bar + B_KV * 8;
        if (threadIdx.x == 0) TL(2, 0);
        if (threadIdx.x < 192) *reinterpret_cast<uint4*>(smem + SM_ZERO + threadIdx.x * 16) = make_uint4(0, 0, 0, 0);
        fence_proxy_async();
        if (warp == 0) {
            if (elect_one()) {
                cnt_wait(CNT_QKV + h / 12, (epoch + 1) * 16);
                cnt_wait(CNT_QKV + (32 + h) / 12, (epoch + 1) * 16);
                cnt_wait(CNT_QKV + (64 + h) / 12, (epoch + 1) * 16);
                const uint8_t* gK = g_img + (size_t)(32 + h) * IMG_BYTES;
                const uint8_t* gV = g_img + (size_t)(64 + h) * IMG_BYTES;
                const uint8_t* gQ = g_img + (size_t)h * IMG_BYTES + qb * 64 * 384;
                mbar_expect_tx(barKV + 128, 6144);
                bulk_load(sK, gK, 6144, barKV + 128);
                for (int p = 0; p < 2; p++) {
                    mbar_expect_tx(bar + (B_Q + p) * 8, 12288);
                    bulk_load(sb + SM_Q + p * 12288, gQ + p * 12288, 12288, bar + (B_Q + p) * 8);
                }
                for (int i = 0; i < 16; i++) {
                    mbar_expect_tx(barKV + i * 8, i < 15 ? 12288 : 6144);
                    bulk_load(sV + i * 6144, gV + i * 6144, 6144, barKV + i * 8);
                    if (i < 15) bulk_load(sK + (i + 1) * 6144, gK + (i + 1) * 6144, 6144, barKV + i * 8);
                }
            }
            __syncwarp();
        }
        __syncthreads();
        if (threadIdx.x == 0) TL(2, 1);
        float* red = reinterpret_cast<float*>(smem + SM_RED);
        float kmax = 0.f, qmax = __ldcg(g_nrm + h * SEQ + qb * 512 + threadIdx.x);
#pragma unroll
        for (int i = 0; i < 4; i++) kmax = fmaxf(kmax, __ldcg(g_nrm + (32 + h) * SEQ + i * 512 + threadIdx.x));
#pragma unroll
        for (int o = 16; o; o >>= 1) {
            kmax = fmaxf(kmax, __shfl_xor_sync(~0u, kmax, o));
            qmax = fmaxf(qmax, __shfl_xor_sync(~0u, qmax, o));
        }
        if (lane == 0) { red[warp] = kmax; red[16 + warp] = qmax; }
        __syncthreads();
        kmax = red[lane & 15]; qmax = red[16 + (lane & 15)];
#pragma unroll
        for (int o = 8; o; o >>= 1) {
            kmax = fmaxf(kmax, __shfl_xor_sync(~0u, kmax, o));
            qmax = fmaxf(qmax, __shfl_xor_sync(~0u, qmax, o));
        }
        const bool safe = __all_sync(~0u, kmax * qmax * 1.1f <= SAFE_BOUND * SAFE_BOUND);
        const uint64_t dK0 = make_desc(sK, 128, 384, 0), dV0 = make_desc(sV, 384, 128, 0);
        auto publish_h = [&]() {
            if (warp == 8 || warp == 12) {
                if (lane == 0) { bulk_wait_all(); cnt_signal(CNT_H + rb); }
                __syncwarp();
            }
        };
        if (!safe) {
#pragma unroll 1
            for (int pass = 0; pass < 2; pass++) {
                const uint32_t sQ = sb + SM_Q + pass * 12288 + wgi * 3072;
                mbar_wait(bar + (B_Q + pass) * 8, 0);
                if (lane < 16) *reinterpret_cast<uint32_t*>(smem + (sQ - sb) + (w4 * 2 + (lane >> 3)) * 384 + 256 + (lane & 7) * 16 + ((h & 1) ? 0 : 8)) = 0u;
                fence_proxy_async();
                asm volatile("bar.sync %0, 128;" ::"r"(wgi + 3) : "memory");
                attn_rows_maxshift(sK, barKV, make_desc(sQ, 128, 384, 0), make_desc(sQ + 256, sb + SM_ZERO - (sQ + 256), 384, 0), h,
                                   qb * 512 + pass * 256 + wgi * 64 + w4 * 16);
                if (pass == 0) publish_h();
            }
        } else {
            const ExpConst kc = make_exp_const();
#pragma unroll 1
            for (int pass = 0; pass < 2; pass++) {
                const int rbase = qb * 512 + pass * 256 + wgi * 64 + w4 * 16;
                const uint32_t sQ = sb + SM_Q + pass * 12288 + wgi * 3072;
                const uint64_t dQ = make_desc(sQ, 128, 384, 0), dQ2 = make_desc(sQ + 256, sb + SM_ZERO - (sQ + 256), 384, 0);
                float o[12], sa[32], sc[32];
                uint32_t p[16];
#pragma unroll
                for (int i = 0; i < 12; i++) o[i] = 0.f;
                fence_regs(o);
                mbar_wait(bar + (B_Q + pass) * 8, 0);
                mbar_wait(barKV + 128, 0);
                qk_tile(sa, dQ, dQ2, dK0);
                wg_wait<0>();
                fence_regs(sa);
                uint64_t dK = dK0, dV = dV0;
                uint32_t bj = barKV;
#pragma unroll 1
                for (int j = 0; j < 16; j++) {
                    mbar_wait(bj, 0);
                    qk_tile(sc, dQ, dQ2, dK + 192);
                    wg_wait<1>();
                    exp_tile<0>(sa, p, kc);
                    pv_tile(o, p, dV);
                    wg_wait<1>();
                    fence_regs(sc);
                    mbar_wait(bj, 0);
                    qk_tile(sa, dQ, dQ2, dK + 384);
                    wg_wait<1>();
                    exp_tile<8>(sc, p, kc);
                    pv_tile(o, p, dV + 192);
                    wg_wait<1>();
                    fence_regs(sa);
                    dK += 384; dV += 384; bj += 8;
                }
                wg_wait<0>();
                fence_regs(o);
                store_o(o, h, rbase, lane);
                if (threadIdx.x == 0) TL(2, 2 + pass);
                if (pass == 0) publish_h();
            }
        }
        __syncthreads();
        if (threadIdx.x == 64) cnt_signal(CNT_O + qb);
        cluster_arrive_relaxed();
    }

    {
        const uint32_t epoch = *reinterpret_cast<volatile uint32_t*>(smem + SM_EPOCH);
        const int ct = cl & 3, rt = (cl >> 2) * 2 + rank;
        if (threadIdx.x == 0) TL(3, 0);
        const int orow = threadIdx.x >> 3, oseg = threadIdx.x & 7;
        const size_t ooff = (size_t)(rt * 64 + orow) * DM + ct * 160 + oseg * 20;
        uint2 xr[5], br[5];
#pragma unroll
        for (int i = 0; i < 5; i++) {
            xr[i] = __ldg(reinterpret_cast<const uint2*>(x + ooff) + i);
            br[i] = __ldg(reinterpret_cast<const uint2*>(b2 + ct * 160 + oseg * 20) + i);
        }
        cluster_wait();
        float* stg = reinterpret_cast<float*>(smem);
        if (warp == 4) {
            if (elect_one()) { prefetch_map(&tm.h); prefetch_map(&tm.o); prefetch_map(&tm.w2); prefetch_map(&tm.wo); cnt_wait(CNT_H + (rt >> 1), (epoch + 1) * 16); }
            __syncwarp();
#pragma unroll 1
            for (int kb = 0; kb < 34; kb++) {
                const int s = kb & 7;
                if (kb >= 8) mbar_wait(bar + (B_E3 + s) * 8, ((kb >> 3) - 1) & 1);
                if (elect_one()) {
                    if (kb == 24) { cnt_wait(CNT_O + (rt >> 3), (epoch + 1) * 32); TL(3, 1); }
                    const uint32_t dst = sb + s * G2_STAGE, fb = bar + (B_F3 + s) * 8;
                    const CUtensorMap* mA = kb < 24 ? &tm.h : &tm.o;
                    const CUtensorMap* mB = kb < 24 ? &tm.w2 : &tm.wo;
                    const int k0 = (kb < 24 ? kb : kb - 24) * 64;
                    mbar_expect_tx(fb, G2_STAGE);
                    tma_load(dst, mA, k0, rt * 64, fb);
                    const int first = ((kb & 1) == (int)rank) ? 0 : 3, last = ((kb & 1) == (int)rank) ? 3 : 5;
                    for (int b = first; b < last; b++) tma_load_mc(dst + 8192 + b * 4096, mB, ct * 160 + b * 32, k0, fb, 3);
                }
                __syncwarp();
            }
        } else if (wgi == 0) {
            float acc[80];
#pragma unroll 1
            for (int kb = 0; kb < 34; kb++) {
                const int s = kb & 7;
                mbar_wait(bar + (B_F3 + s) * 8, (kb >> 3) & 1);
                wg_fence();
                const uint64_t dA = make_desc(sb + s * G2_STAGE, 16, 1024, 1);
                const uint64_t dB = make_desc(sb + s * G2_STAGE + 8192, 4096, 512, 2);
#pragma unroll
                for (int kk = 0; kk < 4; kk++) wgmma_n160_ss_tb(acc, dA + kk * 2, dB + kk * 64, (kb | kk) != 0);
                wg_commit();
                if (kb > 0) {
                    wg_wait<1>();
                    if (kb <= 26) release_stage(bar + (B_E3 + ((kb - 1) & 7)) * 8, peer, lane);
                }
            }
            wg_wait<0>();
            fence_regs(acc);
            if (threadIdx.x == 0) TL(3, 2);
            const int r = w4 * 16 + g;
#pragma unroll
            for (int j = 0; j < 20; j++) {
                *reinterpret_cast<float2*>(stg + r * 168 + j * 8 + 2 * c) = make_float2(acc[4 * j], acc[4 * j + 1]);
                *reinterpret_cast<float2*>(stg + (r + 8) * 168 + j * 8 + 2 * c) = make_float2(acc[4 * j + 2], acc[4 * j + 3]);
            }
        }
        __syncthreads();
        const float4* sp = reinterpret_cast<const float4*>(stg + orow * 168 + oseg * 20);
#pragma unroll
        for (int i = 0; i < 5; i++) {
            const float4 a = sp[i];
            uint2 w;
            w.x = pack_bf16(a.x + bf_lo(br[i].x) + bf_lo(xr[i].x), a.y + bf_hi(br[i].x) + bf_hi(xr[i].x));
            w.y = pack_bf16(a.z + bf_lo(br[i].y) + bf_lo(xr[i].y), a.w + bf_hi(br[i].y) + bf_hi(xr[i].y));
            reinterpret_cast<uint2*>(out + ooff)[i] = w;
        }
        if (blockIdx.x == 0 && threadIdx.x == 0) g_epoch = epoch + 1;
        if (threadIdx.x == 0) TL(3, 3);
    }
    cluster_arrive_relaxed();
    cluster_wait();
}

typedef CUresult (*EncodeTiledFn)(CUtensorMap*, CUtensorMapDataType, cuuint32_t, void*, const cuuint64_t*,
                                  const cuuint64_t*, const cuuint32_t*, const cuuint32_t*, CUtensorMapInterleave,
                                  CUtensorMapSwizzle, CUtensorMapL2promotion, CUtensorMapFloatOOBfill);

CUtensorMap make_map(EncodeTiledFn enc, const void* ptr, int rows, int cols, int box_rows, int box_cols,
                     CUtensorMapSwizzle swz) {
    CUtensorMap m;
    cuuint64_t gd[2] = {(cuuint64_t)cols, (cuuint64_t)rows};
    cuuint64_t gs[1] = {(cuuint64_t)cols * 2};
    cuuint32_t bd[2] = {(cuuint32_t)box_cols, (cuuint32_t)box_rows};
    cuuint32_t es[2] = {1, 1};
    enc(&m, CU_TENSOR_MAP_DATA_TYPE_BFLOAT16, 2, const_cast<void*>(ptr), gd, gs, bd, es, CU_TENSOR_MAP_INTERLEAVE_NONE,
        swz, CU_TENSOR_MAP_L2_PROMOTION_L2_128B, CU_TENSOR_MAP_FLOAT_OOB_FILL_NONE);
    return m;
}

}

extern "C" void kernel_launch(void* const* d_in, const int* in_sizes, int n_in, void* d_out, int out_size) {
    (void)in_sizes; (void)n_in; (void)out_size;
    const __nv_bfloat16* x = (const __nv_bfloat16*)d_in[0];
    const __nv_bfloat16* wqkv = (const __nv_bfloat16*)d_in[1];
    const __nv_bfloat16* wo = (const __nv_bfloat16*)d_in[2];
    const __nv_bfloat16* w1 = (const __nv_bfloat16*)d_in[4];
    const __nv_bfloat16* b1 = (const __nv_bfloat16*)d_in[5];
    const __nv_bfloat16* w2 = (const __nv_bfloat16*)d_in[6];
    const __nv_bfloat16* b2 = (const __nv_bfloat16*)d_in[7];
    __nv_bfloat16* out = (__nv_bfloat16*)d_out;

    static EncodeTiledFn enc = nullptr;
    static void *p_h, *p_o;
    if (!enc) {
        cudaDriverEntryPointQueryResult qr;
        cudaGetDriverEntryPoint("cuTensorMapEncodeTiled", (void**)&enc, cudaEnableDefault, &qr);
        cudaGetSymbolAddress(&p_h, g_h);
        cudaGetSymbolAddress(&p_o, g_o);
        cudaFuncSetAttribute(k_fused, cudaFuncAttributeMaxDynamicSharedMemorySize, SM_TOTAL);
    }
    Maps tm;
    tm.x = make_map(enc, x, SEQ, DM, 128, 64, CU_TENSOR_MAP_SWIZZLE_128B);
    tm.wqkv = make_map(enc, wqkv, DM, 3 * DM, 32, 64, CU_TENSOR_MAP_SWIZZLE_128B);
    tm.w1 = make_map(enc, w1, DM, FF, 32, 64, CU_TENSOR_MAP_SWIZZLE_128B);
    tm.h = make_map(enc, p_h, SEQ, FF, 64, 64, CU_TENSOR_MAP_SWIZZLE_128B);
    tm.o = make_map(enc, p_o, SEQ, DM, 64, 64, CU_TENSOR_MAP_SWIZZLE_128B);
    tm.wo = make_map(enc, wo, DM, DM, 64, 32, CU_TENSOR_MAP_SWIZZLE_64B);
    tm.w2 = make_map(enc, w2, FF, DM, 64, 32, CU_TENSOR_MAP_SWIZZLE_64B);
    k_fused<<<128, 512, SM_TOTAL, cudaStreamPerThread>>>(tm, x, (const uint8_t*)wqkv, (const uint8_t*)w1, (const uint8_t*)w2,
                                                         (const uint8_t*)wo, b1, b2, out);
}
```

```cpp
#include <cuda_runtime.h>
#include <cuda_bf16.h>
#include <cuda.h>
#include <stdint.h>

namespace {

constexpr int SEQ = 2048, DM = 640, FF = 1536;
constexpr float LN_EPS = 1e-5f;

constexpr int IMG_BYTES = 256 * 384;
constexpr uint32_t EMU_MASK = 0xD5D5u;
constexpr float SAFE_BOUND = 80.0f;
#define XV_IT 1
#define PACE_NS 200
constexpr float QSCALE = 0.22360679774997896f * 1.4426950408889634f;

__device__ float4 g_stat[SEQ];
__device__ float2 g_csp[16 * 1728];
__device__ __align__(1024) uint8_t g_img[96 * IMG_BYTES + 1024];
__device__ float g_nrm[64 * SEQ];
__device__ __align__(1024) __nv_bfloat16 g_h[SEQ * FF];
__device__ __align__(1024) __nv_bfloat16 g_o[SEQ * DM];
constexpr int CNT_ST = 0, CNT_QKV = 16, CNT_H = 24, CNT_O = 40, CNT_CS = 44, CNT_CS2 = 52;
__device__ uint32_t g_cnt[60 * 32];
__device__ uint32_t g_epoch;

#define TL(kern, slot) do { } while (0)
#define IT(row, i) do { } while (0)

__device__ __forceinline__ uint32_t smem_u32(const void* p) { return (uint32_t)__cvta_generic_to_shared(p); }
__device__ __forceinline__ void mbar_init(uint32_t bar, int cnt) {
    asm volatile("mbarrier.init.shared::cta.b64 [%0], %1;" ::"r"(bar), "r"(cnt));
}
__device__ __forceinline__ void mbar_expect_tx(uint32_t bar, uint32_t bytes) {
    asm volatile("mbarrier.arrive.expect_tx.shared::cta.b64 _, [%0], %1;" ::"r"(bar), "r"(bytes) : "memory");
}
__device__ __forceinline__ void mbar_wait(uint32_t bar, uint32_t parity) {
    asm volatile("{\n.reg .pred p;\n.reg .u32 n;\nmov.u32 n, 0;\n"
                 "WAIT_LOOP:\nmbarrier.try_wait.parity.shared::cta.b64 p, [%0], %1;\n@p bra WAIT_DONE;\n"
                 "add.u32 n, n, 1;\nsetp.lt.u32 p, n, 4194304;\n@p bra WAIT_LOOP;\nWAIT_DONE:\n}"
                 ::"r"(bar), "r"(parity) : "memory");
}
__device__ __forceinline__ void mbar_arrive(uint32_t bar) {
    asm volatile("mbarrier.arrive.shared::cta.b64 _, [%0];" ::"r"(bar) : "memory");
}
__device__ __forceinline__ void mbar_arrive_cluster(uint32_t bar, uint32_t cta) {
    asm volatile("{\n.reg .b32 ra;\nmapa.shared::cluster.u32 ra, %0, %1;\n"
                 "mbarrier.arrive.shared::cluster.b64 _, [ra];\n}" ::"r"(bar), "r"(cta) : "memory");
}
__device__ __forceinline__ void fence_barrier_init() { asm volatile("fence.mbarrier_init.release.cluster;" ::: "memory"); }
__device__ __forceinline__ void fence_proxy_async() { asm volatile("fence.proxy.async.shared::cta;" ::: "memory"); }
__device__ __forceinline__ void cluster_sync() {
    asm volatile("barrier.cluster.arrive.release.aligned;\nbarrier.cluster.wait.acquire.aligned;" ::: "memory");
}
__device__ __forceinline__ bool elect_one() {
    uint32_t pred;
    asm volatile("{\n.reg .pred p;\nelect.sync _|p, 0xFFFFFFFF;\nselp.b32 %0, 1, 0, p;\n}" : "=r"(pred));
    return pred != 0;
}
__device__ __forceinline__ void pdl_launch() { asm volatile("griddepcontrol.launch_dependents;" ::: "memory"); }
__device__ __forceinline__ void pdl_wait() { asm volatile("griddepcontrol.wait;" ::: "memory"); }
__device__ __forceinline__ void prefetch_map(const CUtensorMap* m) {
    asm volatile("prefetch.tensormap [%0];" ::"l"(m) : "memory");
}
__device__ __forceinline__ void tma_load(uint32_t dst, const CUtensorMap* m, int c0, int c1, uint32_t bar) {
    asm volatile("cp.async.bulk.tensor.2d.shared::cluster.global.mbarrier::complete_tx::bytes [%0], [%1, {%3, %4}], [%2];"
                 ::"r"(dst), "l"(m), "r"(bar), "r"(c0), "r"(c1) : "memory");
}
__device__ __forceinline__ void tma_load_mc(uint32_t dst, const CUtensorMap* m, int c0, int c1, uint32_t bar, uint16_t mask) {
    asm volatile("cp.async.bulk.tensor.2d.shared::cluster.global.mbarrier::complete_tx::bytes.multicast::cluster"
                 " [%0], [%1, {%3, %4}], [%2], %5;"
                 ::"r"(dst), "l"(m), "r"(bar), "r"(c0), "r"(c1), "h"(mask) : "memory");
}
__device__ __forceinline__ void tma_store(const CUtensorMap* m, uint32_t src, int c0, int c1) {
    asm volatile("cp.async.bulk.tensor.2d.global.shared::cta.bulk_group [%0, {%2, %3}], [%1];"
                 ::"l"(m), "r"(src), "r"(c0), "r"(c1) : "memory");
}
__device__ __forceinline__ void bulk_commit() { asm volatile("cp.async.bulk.commit_group;" ::: "memory"); }
__device__ __forceinline__ void bulk_wait_all() { asm volatile("cp.async.bulk.wait_group 0;" ::: "memory"); }
__device__ __forceinline__ void bulk_load(uint32_t dst, const void* src, uint32_t bytes, uint32_t bar) {
    asm volatile("cp.async.bulk.shared::cluster.global.mbarrier::complete_tx::bytes [%0], [%1], %2, [%3];"
                 ::"r"(dst), "l"(src), "r"(bytes), "r"(bar) : "memory");
}
__device__ __forceinline__ void prefetch_l2(const void* p, uint32_t bytes) {
    asm volatile("cp.async.bulk.prefetch.L2.global [%0], %1;" ::"l"(p), "r"(bytes) : "memory");
}
__device__ __forceinline__ void tma_prefetch_l2(const CUtensorMap* m, int c0, int c1) {
    asm volatile("cp.async.bulk.prefetch.tensor.2d.L2.global.tile [%0, {%1, %2}];" ::"l"(m), "r"(c0), "r"(c1) : "memory");
}
__device__ __forceinline__ void wg_fence() { asm volatile("wgmma.fence.sync.aligned;" ::: "memory"); }
__device__ __forceinline__ void wg_commit() { asm volatile("wgmma.commit_group.sync.aligned;" ::: "memory"); }
template <int N> __device__ __forceinline__ void wg_wait() {
    asm volatile("wgmma.wait_group.sync.aligned %0;" ::"n"(N) : "memory");
}
template <int N> __device__ __forceinline__ void reg_alloc() { asm volatile("setmaxnreg.inc.sync.aligned.u32 %0;" ::"n"(N)); }
template <int N> __device__ __forceinline__ void reg_dealloc() { asm volatile("setmaxnreg.dec.sync.aligned.u32 %0;" ::"n"(N)); }
template <int N> __device__ __forceinline__ void fence_regs(float (&d)[N]) {
#pragma unroll
    for (int i = 0; i < N; i++) asm volatile("" : "+f"(d[i])::"memory");
}
__device__ __forceinline__ uint64_t make_desc(uint32_t addr, uint32_t lbo, uint32_t sbo, uint32_t swz) {
    return (uint64_t)((addr & 0x3FFFF) >> 4) | ((uint64_t)(lbo >> 4) << 16) | ((uint64_t)(sbo >> 4) << 32) |
           ((uint64_t)swz << 62);
}
__device__ __forceinline__ uint32_t pack_bf16(float lo, float hi) {
    uint32_t r;
    asm("cvt.rn.bf16x2.f32 %0, %1, %2;" : "=r"(r) : "f"(hi), "f"(lo));
    return r;
}
__device__ __forceinline__ float ex2(float x) {
    float r;
    asm("ex2.approx.ftz.f32 %0, %1;" : "=f"(r) : "f"(x));
    return r;
}
__device__ __forceinline__ float bf_lo(uint32_t v) { return __uint_as_float(v << 16); }
__device__ __forceinline__ float bf_hi(uint32_t v) { return __uint_as_float(v & 0xFFFF0000u); }
__device__ __forceinline__ void stmatrix_x4(uint32_t addr, uint32_t r0, uint32_t r1, uint32_t r2, uint32_t r3) {
    asm volatile("stmatrix.sync.aligned.m8n8.x4.shared.b16 [%0], {%1, %2, %3, %4};"
                 ::"r"(addr), "r"(r0), "r"(r1), "r"(r2), "r"(r3) : "memory");
}

__device__ __forceinline__ void wgmma_n200_ss_tb(float (&d)[100], uint64_t descA, uint64_t descB, int scaleD) {
    asm volatile("{\n.reg .pred p;\nsetp.ne.b32 p, %102, 0;\n"
        "wgmma.mma_async.sync.aligned.m64n200k16.f32.bf16.bf16 {"
        "%0, %1, %2, %3, %4, %5, %6, %7, %8, %9, %10, %11, %12, %13, %14, %15, "
        "%16, %17, %18, %19, %20, %21, %22, %23, %24, %25, %26, %27, %28, %29, %30, %31, "
        "%32, %33, %34, %35, %36, %37, %38, %39, %40, %41, %42, %43, %44, %45, %46, %47, "
        "%48, %49, %50, %51, %52, %53, %54, %55, %56, %57, %58, %59, %60, %61, %62, %63, "
        "%64, %65, %66, %67, %68, %69, %70, %71, %72, %73, %74, %75, %76, %77, %78, %79, "
        "%80, %81, %82, %83, %84, %85, %86, %87, %88, %89, %90, %91, %92, %93, %94, %95, "
        "%96, %97, %98, %99}, "
        "%100, %101, p, 1, 1, 0, 1;\n}\n"
        : "+f"(d[0]), "+f"(d[1]), "+f"(d[2]), "+f"(d[3]), "+f"(d[4]), "+f"(d[5]), "+f"(d[6]), "+f"(d[7]),
          "+f"(d[8]), "+f"(d[9]), "+f"(d[10]), "+f"(d[11]), "+f"(d[12]), "+f"(d[13]), "+f"(d[14]), "+f"(d[15]),
          "+f"(d[16]), "+f"(d[17]), "+f"(d[18]), "+f"(d[19]), "+f"(d[20]), "+f"(d[21]), "+f"(d[22]), "+f"(d[23]),
          "+f"(d[24]), "+f"(d[25]), "+f"(d[26]), "+f"(d[27]), "+f"(d[28]), "+f"(d[29]), "+f"(d[30]), "+f"(d[31]),
          "+f"(d[32]), "+f"(d[33]), "+f"(d[34]), "+f"(d[35]), "+f"(d[36]), "+f"(d[37]), "+f"(d[38]), "+f"(d[39]),
          "+f"(d[40]), "+f"(d[41]), "+f"(d[42]), "+f"(d[43]), "+f"(d[44]), "+f"(d[45]), "+f"(d[46]), "+f"(d[47]),
          "+f"(d[48]), "+f"(d[49]), "+f"(d[50]), "+f"(d[51]), "+f"(d[52]), "+f"(d[53]), "+f"(d[54]), "+f"(d[55]),
          "+f"(d[56]), "+f"(d[57]), "+f"(d[58]), "+f"(d[59]), "+f"(d[60]), "+f"(d[61]), "+f"(d[62]), "+f"(d[63]),
          "+f"(d[64]), "+f"(d[65]), "+f"(d[66]), "+f"(d[67]), "+f"(d[68]), "+f"(d[69]), "+f"(d[70]), "+f"(d[71]),
          "+f"(d[72]), "+f"(d[73]), "+f"(d[74]), "+f"(d[75]), "+f"(d[76]), "+f"(d[77]), "+f"(d[78]), "+f"(d[79]),
          "+f"(d[80]), "+f"(d[81]), "+f"(d[82]), "+f"(d[83]), "+f"(d[84]), "+f"(d[85]), "+f"(d[86]), "+f"(d[87]),
          "+f"(d[88]), "+f"(d[89]), "+f"(d[90]), "+f"(d[91]), "+f"(d[92]), "+f"(d[93]), "+f"(d[94]), "+f"(d[95]),
          "+f"(d[96]), "+f"(d[97]), "+f"(d[98]), "+f"(d[99])
        : "l"(descA), "l"(descB), "r"(scaleD));
}

__device__ __forceinline__ void wgmma_n40_ss_tb(float (&d)[20], uint64_t descA, uint64_t descB, int scaleD) {
    asm volatile("{\n.reg .pred p;\nsetp.ne.b32 p, %22, 0;\n"
        "wgmma.mma_async.sync.aligned.m64n40k16.f32.bf16.bf16 {"
        "%0, %1, %2, %3, %4, %5, %6, %7, %8, %9, %10, %11, %12, %13, %14, %15, "
        "%16, %17, %18, %19}, "
        "%20, %21, p, 1, 1, 0, 1;\n}\n"
        : "+f"(d[0]), "+f"(d[1]), "+f"(d[2]), "+f"(d[3]), "+f"(d[4]), "+f"(d[5]), "+f"(d[6]), "+f"(d[7]),
          "+f"(d[8]), "+f"(d[9]), "+f"(d[10]), "+f"(d[11]), "+f"(d[12]), "+f"(d[13]), "+f"(d[14]), "+f"(d[15]),
          "+f"(d[16]), "+f"(d[17]), "+f"(d[18]), "+f"(d[19])
        : "l"(descA), "l"(descB), "r"(scaleD));
}

__device__ __forceinline__ void wgmma_n192_ss_tb(float (&d)[96], uint64_t descA, uint64_t descB, int scaleD) {
    asm volatile("{\n.reg .pred p;\nsetp.ne.b32 p, %98, 0;\n"
        "wgmma.mma_async.sync.aligned.m64n192k16.f32.bf16.bf16 {"
        "%0, %1, %2, %3, %4, %5, %6, %7, %8, %9, %10, %11, %12, %13, %14, %15, "
        "%16, %17, %18, %19, %20, %21, %22, %23, %24, %25, %26, %27, %28, %29, %30, %31, "
        "%32, %33, %34, %35, %36, %37, %38, %39, %40, %41, %42, %43, %44, %45, %46, %47, "
        "%48, %49, %50, %51, %52, %53, %54, %55, %56, %57, %58, %59, %60, %61, %62, %63, "
        "%64, %65, %66, %67, %68, %69, %70, %71, %72, %73, %74, %75, %76, %77, %78, %79, "
        "%80, %81, %82, %83, %84, %85, %86, %87, %88, %89, %90, %91, %92, %93, %94, %95}, "
        "%96, %97, p, 1, 1, 0, 1;\n}\n"
        : "+f"(d[0]), "+f"(d[1]), "+f"(d[2]), "+f"(d[3]), "+f"(d[4]), "+f"(d[5]), "+f"(d[6]), "+f"(d[7]),
          "+f"(d[8]), "+f"(d[9]), "+f"(d[10]), "+f"(d[11]), "+f"(d[12]), "+f"(d[13]), "+f"(d[14]), "+f"(d[15]),
          "+f"(d[16]), "+f"(d[17]), "+f"(d[18]), "+f"(d[19]), "+f"(d[20]), "+f"(d[21]), "+f"(d[22]), "+f"(d[23]),
          "+f"(d[24]), "+f"(d[25]), "+f"(d[26]), "+f"(d[27]), "+f"(d[28]), "+f"(d[29]), "+f"(d[30]), "+f"(d[31]),
          "+f"(d[32]), "+f"(d[33]), "+f"(d[34]), "+f"(d[35]), "+f"(d[36]), "+f"(d[37]), "+f"(d[38]), "+f"(d[39]),
          "+f"(d[40]), "+f"(d[41]), "+f"(d[42]), "+f"(d[43]), "+f"(d[44]), "+f"(d[45]), "+f"(d[46]), "+f"(d[47]),
          "+f"(d[48]), "+f"(d[49]), "+f"(d[50]), "+f"(d[51]), "+f"(d[52]), "+f"(d[53]), "+f"(d[54]), "+f"(d[55]),
          "+f"(d[56]), "+f"(d[57]), "+f"(d[58]), "+f"(d[59]), "+f"(d[60]), "+f"(d[61]), "+f"(d[62]), "+f"(d[63]),
          "+f"(d[64]), "+f"(d[65]), "+f"(d[66]), "+f"(d[67]), "+f"(d[68]), "+f"(d[69]), "+f"(d[70]), "+f"(d[71]),
          "+f"(d[72]), "+f"(d[73]), "+f"(d[74]), "+f"(d[75]), "+f"(d[76]), "+f"(d[77]), "+f"(d[78]), "+f"(d[79]),
          "+f"(d[80]), "+f"(d[81]), "+f"(d[82]), "+f"(d[83]), "+f"(d[84]), "+f"(d[85]), "+f"(d[86]), "+f"(d[87]),
          "+f"(d[88]), "+f"(d[89]), "+f"(d[90]), "+f"(d[91]), "+f"(d[92]), "+f"(d[93]), "+f"(d[94]), "+f"(d[95])
        : "l"(descA), "l"(descB), "r"(scaleD));
}

__device__ __forceinline__ void wgmma_n192_ss_tb_z(float (&d)[96], uint64_t descA, uint64_t descB) {
    asm volatile("{\n.reg .pred p;\nsetp.ne.b32 p, 0, 0;\n"
        "wgmma.mma_async.sync.aligned.m64n192k16.f32.bf16.bf16 {"
        "%0, %1, %2, %3, %4, %5, %6, %7, %8, %9, %10, %11, %12, %13, %14, %15, "
        "%16, %17, %18, %19, %20, %21, %22, %23, %24, %25, %26, %27, %28, %29, %30, %31, "
        "%32, %33, %34, %35, %36, %37, %38, %39, %40, %41, %42, %43, %44, %45, %46, %47, "
        "%48, %49, %50, %51, %52, %53, %54, %55, %56, %57, %58, %59, %60, %61, %62, %63, "
        "%64, %65, %66, %67, %68, %69, %70, %71, %72, %73, %74, %75, %76, %77, %78, %79, "
        "%80, %81, %82, %83, %84, %85, %86, %87, %88, %89, %90, %91, %92, %93, %94, %95}, "
        "%96, %97, p, 1, 1, 0, 1;\n}\n"
        : "=f"(d[0]), "=f"(d[1]), "=f"(d[2]), "=f"(d[3]), "=f"(d[4]), "=f"(d[5]), "=f"(d[6]), "=f"(d[7]),
          "=f"(d[8]), "=f"(d[9]), "=f"(d[10]), "=f"(d[11]), "=f"(d[12]), "=f"(d[13]), "=f"(d[14]), "=f"(d[15]),
          "=f"(d[16]), "=f"(d[17]), "=f"(d[18]), "=f"(d[19]), "=f"(d[20]), "=f"(d[21]), "=f"(d[22]), "=f"(d[23]),
          "=f"(d[24]), "=f"(d[25]), "=f"(d[26]), "=f"(d[27]), "=f"(d[28]), "=f"(d[29]), "=f"(d[30]), "=f"(d[31]),
          "=f"(d[32]), "=f"(d[33]), "=f"(d[34]), "=f"(d[35]), "=f"(d[36]), "=f"(d[37]), "=f"(d[38]), "=f"(d[39]),
          "=f"(d[40]), "=f"(d[41]), "=f"(d[42]), "=f"(d[43]), "=f"(d[44]), "=f"(d[45]), "=f"(d[46]), "=f"(d[47]),
          "=f"(d[48]), "=f"(d[49]), "=f"(d[50]), "=f"(d[51]), "=f"(d[52]), "=f"(d[53]), "=f"(d[54]), "=f"(d[55]),
          "=f"(d[56]), "=f"(d[57]), "=f"(d[58]), "=f"(d[59]), "=f"(d[60]), "=f"(d[61]), "=f"(d[62]), "=f"(d[63]),
          "=f"(d[64]), "=f"(d[65]), "=f"(d[66]), "=f"(d[67]), "=f"(d[68]), "=f"(d[69]), "=f"(d[70]), "=f"(d[71]),
          "=f"(d[72]), "=f"(d[73]), "=f"(d[74]), "=f"(d[75]), "=f"(d[76]), "=f"(d[77]), "=f"(d[78]), "=f"(d[79]),
          "=f"(d[80]), "=f"(d[81]), "=f"(d[82]), "=f"(d[83]), "=f"(d[84]), "=f"(d[85]), "=f"(d[86]), "=f"(d[87]),
          "=f"(d[88]), "=f"(d[89]), "=f"(d[90]), "=f"(d[91]), "=f"(d[92]), "=f"(d[93]), "=f"(d[94]), "=f"(d[95])
        : "l"(descA), "l"(descB));
}

__device__ __forceinline__ void wgmma_n160_ss_tb(float (&d)[80], uint64_t descA, uint64_t descB, int scaleD) {
    asm volatile("{\n.reg .pred p;\nsetp.ne.b32 p, %82, 0;\n"
        "wgmma.mma_async.sync.aligned.m64n160k16.f32.bf16.bf16 {"
        "%0, %1, %2, %3, %4, %5, %6, %7, %8, %9, %10, %11, %12, %13, %14, %15, "
        "%16, %17, %18, %19, %20, %21, %22, %23, %24, %25, %26, %27, %28, %29, %30, %31, "
        "%32, %33, %34, %35, %36, %37, %38, %39, %40, %41, %42, %43, %44, %45, %46, %47, "
        "%48, %49, %50, %51, %52, %53, %54, %55, %56, %57, %58, %59, %60, %61, %62, %63, "
        "%64, %65, %66, %67, %68, %69, %70, %71, %72, %73, %74, %75, %76, %77, %78, %79}, "
        "%80, %81, p, 1, 1, 0, 1;\n}\n"
        : "+f"(d[0]), "+f"(d[1]), "+f"(d[2]), "+f"(d[3]), "+f"(d[4]), "+f"(d[5]), "+f"(d[6]), "+f"(d[7]),
          "+f"(d[8]), "+f"(d[9]), "+f"(d[10]), "+f"(d[11]), "+f"(d[12]), "+f"(d[13]), "+f"(d[14]), "+f"(d[15]),
          "+f"(d[16]), "+f"(d[17]), "+f"(d[18]), "+f"(d[19]), "+f"(d[20]), "+f"(d[21]), "+f"(d[22]), "+f"(d[23]),
          "+f"(d[24]), "+f"(d[25]), "+f"(d[26]), "+f"(d[27]), "+f"(d[28]), "+f"(d[29]), "+f"(d[30]), "+f"(d[31]),
          "+f"(d[32]), "+f"(d[33]), "+f"(d[34]), "+f"(d[35]), "+f"(d[36]), "+f"(d[37]), "+f"(d[38]), "+f"(d[39]),
          "+f"(d[40]), "+f"(d[41]), "+f"(d[42]), "+f"(d[43]), "+f"(d[44]), "+f"(d[45]), "+f"(d[46]), "+f"(d[47]),
          "+f"(d[48]), "+f"(d[49]), "+f"(d[50]), "+f"(d[51]), "+f"(d[52]), "+f"(d[53]), "+f"(d[54]), "+f"(d[55]),
          "+f"(d[56]), "+f"(d[57]), "+f"(d[58]), "+f"(d[59]), "+f"(d[60]), "+f"(d[61]), "+f"(d[62]), "+f"(d[63]),
          "+f"(d[64]), "+f"(d[65]), "+f"(d[66]), "+f"(d[67]), "+f"(d[68]), "+f"(d[69]), "+f"(d[70]), "+f"(d[71]),
          "+f"(d[72]), "+f"(d[73]), "+f"(d[74]), "+f"(d[75]), "+f"(d[76]), "+f"(d[77]), "+f"(d[78]), "+f"(d[79])
        : "l"(descA), "l"(descB), "r"(scaleD));
}

__device__ __forceinline__ void wgmma_n64_ss(float (&d)[32], uint64_t descA, uint64_t descB, int scaleD) {
    asm volatile("{\n.reg .pred p;\nsetp.ne.b32 p, %34, 0;\n"
        "wgmma.mma_async.sync.aligned.m64n64k16.f32.bf16.bf16 {"
        "%0, %1, %2, %3, %4, %5, %6, %7, %8, %9, %10, %11, %12, %13, %14, %15, "
        "%16, %17, %18, %19, %20, %21, %22, %23, %24, %25, %26, %27, %28, %29, %30, %31}, "
        "%32, %33, p, 1, 1, 0, 0;\n}\n"
        : "+f"(d[0]), "+f"(d[1]), "+f"(d[2]), "+f"(d[3]), "+f"(d[4]), "+f"(d[5]), "+f"(d[6]), "+f"(d[7]),
          "+f"(d[8]), "+f"(d[9]), "+f"(d[10]), "+f"(d[11]), "+f"(d[12]), "+f"(d[13]), "+f"(d[14]), "+f"(d[15]),
          "+f"(d[16]), "+f"(d[17]), "+f"(d[18]), "+f"(d[19]), "+f"(d[20]), "+f"(d[21]), "+f"(d[22]), "+f"(d[23]),
          "+f"(d[24]), "+f"(d[25]), "+f"(d[26]), "+f"(d[27]), "+f"(d[28]), "+f"(d[29]), "+f"(d[30]), "+f"(d[31])
        : "l"(descA), "l"(descB), "r"(scaleD));
}

__device__ __forceinline__ void wgmma_n64_ss_z(float (&d)[32], uint64_t descA, uint64_t descB) {
    asm volatile("{\n.reg .pred p;\nsetp.ne.b32 p, 0, 0;\n"
        "wgmma.mma_async.sync.aligned.m64n64k16.f32.bf16.bf16 {"
        "%0, %1, %2, %3, %4, %5, %6, %7, %8, %9, %10, %11, %12, %13, %14, %15, "
        "%16, %17, %18, %19, %20, %21, %22, %23, %24, %25, %26, %27, %28, %29, %30, %31}, "
        "%32, %33, p, 1, 1, 0, 0;\n}\n"
        : "=f"(d[0]), "=f"(d[1]), "=f"(d[2]), "=f"(d[3]), "=f"(d[4]), "=f"(d[5]), "=f"(d[6]), "=f"(d[7]),
          "=f"(d[8]), "=f"(d[9]), "=f"(d[10]), "=f"(d[11]), "=f"(d[12]), "=f"(d[13]), "=f"(d[14]), "=f"(d[15]),
          "=f"(d[16]), "=f"(d[17]), "=f"(d[18]), "=f"(d[19]), "=f"(d[20]), "=f"(d[21]), "=f"(d[22]), "=f"(d[23]),
          "=f"(d[24]), "=f"(d[25]), "=f"(d[26]), "=f"(d[27]), "=f"(d[28]), "=f"(d[29]), "=f"(d[30]), "=f"(d[31])
        : "l"(descA), "l"(descB));
}

__device__ __forceinline__ void wgmma_n24_rs_tb(float (&d)[12], uint32_t a0, uint32_t a1, uint32_t a2, uint32_t a3, uint64_t descB, int scaleD) {
    asm volatile("{\n.reg .pred p;\nsetp.ne.b32 p, %17, 0;\n"
        "wgmma.mma_async.sync.aligned.m64n24k16.f32.bf16.bf16 {"
        "%0, %1, %2, %3, %4, %5, %6, %7, %8, %9, %10, %11}, "
        "{%12, %13, %14, %15}, %16, p, 1, 1, 1;\n}\n"
        : "+f"(d[0]), "+f"(d[1]), "+f"(d[2]), "+f"(d[3]), "+f"(d[4]), "+f"(d[5]), "+f"(d[6]), "+f"(d[7]),
          "+f"(d[8]), "+f"(d[9]), "+f"(d[10]), "+f"(d[11])
        : "r"(a0), "r"(a1), "r"(a2), "r"(a3), "l"(descB), "r"(scaleD));
}

__device__ __forceinline__ void cnt_signal(int idx) {
    asm volatile("fence.acq_rel.gpu;\nred.relaxed.gpu.global.add.u32 [%0], 1;"
                 ::"l"(g_cnt + idx * 32) : "memory");
}
__device__ __forceinline__ void cnt_wait(int idx, uint32_t target) {
    const uint32_t* p = g_cnt + idx * 32;
#pragma unroll 1
    for (uint32_t i = 0; i < (1u << 22); i++) {
        uint32_t v;
        asm volatile("ld.acquire.gpu.global.u32 %0, [%1];" : "=r"(v) : "l"(p) : "memory");
        if ((int32_t)(v - target) >= 0) break;
    }
    asm volatile("fence.proxy.async.global;" ::: "memory");
}
__device__ __forceinline__ void cluster_arrive() { asm volatile("barrier.cluster.arrive.release.aligned;" ::: "memory"); }
__device__ __forceinline__ void cluster_arrive_relaxed() { asm volatile("barrier.cluster.arrive.relaxed.aligned;" ::: "memory"); }
__device__ __forceinline__ void cluster_wait() { asm volatile("barrier.cluster.wait.acquire.aligned;" ::: "memory"); }
__device__ __forceinline__ void bulk_wait_read() { asm volatile("cp.async.bulk.wait_group.read 0;" ::: "memory"); }

__device__ __forceinline__ float gelu_tanh(float x) {
    const float u = x * (0.7978845608028654f + 0.035677408136300125f * x * x);
    float t;
    asm("tanh.approx.f32 %0, %1;" : "=f"(t) : "f"(u));
    const float h = 0.5f * x;
    return fmaf(h, t, h);
}
__device__ __forceinline__ void release_stage(uint32_t bar, uint32_t peer, int lane) {
    if (lane == 0) { mbar_arrive(bar); mbar_arrive_cluster(bar, peer); }
}

constexpr int SM_RING = 163840;
constexpr int SM_Q = 2 * IMG_BYTES, SM_ZERO = SM_Q + 24576;
constexpr int G2_STAGE = 8192 + 20480;
constexpr int SM_MISC = 229376;
constexpr int SM_BIAS = SM_MISC, SM_RED = SM_BIAS + 384, SM_BAR = SM_RED + 128;
constexpr int B_A = 0, B_F1 = 10, B_E1 = 14, B_F2 = 18, B_E2 = 23, B_KV = 28, B_Q = 45, B_F3 = 47, B_E3 = 55, B_ST = 63, B_STAT = 65, B_AUX = 66, B_AUX2 = 67, B_COUNT = 68;
constexpr int SM_EPOCH = SM_BAR + 544;
constexpr int SM_CS = SM_EPOCH + 16;
constexpr int SM_DBG = SM_CS + 1728;
constexpr int SM_TOTAL = SM_DBG + 128;
static_assert(SM_TOTAL <= 232448, "shared memory budget");

struct Maps { CUtensorMap x, wqkv, w1, h, o, wo, w2; };

__device__ __forceinline__ uint32_t bf2_fma(uint32_t a, uint32_t b, uint32_t c) {
    uint32_t r;
    asm("fma.rn.bf16x2 %0, %1, %2, %3;" : "=r"(r) : "r"(a), "r"(b), "r"(c));
    return r;
}
__device__ __forceinline__ uint32_t lop_and_or(uint32_t a, uint32_t m, uint32_t o) {
    uint32_t r;
    asm("lop3.b32 %0, %1, %2, %3, 0xEA;" : "=r"(r) : "r"(a), "r"(m), "r"(o));
    return r;
}
struct ExpConst { uint32_t mask, slope; };
__device__ __forceinline__ ExpConst make_exp_const() {
    ExpConst k;
    asm volatile("mov.b32 %0, 0x007F007F;" : "=r"(k.mask));
    asm volatile("mov.b32 %0, 0x3EF83EF8;" : "=r"(k.slope));
    return k;
}
__device__ __forceinline__ uint32_t exp2_pair_fma(float t0, float t1, const ExpConst& k) {
    const uint32_t L = __byte_perm(__float_as_uint(t0), __float_as_uint(t1), 0x6521);
    const uint32_t g = lop_and_or(L, k.mask, 0x3F803F80u);
    const uint32_t u = bf2_fma(g, k.slope, 0xBF37BF37u);
    const uint32_t e = bf2_fma(u, u, 0xBD71BD71u);
    return bf2_fma(L, e, L);
}
template <int SHIFT>
__device__ __forceinline__ void exp_tile(const float (&s)[32], uint32_t (&p)[16], const ExpConst& k) {
#pragma unroll
    for (int b = 0; b < 8; b++) {
        if ((EMU_MASK >> (b + SHIFT)) & 1) {
            p[2 * b] = exp2_pair_fma(s[4 * b], s[4 * b + 1], k);
            p[2 * b + 1] = exp2_pair_fma(s[4 * b + 2], s[4 * b + 3], k);
        } else {
            p[2 * b] = pack_bf16(ex2(s[4 * b]), ex2(s[4 * b + 1]));
            p[2 * b + 1] = pack_bf16(ex2(s[4 * b + 2]), ex2(s[4 * b + 3]));
        }
    }
}

__device__ __forceinline__ void qk_tile(float (&s)[32], uint64_t dQ, uint64_t dQ2, uint64_t dK) {
    wg_fence();
    wgmma_n64_ss_z(s, dQ, dK);
    wgmma_n64_ss(s, dQ2, dK + 16, 1);
    wg_commit();
}
__device__ __forceinline__ void pv_tile(float (&o)[12], const uint32_t (&p)[16], uint64_t dV) {
    wg_fence();
#pragma unroll
    for (int ks = 0; ks < 4; ks++)
        wgmma_n24_rs_tb(o, p[4 * ks], p[4 * ks + 1], p[4 * ks + 2], p[4 * ks + 3], dV + ks * 48, 1);
    wg_commit();
}
__device__ __forceinline__ void store_o(const float (&o)[12], int h, int rbase, int lane) {
    const int g = lane >> 2, c = lane & 3;
    const bool odd = h & 1;
    const int lsrc = (lane & ~3) | (odd ? 0 : 2);
    const float i0 = 1.f / __shfl_sync(~0u, o[8], lsrc), i1 = 1.f / __shfl_sync(~0u, o[10], lsrc);
    __nv_bfloat16* dst = g_o + (size_t)(rbase + g) * DM + h * 20;
    const int d0 = (odd ? 4 : 0) + 2 * c, d1 = d0 + 8, d2 = odd ? 2 * c - 4 : 16 + 2 * c;
    *(uint32_t*)(dst + d0) = pack_bf16(o[0] * i0, o[1] * i0);
    *(uint32_t*)(dst + d1) = pack_bf16(o[4] * i0, o[5] * i0);
    *(uint32_t*)(dst + 8 * DM + d0) = pack_bf16(o[2] * i1, o[3] * i1);
    *(uint32_t*)(dst + 8 * DM + d1) = pack_bf16(o[6] * i1, o[7] * i1);
    if (odd ? (c >= 2) : (c < 2)) {
        *(uint32_t*)(dst + d2) = pack_bf16(o[8] * i0, o[9] * i0);
        *(uint32_t*)(dst + 8 * DM + d2) = pack_bf16(o[10] * i1, o[11] * i1);
    }
}

__device__ __forceinline__ void attn_rows_maxshift(uint32_t sK, uint32_t barKV, uint64_t dQ, uint64_t dQ2, int h, int rbase) {
    const int lane = threadIdx.x & 31;
    const uint64_t dK0 = make_desc(sK, 128, 384, 0), dV0 = make_desc(sK + IMG_BYTES, 384, 128, 0);
    float o[12], s[32];
    uint32_t p[16];
#pragma unroll
    for (int i = 0; i < 12; i++) o[i] = 0.f;
    float m0 = -3.0e38f, m1 = -3.0e38f;
    mbar_wait(barKV + 128, 0);
#pragma unroll 1
    for (int t = 0; t < 32; t++) {
        mbar_wait(barKV + (t >> 1) * 8, 0);
        qk_tile(s, dQ, dQ2, dK0 + t * 192);
        wg_wait<0>();
        fence_regs(s);
        const uint32_t mask = EMU_MASK >> ((t & 1) * 8);
        float n0 = m0, n1 = m1;
#pragma unroll
        for (int b = 0; b < 8; b++) {
            const bool emu = (mask >> b) & 1;
            const float f = emu ? 0.5f : 1.f, off = emu ? -383.00390625f : 0.f;
#pragma unroll
            for (int i = 0; i < 4; i++) s[4 * b + i] = fmaf(s[4 * b + i], f, off);
            n0 = fmaxf(n0, fmaxf(s[4 * b], s[4 * b + 1]));
            n1 = fmaxf(n1, fmaxf(s[4 * b + 2], s[4 * b + 3]));
        }
        n0 = fmaxf(n0, __shfl_xor_sync(~0u, n0, 1)); n0 = fmaxf(n0, __shfl_xor_sync(~0u, n0, 2));
        n1 = fmaxf(n1, __shfl_xor_sync(~0u, n1, 1)); n1 = fmaxf(n1, __shfl_xor_sync(~0u, n1, 2));
        const float c0 = ex2(m0 - n0), c1 = ex2(m1 - n1);
        m0 = n0; m1 = n1;
#pragma unroll
        for (int b = 0; b < 3; b++) { o[4 * b] *= c0; o[4 * b + 1] *= c0; o[4 * b + 2] *= c1; o[4 * b + 3] *= c1; }
#pragma unroll
        for (int b = 0; b < 8; b++) {
            p[2 * b] = pack_bf16(ex2(s[4 * b] - m0), ex2(s[4 * b + 1] - m0));
            p[2 * b + 1] = pack_bf16(ex2(s[4 * b + 2] - m1), ex2(s[4 * b + 3] - m1));
        }
        pv_tile(o, p, dV0 + t * 192);
        wg_wait<0>();
        fence_regs(o);
    }
    store_o(o, h, rbase, lane);
}

__global__ void __launch_bounds__(512, 1) __cluster_dims__(2, 1, 1)
k_fused(const __grid_constant__ Maps tm, const __nv_bfloat16* __restrict__ x, const uint8_t* __restrict__ wqkv,
        const uint8_t* __restrict__ w1, const uint8_t* __restrict__ w2, const uint8_t* __restrict__ wo,
        const __nv_bfloat16* __restrict__ b1, const __nv_bfloat16* __restrict__ b2, __nv_bfloat16* __restrict__ out) {
    extern __shared__ __align__(1024) uint8_t smem[];
    const uint32_t sb = smem_u32(smem);
    const uint32_t bar = sb + SM_BAR;
    const int warp = __shfl_sync(~0u, threadIdx.x >> 5, 0), lane = threadIdx.x & 31;
    const int wgi = warp >> 2, w4 = warp & 3, g = lane >> 2, c = lane & 3;
    const uint32_t rank = blockIdx.x & 1, peer = rank ^ 1;
    const int cl = blockIdx.x >> 1;
    const int cg = cl >> 3, rb = (cl & 7) * 2 + rank;

    if (threadIdx.x == 0) TL(0, 0);
    if (warp == 15 && lane < 4) prefetch_map(lane == 0 ? &tm.x : lane == 1 ? &tm.wqkv : lane == 2 ? &tm.w1 : &tm.h);
    if (elect_one()) {
#pragma unroll
        for (int j = 0; j < 5; j++) {
            const int i = warp * 5 + j;
            const int cnt = (i >= B_E1 && i < B_F2) || (i >= B_E2 && i < B_KV) ? 16
                          : (i >= B_E3 && i <= B_ST) || i == B_STAT ? 8 : i == B_ST + 1 ? 2 : i >= B_AUX ? 7 : 1;
            if (i < B_COUNT) mbar_init(bar + i * 8, cnt);
        }
        fence_barrier_init();
    }
    __syncthreads();
    if (threadIdx.x == 0) TL(0, 1);
    cluster_arrive_relaxed();
    cluster_wait();
    if (threadIdx.x == 0) TL(0, 3);

    {
        const uint32_t sB = sb + SM_RING;
        if (threadIdx.x == 0) TL(1, 0);
        if (wgi < 2) {
            reg_dealloc<56>();
            if (threadIdx.x == 0) TL(4, 2);
            if (warp == 0) {
#pragma unroll 1
                for (int it = 0; it < 20; it++) {
                    const int s = it & 3;
                    const int kb = it < 2 ? it : (it & 1) ? (it + 1) >> 1 : 10;
                    if (it >= 4) mbar_wait(bar + (B_E1 + s) * 8, ((it >> 2) - 1) & 1);
                    else if (it > 0) __nanosleep(PACE_NS);
                    if (elect_one()) {
                        if (kb < 10) {
                            mbar_expect_tx(bar + (B_A + kb) * 8, 16384);
                            tma_load(sb + kb * 16384, &tm.x, kb * 64, rb * 128, bar + (B_A + kb) * 8);
                        }
                        const uint32_t dst = sB + s * 16384 + rank * 8192, fb = bar + (B_F1 + s) * 8;
                        const int c0 = cg * 240 + rank * 128;
                        mbar_expect_tx(fb, 16384);
                        tma_load_mc(dst, &tm.wqkv, c0, it * 32, fb, 3);
                        tma_load_mc(dst + 4096, &tm.wqkv, c0 + 64, it * 32, fb, 3);
                    }
                    __syncwarp();
                    if (lane == 0 && it < 8) TL(5, it) ;
                }
#pragma unroll 1
                for (int it = 0; it < 20; it++) {
                    const int s = it % 5;
                    if (it < 5) { if (it != 3) mbar_wait(bar + (B_E1 + (it == 4 ? 3 : it)) * 8, 0); }
                    else mbar_wait(bar + (B_E2 + s) * 8, ((it / 5) - 1) & 1);
                    if (elect_one()) {
                        const uint32_t dst = sB + s * 12288, fb = bar + (B_F2 + s) * 8;
                        mbar_expect_tx(fb, 12288);
                        if ((it & 1) == (int)rank) {
                            tma_load_mc(dst, &tm.w1, cg * 192, it * 32, fb, 3);
                            tma_load_mc(dst + 4096, &tm.w1, cg * 192 + 64, it * 32, fb, 3);
                        } else {
                            tma_load_mc(dst + 8192, &tm.w1, cg * 192 + 128, it * 32, fb, 3);
                        }
                    }
                    __syncwarp();
                }
            } else {
                const int ht = threadIdx.x - 32;
                if (ht == 192) *reinterpret_cast<volatile uint32_t*>(smem + SM_EPOCH) = *(volatile uint32_t*)&g_epoch;
                auto slab_sum = [&](const uint32_t* src, int pitch) {
                    float s0 = 0.f, s1 = 0.f;
                    uint32_t v[40];
#pragma unroll
                    for (int k = 0; k < 40; k++) v[k] = __ldg(src + k * pitch);
#pragma unroll
                    for (int k = 0; k < 40; k++) { s0 += bf_lo(v[k]); s1 += bf_hi(v[k]); }
                    return make_float2(s0, s1);
                };
                auto gather = [&](int idx) {
                    float s0 = 0.f, s1 = 0.f;
#pragma unroll
                    for (int r = 0; r < 16; r++) {
                        const float2 v = __ldcg(g_csp + r * 1728 + cg * 216 + idx);
                        s0 += v.x; s1 += v.y;
                    }
                    reinterpret_cast<float2*>(smem + SM_CS)[idx] = make_float2(s0, s1);
                };
                if (warp >= 5) {
#pragma unroll 1
                    for (int r0 = (warp - 5) * 6; r0 < min(16, (warp - 5) * 6 + 6); r0 += 3) {
                        uint2 xv[3][5];
#pragma unroll
                        for (int u = 0; u < 3; u++)
#pragma unroll
                            for (int i = 0; i < 5; i++)
                                xv[u][i] = __ldg(reinterpret_cast<const uint2*>(x + (size_t)(rb * 128 + cg * 16 + min(r0 + u, 15)) * DM) + lane + 32 * i);
#pragma unroll
                        for (int u = 0; u < 3; u++) {
                            float sm = 0.f;
#pragma unroll
                            for (int i = 0; i < 5; i++) sm += (bf_lo(xv[u][i].x) + bf_hi(xv[u][i].x)) + (bf_lo(xv[u][i].y) + bf_hi(xv[u][i].y));
#pragma unroll
                            for (int o = 16; o; o >>= 1) sm += __shfl_xor_sync(~0u, sm, o);
                            const float mu = sm * (1.f / DM);
                            float q = 0.f;
#pragma unroll
                            for (int i = 0; i < 5; i++) {
                                const float d0 = bf_lo(xv[u][i].x) - mu, d1 = bf_hi(xv[u][i].x) - mu;
                                const float d2 = bf_lo(xv[u][i].y) - mu, d3 = bf_hi(xv[u][i].y) - mu;
                                q = fmaf(d0, d0, fmaf(d1, d1, fmaf(d2, d2, fmaf(d3, d3, q))));
                            }
#pragma unroll
                            for (int o = 16; o; o >>= 1) q += __shfl_xor_sync(~0u, q, o);
                            const float var = q * (1.f / DM);
                            const float r1 = 1.f / sqrtf(var + LN_EPS);
                            const float r2 = 1.f / sqrtf(var * r1 * r1 + LN_EPS);
                            if (lane == 0 && r0 + u < 16) g_stat[rb * 128 + cg * 16 + r0 + u] = make_float4(mu, r1, r1 * r2, 0.f);
                        }
                    }
                }
                if (ht < 120)
                    g_csp[rb * 1728 + cg * 216 + ht] = slab_sum(reinterpret_cast<const uint32_t*>(wqkv) + rb * 40 * 960 + cg * 120 + ht, 960);
                if (threadIdx.x == 64) IT(3, 0);
                asm volatile("bar.sync 8, 224;" ::: "memory");
                const uint32_t epoch = *reinterpret_cast<volatile uint32_t*>(smem + SM_EPOCH);
                if (warp == 6) { if (elect_one()) cnt_signal(CNT_CS + cg); __syncwarp(); }
                if (warp == 7) { if (elect_one()) cnt_signal(CNT_ST + rb); __syncwarp(); }
                if (ht < 96) {
                    g_csp[rb * 1728 + cg * 216 + 120 + ht] = slab_sum(reinterpret_cast<const uint32_t*>(w1) + rb * 40 * 768 + cg * 96 + ht, 768);
                    reinterpret_cast<uint32_t*>(smem + SM_BIAS)[ht] = __ldg(reinterpret_cast<const uint32_t*>(b1 + cg * 192) + ht);
                }
                asm volatile("bar.sync 8, 224;" ::: "memory");
                if (warp == 6) { if (elect_one()) cnt_signal(CNT_CS2 + cg); __syncwarp(); }
                if (threadIdx.x == 64) IT(3, 2);
                if (lane == 0) { cnt_wait(CNT_CS + cg, (epoch + 1) * 16); cnt_wait(CNT_ST + rb, (epoch + 1) * 8); }
                __syncwarp();
                if (threadIdx.x == 64) IT(3, 4);
                if (ht < 120) gather(ht);
                __syncwarp();
                if (threadIdx.x == 64) IT(3, 5);
                if (lane == 0) mbar_arrive(bar + B_AUX * 8);
                if (warp == 3 && elect_one()) {
                    prefetch_l2(w2 + blockIdx.x * 15360, 15360);
                    prefetch_l2(wo + blockIdx.x * 6400, 6400);
                }
                if (lane == 0) cnt_wait(CNT_CS2 + cg, (epoch + 1) * 16);
                __syncwarp();
                if (ht < 96) gather(120 + ht);
                __syncwarp();
                if (lane == 0) mbar_arrive(bar + B_AUX2 * 8);
                if (warp == 4) {
                    mbar_wait(bar + B_ST * 8, 0);
                    if (elect_one()) cnt_signal(CNT_QKV + cg);
                    __syncwarp();
                }
            }
            asm volatile("bar.sync %0, 128;" ::"r"(wgi + 3) : "memory");
            reg_alloc<128>();
        } else {
            reg_alloc<200>();
            if (threadIdx.x == 256) TL(4, 0);
            const int wi = wgi - 2;
            const int row0 = rb * 128 + wi * 64 + w4 * 16 + g;
            const uint32_t sAw = sb + wi * 8192;
            const int rbk = row0 >> 3, hs0 = cg * 12;
            if (threadIdx.x == 256) TL(4, 1);
            float accA[100], accB[20];
            const uint64_t dA0 = make_desc(sAw, 16, 1024, 1), dB0 = make_desc(sB, 4096, 1024, 1);
#pragma unroll 2
            for (int it = 0; it < 20; it++) {
                const int s = it & 3;
                if (!(it & 1)) mbar_wait(bar + (B_A + (it >> 1)) * 8, 0);
                if (threadIdx.x == 256 && it == 0) TL(0, 2);
                if (threadIdx.x == 256 && it == 2) TL(4, 3);
                if (threadIdx.x == 256) IT(0, it);
                mbar_wait(bar + (B_F1 + s) * 8, (it >> 2) & 1);
                if (threadIdx.x == 256) IT(1, it);
                const uint64_t dA = dA0 + (it >> 1) * 1024 + (it & 1) * 4, dB = dB0 + s * 1024;
                wg_fence();
                wgmma_n40_ss_tb(accB, dA, dB + 769, it > 0);
                wgmma_n40_ss_tb(accB, dA + 2, dB + 769 + 128, 1);
                wgmma_n200_ss_tb(accA, dA, dB, it > 0);
                wgmma_n200_ss_tb(accA, dA + 2, dB + 128, 1);
                wg_commit();
                if (it > 0) { wg_wait<1>(); release_stage(bar + (B_E1 + ((it - 1) & 3)) * 8, peer, lane); }
            }
            if (threadIdx.x == 256) IT(2, 0);
            mbar_wait(bar + B_AUX * 8, 0);
            if (threadIdx.x == 256) IT(2, 1);
            const float4 st0 = __ldcg(g_stat + row0), st1 = __ldcg(g_stat + row0 + 8);
            wg_wait<0>();
            release_stage(bar + (B_E1 + 3) * 8, peer, lane);
            fence_regs(accA);
            fence_regs(accB);
            if (threadIdx.x == 256) TL(1, 1);
            const float2* cs = reinterpret_cast<const float2*>(smem + SM_CS) + c;
            uint8_t* img = g_img + (size_t)hs0 * IMG_BYTES + rbk * 384 + g * 16 + c * 4;
            const bool emu0 = (EMU_MASK >> (rbk & 15)) & 1, emu1 = (EMU_MASK >> ((rbk + 1) & 15)) & 1;
            const bool low = c < 2;
            uint32_t pk[60];
#pragma unroll
            for (int m = 0; m < 6; m++) {
                const int which = (hs0 + 2 * m) >> 5;
                const float m0 = st0.y * (which == 0 ? QSCALE : (which == 1 && emu0) ? 2.f : 1.f);
                const float m1 = st1.y * (which == 0 ? QSCALE : (which == 1 && emu1) ? 2.f : 1.f);
                const float d0 = -st0.x * m0, d1 = -st1.x * m1;
                const float* a = m < 5 ? &accA[20 * m] : accB;
#pragma unroll
                for (int b = 0; b < 5; b++) {
                    const float2 cv = cs[(5 * m + b) * 4];
                    pk[10 * m + 2 * b] = pack_bf16(fmaf(a[4 * b], m0, d0 * cv.x), fmaf(a[4 * b + 1], m0, d0 * cv.y));
                    pk[10 * m + 2 * b + 1] = pack_bf16(fmaf(a[4 * b + 2], m1, d1 * cv.x), fmaf(a[4 * b + 3], m1, d1 * cv.y));
                }
            }
            const float r20 = st0.z, r21 = st1.z, e20 = -st0.x * st0.z, e21 = -st1.x * st1.z;
            if (threadIdx.x == 256) IT(2, 2);
            float acc2[96];
#pragma unroll
            for (int it = 0; it < 20; it++) {
                const int s = it % 5;
                if (threadIdx.x == 256) IT(0, 20 + it);
                mbar_wait(bar + (B_F2 + s) * 8, (it / 5) & 1);
                if (threadIdx.x == 256) IT(1, 20 + it);
                wg_fence();
                const uint64_t dA = make_desc(sAw + (it >> 1) * 16384 + (it & 1) * 64, 16, 1024, 1);
                const uint64_t dB = make_desc(sB + s * 12288, 4096, 1024, 1);
                if (it == 0) wgmma_n192_ss_tb_z(acc2, dA, dB); else wgmma_n192_ss_tb(acc2, dA, dB, 1);
                wgmma_n192_ss_tb(acc2, dA + 2, dB + 128, 1);
                wg_commit();
                if (it > 0) {
                    wg_wait<1>();
                    if (it <= 15) release_stage(bar + (B_E2 + (it - 1) % 5) * 8, peer, lane);
                }
                if (it < 12) {
                    const int m = it / 2, part = it % 2;
                    const int hs = hs0 + 2 * m, which = hs >> 5;
                    const uint32_t* a = pk + 10 * m;
                    uint8_t* pe = img + (2 * m) * IMG_BYTES;
                    uint8_t* po = pe + IMG_BYTES;
                    if (part == 0) {
                        const uint32_t padv = which == 0 ? 0x3F803F80u : which == 1 ? 0xBFFF4440u : 0x00003F80u;
                        const uint32_t p0 = ((c & 1) || (which == 1 && !emu0)) ? 0u : padv;
                        const uint32_t p1 = ((c & 1) || (which == 1 && !emu1)) ? 0u : padv;
                        *(uint32_t*)(pe) = a[0];
                        *(uint32_t*)(pe + 128) = a[2];
                        *(uint32_t*)(pe + 256) = low ? a[4] : p0;
                        *(uint32_t*)(pe + 384) = a[1];
                        *(uint32_t*)(pe + 512) = a[3];
                        *(uint32_t*)(pe + 640) = low ? a[5] : p1;
                        *(uint32_t*)(po + 256) = low ? p0 : a[4];
                        *(uint32_t*)(po + 640) = low ? p1 : a[5];
                    } else {
                        *(uint32_t*)(po) = a[6];
                        *(uint32_t*)(po + 128) = a[8];
                        *(uint32_t*)(po + 384) = a[7];
                        *(uint32_t*)(po + 512) = a[9];
                        if (which < 2) {
                            const uint32_t u0 = bf2_fma(a[4], a[4], 0u), u1 = bf2_fma(a[5], a[5], 0u);
                            const uint32_t pe0 = bf2_fma(a[0], a[0], bf2_fma(a[2], a[2], low ? u0 : 0u));
                            const uint32_t pe1 = bf2_fma(a[1], a[1], bf2_fma(a[3], a[3], low ? u1 : 0u));
                            const uint32_t po0 = bf2_fma(a[6], a[6], bf2_fma(a[8], a[8], low ? 0u : u0));
                            const uint32_t po1 = bf2_fma(a[7], a[7], bf2_fma(a[9], a[9], low ? 0u : u1));
                            const float e0 = bf_lo(pe0) + bf_hi(pe0), e1 = bf_lo(pe1) + bf_hi(pe1);
                            const float o0 = bf_lo(po0) + bf_hi(po0), o1 = bf_lo(po1) + bf_hi(po1);
                            const bool b0 = c & 1, b1_ = c & 2;
                            const float x0 = (b0 ? e1 : e0) + __shfl_xor_sync(~0u, b0 ? e0 : e1, 1);
                            const float x1 = (b0 ? o1 : o0) + __shfl_xor_sync(~0u, b0 ? o0 : o1, 1);
                            float y = (b1_ ? x1 : x0) + __shfl_xor_sync(~0u, b1_ ? x0 : x1, 2);
                            if (which == 1 && (b0 ? emu1 : emu0)) y *= 0.25f;
                            g_nrm[(hs + (c >> 1)) * SEQ + row0 + (c & 1) * 8] = y;
                        }
                    }
                    if (it == 11) { __syncwarp(); if (lane == 0) mbar_arrive(bar + B_ST * 8); }
                }
            }
            wg_wait<0>();
            fence_regs(acc2);
            if (threadIdx.x == 256) TL(1, 2);
            mbar_wait(bar + B_AUX2 * 8, 0);
            const uint32_t* bias = reinterpret_cast<const uint32_t*>(smem + SM_BIAS) + c;
            const int mrow = w4 * 16 + (lane & 15);
            const uint32_t st_row = sAw + mrow * 128;
#pragma unroll
            for (int j = 0; j < 24; j += 2) {
                const uint32_t bA = bias[j * 4], bB = bias[j * 4 + 4];
                const float2 cA = cs[(30 + j) * 4], cB = cs[(31 + j) * 4];
                const float* a = acc2 + j * 4;
                const uint32_t r00 = pack_bf16(gelu_tanh(fmaf(a[0], r20, fmaf(e20, cA.x, bf_lo(bA)))), gelu_tanh(fmaf(a[1], r20, fmaf(e20, cA.y, bf_hi(bA)))));
                const uint32_t r10 = pack_bf16(gelu_tanh(fmaf(a[2], r21, fmaf(e21, cA.x, bf_lo(bA)))), gelu_tanh(fmaf(a[3], r21, fmaf(e21, cA.y, bf_hi(bA)))));
                const uint32_t r01 = pack_bf16(gelu_tanh(fmaf(a[4], r20, fmaf(e20, cB.x, bf_lo(bB)))), gelu_tanh(fmaf(a[5], r20, fmaf(e20, cB.y, bf_hi(bB)))));
                const uint32_t r11 = pack_bf16(gelu_tanh(fmaf(a[6], r21, fmaf(e21, cB.x, bf_lo(bB)))), gelu_tanh(fmaf(a[7], r21, fmaf(e21, cB.y, bf_hi(bB)))));
                const int chunk = (j & 7) + (lane >> 4);
                stmatrix_x4(st_row + (j >> 3) * 16384 + ((chunk ^ (mrow & 7)) << 4), r00, r10, r01, r11);
            }
            fence_proxy_async();
            asm volatile("bar.sync %0, 128;" ::"r"(wgi + 3) : "memory");
            if (w4 == 0 && lane == 0) {
#pragma unroll
                for (int b = 0; b < 3; b++) tma_store(&tm.h, sAw + b * 16384, cg * 192 + b * 64, rb * 128 + wi * 64);
                bulk_commit();
                bulk_wait_read();
            }
            __syncwarp();
            reg_dealloc<128>();
        }
        __syncthreads();
        if (threadIdx.x == 0) TL(1, 3);
    }

    {
        const uint32_t epoch = *reinterpret_cast<volatile uint32_t*>(smem + SM_EPOCH);
        const int h = blockIdx.x >> 2, qb = blockIdx.x & 3;
        const uint32_t sK = sb, sV = sb + IMG_BYTES, barKV = bar + B_KV * 8;
        if (threadIdx.x == 0) TL(2, 0);
        if (threadIdx.x < 192) *reinterpret_cast<uint4*>(smem + SM_ZERO + threadIdx.x * 16) = make_uint4(0, 0, 0, 0);
        fence_proxy_async();
        if (warp == 0) {
            if (elect_one()) {
                cnt_wait(CNT_QKV + h / 12, (epoch + 1) * 16);
                cnt_wait(CNT_QKV + (32 + h) / 12, (epoch + 1) * 16);
                cnt_wait(CNT_QKV + (64 + h) / 12, (epoch + 1) * 16);
                const uint8_t* gK = g_img + (size_t)(32 + h) * IMG_BYTES;
                const uint8_t* gV = g_img + (size_t)(64 + h) * IMG_BYTES;
                const uint8_t* gQ = g_img + (size_t)h * IMG_BYTES + qb * 64 * 384;
                mbar_expect_tx(barKV + 128, 6144);
                bulk_load(sK, gK, 6144, barKV + 128);
                for (int p = 0; p < 2; p++) {
                    mbar_expect_tx(bar + (B_Q + p) * 8, 12288);
                    bulk_load(sb + SM_Q + p * 12288, gQ + p * 12288, 12288, bar + (B_Q + p) * 8);
                }
                for (int i = 0; i < 16; i++) {
                    mbar_expect_tx(barKV + i * 8, i < 15 ? 12288 : 6144);
                    bulk_load(sV + i * 6144, gV + i * 6144, 6144, barKV + i * 8);
                    if (i < 15) bulk_load(sK + (i + 1) * 6144, gK + (i + 1) * 6144, 6144, barKV + i * 8);
                }
            }
            __syncwarp();
        }
        __syncthreads();
        if (threadIdx.x == 0) TL(2, 1);
        float* red = reinterpret_cast<float*>(smem + SM_RED);
        float kmax = 0.f, qmax = __ldcg(g_nrm + h * SEQ + qb * 512 + threadIdx.x);
#pragma unroll
        for (int i = 0; i < 4; i++) kmax = fmaxf(kmax, __ldcg(g_nrm + (32 + h) * SEQ + i * 512 + threadIdx.x));
#pragma unroll
        for (int o = 16; o; o >>= 1) {
            kmax = fmaxf(kmax, __shfl_xor_sync(~0u, kmax, o));
            qmax = fmaxf(qmax, __shfl_xor_sync(~0u, qmax, o));
        }
        if (lane == 0) { red[warp] = kmax; red[16 + warp] = qmax; }
        __syncthreads();
        kmax = red[lane & 15]; qmax = red[16 + (lane & 15)];
#pragma unroll
        for (int o = 8; o; o >>= 1) {
            kmax = fmaxf(kmax, __shfl_xor_sync(~0u, kmax, o));
            qmax = fmaxf(qmax, __shfl_xor_sync(~0u, qmax, o));
        }
        const bool safe = __all_sync(~0u, kmax * qmax * 1.1f <= SAFE_BOUND * SAFE_BOUND);
        const uint64_t dK0 = make_desc(sK, 128, 384, 0), dV0 = make_desc(sV, 384, 128, 0);
        auto publish_h = [&]() {
            if (warp == 8 || warp == 12) {
                if (lane == 0) { bulk_wait_all(); cnt_signal(CNT_H + rb); }
                __syncwarp();
            }
        };
        if (!safe) {
#pragma unroll 1
            for (int pass = 0; pass < 2; pass++) {
                const uint32_t sQ = sb + SM_Q + pass * 12288 + wgi * 3072;
                mbar_wait(bar + (B_Q + pass) * 8, 0);
                if (lane < 16) *reinterpret_cast<uint32_t*>(smem + (sQ - sb) + (w4 * 2 + (lane >> 3)) * 384 + 256 + (lane & 7) * 16 + ((h & 1) ? 0 : 8)) = 0u;
                fence_proxy_async();
                asm volatile("bar.sync %0, 128;" ::"r"(wgi + 3) : "memory");
                attn_rows_maxshift(sK, barKV, make_desc(sQ, 128, 384, 0), make_desc(sQ + 256, sb + SM_ZERO - (sQ + 256), 384, 0), h,
                                   qb * 512 + pass * 256 + wgi * 64 + w4 * 16);
                if (pass == 0) publish_h();
            }
        } else {
            const ExpConst kc = make_exp_const();
#pragma unroll 1
            for (int pass = 0; pass < 2; pass++) {
                const int rbase = qb * 512 + pass * 256 + wgi * 64 + w4 * 16;
                const uint32_t sQ = sb + SM_Q + pass * 12288 + wgi * 3072;
                const uint64_t dQ = make_desc(sQ, 128, 384, 0), dQ2 = make_desc(sQ + 256, sb + SM_ZERO - (sQ + 256), 384, 0);
                float o[12], sa[32], sc[32];
                uint32_t p[16];
#pragma unroll
                for (int i = 0; i < 12; i++) o[i] = 0.f;
                fence_regs(o);
                mbar_wait(bar + (B_Q + pass) * 8, 0);
                mbar_wait(barKV + 128, 0);
                qk_tile(sa, dQ, dQ2, dK0);
                wg_wait<0>();
                fence_regs(sa);
                uint64_t dK = dK0, dV = dV0;
                uint32_t bj = barKV;
#pragma unroll 1
                for (int j = 0; j < 16; j++) {
                    mbar_wait(bj, 0);
                    qk_tile(sc, dQ, dQ2, dK + 192);
                    wg_wait<1>();
                    exp_tile<0>(sa, p, kc);
                    pv_tile(o, p, dV);
                    wg_wait<1>();
                    fence_regs(sc);
                    mbar_wait(bj, 0);
                    qk_tile(sa, dQ, dQ2, dK + 384);
                    wg_wait<1>();
                    exp_tile<8>(sc, p, kc);
                    pv_tile(o, p, dV + 192);
                    wg_wait<1>();
                    fence_regs(sa);
                    dK += 384; dV += 384; bj += 8;
                }
                wg_wait<0>();
                fence_regs(o);
                store_o(o, h, rbase, lane);
                if (threadIdx.x == 0) TL(2, 2 + pass);
                if (pass == 0) publish_h();
            }
        }
        __syncthreads();
        if (threadIdx.x == 64) cnt_signal(CNT_O + qb);
        cluster_arrive_relaxed();
    }

    {
        const uint32_t epoch = *reinterpret_cast<volatile uint32_t*>(smem + SM_EPOCH);
        const int ct = cl & 3, rt = (cl >> 2) * 2 + rank;
        if (threadIdx.x == 0) TL(3, 0);
        const int orow = threadIdx.x >> 3, oseg = threadIdx.x & 7;
        const size_t ooff = (size_t)(rt * 64 + orow) * DM + ct * 160 + oseg * 20;
        uint2 xr[5], br[5];
#pragma unroll
        for (int i = 0; i < 5; i++) {
            xr[i] = __ldg(reinterpret_cast<const uint2*>(x + ooff) + i);
            br[i] = __ldg(reinterpret_cast<const uint2*>(b2 + ct * 160 + oseg * 20) + i);
        }
        cluster_wait();
        float* stg = reinterpret_cast<float*>(smem);
        if (warp == 4) {
            if (elect_one()) { prefetch_map(&tm.h); prefetch_map(&tm.o); prefetch_map(&tm.w2); prefetch_map(&tm.wo); cnt_wait(CNT_H + (rt >> 1), (epoch + 1) * 16); }
            __syncwarp();
#pragma unroll 1
            for (int kb = 0; kb < 34; kb++) {
                const int s = kb & 7;
                if (kb >= 8) mbar_wait(bar + (B_E3 + s) * 8, ((kb >> 3) - 1) & 1);
                if (elect_one()) {
                    if (kb == 24) { cnt_wait(CNT_O + (rt >> 3), (epoch + 1) * 32); TL(3, 1); }
                    const uint32_t dst = sb + s * G2_STAGE, fb = bar + (B_F3 + s) * 8;
                    const CUtensorMap* mA = kb < 24 ? &tm.h : &tm.o;
                    const CUtensorMap* mB = kb < 24 ? &tm.w2 : &tm.wo;
                    const int k0 = (kb < 24 ? kb : kb - 24) * 64;
                    mbar_expect_tx(fb, G2_STAGE);
                    tma_load(dst, mA, k0, rt * 64, fb);
                    const int first = ((kb & 1) == (int)rank) ? 0 : 3, last = ((kb & 1) == (int)rank) ? 3 : 5;
                    for (int b = first; b < last; b++) tma_load_mc(dst + 8192 + b * 4096, mB, ct * 160 + b * 32, k0, fb, 3);
                }
                __syncwarp();
            }
        } else if (wgi == 0) {
            float acc[80];
#pragma unroll 1
            for (int kb = 0; kb < 34; kb++) {
                const int s = kb & 7;
                mbar_wait(bar + (B_F3 + s) * 8, (kb >> 3) & 1);
                wg_fence();
                const uint64_t dA = make_desc(sb + s * G2_STAGE, 16, 1024, 1);
                const uint64_t dB = make_desc(sb + s * G2_STAGE + 8192, 4096, 512, 2);
#pragma unroll
                for (int kk = 0; kk < 4; kk++) wgmma_n160_ss_tb(acc, dA + kk * 2, dB + kk * 64, (kb | kk) != 0);
                wg_commit();
                if (kb > 0) {
                    wg_wait<1>();
                    if (kb <= 26) release_stage(bar + (B_E3 + ((kb - 1) & 7)) * 8, peer, lane);
                }
            }
            wg_wait<0>();
            fence_regs(acc);
            if (threadIdx.x == 0) TL(3, 2);
            const int r = w4 * 16 + g;
#pragma unroll
            for (int j = 0; j < 20; j++) {
                *reinterpret_cast<float2*>(stg + r * 168 + j * 8 + 2 * c) = make_float2(acc[4 * j], acc[4 * j + 1]);
                *reinterpret_cast<float2*>(stg + (r + 8) * 168 + j * 8 + 2 * c) = make_float2(acc[4 * j + 2], acc[4 * j + 3]);
            }
        }
        __syncthreads();
        const float4* sp = reinterpret_cast<const float4*>(stg + orow * 168 + oseg * 20);
#pragma unroll
        for (int i = 0; i < 5; i++) {
            const float4 a = sp[i];
            uint2 w;
            w.x = pack_bf16(a.x + bf_lo(br[i].x) + bf_lo(xr[i].x), a.y + bf_hi(br[i].x) + bf_hi(xr[i].x));
            w.y = pack_bf16(a.z + bf_lo(br[i].y) + bf_lo(xr[i].y), a.w + bf_hi(br[i].y) + bf_hi(xr[i].y));
            reinterpret_cast<uint2*>(out + ooff)[i] = w;
        }
        if (blockIdx.x == 0 && threadIdx.x == 0) g_epoch = epoch + 1;
        if (threadIdx.x == 0) TL(3, 3);
    }
    cluster_arrive_relaxed();
    cluster_wait();
}

typedef CUresult (*EncodeTiledFn)(CUtensorMap*, CUtensorMapDataType, cuuint32_t, void*, const cuuint64_t*,
                                  const cuuint64_t*, const cuuint32_t*, const cuuint32_t*, CUtensorMapInterleave,
                                  CUtensorMapSwizzle, CUtensorMapL2promotion, CUtensorMapFloatOOBfill);

CUtensorMap make_map(EncodeTiledFn enc, const void* ptr, int rows, int cols, int box_rows, int box_cols,
                     CUtensorMapSwizzle swz) {
    CUtensorMap m;
    cuuint64_t gd[2] = {(cuuint64_t)cols, (cuuint64_t)rows};
    cuuint64_t gs[1] = {(cuuint64_t)cols * 2};
    cuuint32_t bd[2] = {(cuuint32_t)box_cols, (cuuint32_t)box_rows};
    cuuint32_t es[2] = {1, 1};
    enc(&m, CU_TENSOR_MAP_DATA_TYPE_BFLOAT16, 2, const_cast<void*>(ptr), gd, gs, bd, es, CU_TENSOR_MAP_INTERLEAVE_NONE,
        swz, CU_TENSOR_MAP_L2_PROMOTION_L2_128B, CU_TENSOR_MAP_FLOAT_OOB_FILL_NONE);
    return m;
}

}

extern "C" void kernel_launch(void* const* d_in, const int* in_sizes, int n_in, void* d_out, int out_size) {
    (void)in_sizes; (void)n_in; (void)out_size;
    const __nv_bfloat16* x = (const __nv_bfloat16*)d_in[0];
    const __nv_bfloat16* wqkv = (const __nv_bfloat16*)d_in[1];
    const __nv_bfloat16* wo = (const __nv_bfloat16*)d_in[2];
    const __nv_bfloat16* w1 = (const __nv_bfloat16*)d_in[4];
    const __nv_bfloat16* b1 = (const __nv_bfloat16*)d_in[5];
    const __nv_bfloat16* w2 = (const __nv_bfloat16*)d_in[6];
    const __nv_bfloat16* b2 = (const __nv_bfloat16*)d_in[7];
    __nv_bfloat16* out = (__nv_bfloat16*)d_out;

    static EncodeTiledFn enc = nullptr;
    static void *p_h, *p_o;
    if (!enc) {
        cudaDriverEntryPointQueryResult qr;
        cudaGetDriverEntryPoint("cuTensorMapEncodeTiled", (void**)&enc, cudaEnableDefault, &qr);
        cudaGetSymbolAddress(&p_h, g_h);
        cudaGetSymbolAddress(&p_o, g_o);
        cudaFuncSetAttribute(k_fused, cudaFuncAttributeMaxDynamicSharedMemorySize, SM_TOTAL);
    }
    Maps tm;
    tm.x = make_map(enc, x, SEQ, DM, 128, 64, CU_TENSOR_MAP_SWIZZLE_128B);
    tm.wqkv = make_map(enc, wqkv, DM, 3 * DM, 32, 64, CU_TENSOR_MAP_SWIZZLE_128B);
    tm.w1 = make_map(enc, w1, DM, FF, 32, 64, CU_TENSOR_MAP_SWIZZLE_128B);
    tm.h = make_map(enc, p_h, SEQ, FF, 64, 64, CU_TENSOR_MAP_SWIZZLE_128B);
    tm.o = make_map(enc, p_o, SEQ, DM, 64, 64, CU_TENSOR_MAP_SWIZZLE_128B);
    tm.wo = make_map(enc, wo, DM, DM, 64, 32, CU_TENSOR_MAP_SWIZZLE_64B);
    tm.w2 = make_map(enc, w2, FF, DM, 64, 32, CU_TENSOR_MAP_SWIZZLE_64B);
    k_fused<<<128, 512, SM_TOTAL, cudaStreamPerThread>>>(tm, x, (const uint8_t*)wqkv, (const uint8_t*)w1, (const uint8_t*)w2,
                                                         (const uint8_t*)wo, b1, b2, out);
}
```

```cpp
#include <cuda_runtime.h>
#include <cuda_bf16.h>
#include <cuda.h>
#include <stdint.h>

namespace {

constexpr int SEQ = 2048, DM = 640, FF = 1536;
constexpr float LN_EPS = 1e-5f;

constexpr int IMG_BYTES = 256 * 384;
constexpr uint32_t EMU_MASK = 0xD5D5u;
constexpr float SAFE_BOUND = 80.0f;
#define XV_IT 1
#define PACE_NS 200
constexpr float QSCALE = 0.22360679774997896f * 1.4426950408889634f;

__device__ float4 g_stat[SEQ];
__device__ float2 g_csp[16 * 1728];
__device__ __align__(1024) uint8_t g_img[96 * IMG_BYTES + 1024];
__device__ float g_nrm[64 * SEQ];
__device__ __align__(1024) __nv_bfloat16 g_h[SEQ * FF];
__device__ __align__(1024) __nv_bfloat16 g_o[SEQ * DM];
constexpr int CNT_ST = 0, CNT_QKV = 16, CNT_H = 24, CNT_O = 40, CNT_CS = 44, CNT_CS2 = 52;
__device__ uint32_t g_cnt[60 * 32];
__device__ uint32_t g_epoch;

#define TL(kern, slot) do { } while (0)
#define IT(row, i) do { } while (0)

__device__ __forceinline__ uint32_t smem_u32(const void* p) { return (uint32_t)__cvta_generic_to_shared(p); }
__device__ __forceinline__ void mbar_init(uint32_t bar, int cnt) {
    asm volatile("mbarrier.init.shared::cta.b64 [%0], %1;" ::"r"(bar), "r"(cnt));
}
__device__ __forceinline__ void mbar_expect_tx(uint32_t bar, uint32_t bytes) {
    asm volatile("mbarrier.arrive.expect_tx.shared::cta.b64 _, [%0], %1;" ::"r"(bar), "r"(bytes) : "memory");
}
__device__ __forceinline__ void mbar_wait(uint32_t bar, uint32_t parity) {
    asm volatile("{\n.reg .pred p;\n.reg .u32 n;\nmov.u32 n, 0;\n"
                 "WAIT_LOOP:\nmbarrier.try_wait.parity.shared::cta.b64 p, [%0], %1;\n@p bra WAIT_DONE;\n"
                 "add.u32 n, n, 1;\nsetp.lt.u32 p, n, 4194304;\n@p bra WAIT_LOOP;\nWAIT_DONE:\n}"
                 ::"r"(bar), "r"(parity) : "memory");
}
__device__ __forceinline__ void mbar_arrive(uint32_t bar) {
    asm volatile("mbarrier.arrive.shared::cta.b64 _, [%0];" ::"r"(bar) : "memory");
}
__device__ __forceinline__ void mbar_arrive_cluster(uint32_t bar, uint32_t cta) {
    asm volatile("{\n.reg .b32 ra;\nmapa.shared::cluster.u32 ra, %0, %1;\n"
                 "mbarrier.arrive.shared::cluster.b64 _, [ra];\n}" ::"r"(bar), "r"(cta) : "memory");
}
__device__ __forceinline__ void fence_barrier_init() { asm volatile("fence.mbarrier_init.release.cluster;" ::: "memory"); }
__device__ __forceinline__ void fence_proxy_async() { asm volatile("fence.proxy.async.shared::cta;" ::: "memory"); }
__device__ __forceinline__ void cluster_sync() {
    asm volatile("barrier.cluster.arrive.release.aligned;\nbarrier.cluster.wait.acquire.aligned;" ::: "memory");
}
__device__ __forceinline__ bool elect_one() {
    uint32_t pred;
    asm volatile("{\n.reg .pred p;\nelect.sync _|p, 0xFFFFFFFF;\nselp.b32 %0, 1, 0, p;\n}" : "=r"(pred));
    return pred != 0;
}
__device__ __forceinline__ void pdl_launch() { asm volatile("griddepcontrol.launch_dependents;" ::: "memory"); }
__device__ __forceinline__ void pdl_wait() { asm volatile("griddepcontrol.wait;" ::: "memory"); }
__device__ __forceinline__ void prefetch_map(const CUtensorMap* m) {
    asm volatile("prefetch.tensormap [%0];" ::"l"(m) : "memory");
}
__device__ __forceinline__ void tma_load(uint32_t dst, const CUtensorMap* m, int c0, int c1, uint32_t bar) {
    asm volatile("cp.async.bulk.tensor.2d.shared::cluster.global.mbarrier::complete_tx::bytes [%0], [%1, {%3, %4}], [%2];"
                 ::"r"(dst), "l"(m), "r"(bar), "r"(c0), "r"(c1) : "memory");
}
__device__ __forceinline__ void tma_load_mc(uint32_t dst, const CUtensorMap* m, int c0, int c1, uint32_t bar, uint16_t mask) {
    asm volatile("cp.async.bulk.tensor.2d.shared::cluster.global.mbarrier::complete_tx::bytes.multicast::cluster"
                 " [%0], [%1, {%3, %4}], [%2], %5;"
                 ::"r"(dst), "l"(m), "r"(bar), "r"(c0), "r"(c1), "h"(mask) : "memory");
}
__device__ __forceinline__ void tma_store(const CUtensorMap* m, uint32_t src, int c0, int c1) {
    asm volatile("cp.async.bulk.tensor.2d.global.shared::cta.bulk_group [%0, {%2, %3}], [%1];"
                 ::"l"(m), "r"(src), "r"(c0), "r"(c1) : "memory");
}
__device__ __forceinline__ void bulk_commit() { asm volatile("cp.async.bulk.commit_group;" ::: "memory"); }
__device__ __forceinline__ void bulk_wait_all() { asm volatile("cp.async.bulk.wait_group 0;" ::: "memory"); }
__device__ __forceinline__ void bulk_load(uint32_t dst, const void* src, uint32_t bytes, uint32_t bar) {
    asm volatile("cp.async.bulk.shared::cluster.global.mbarrier::complete_tx::bytes [%0], [%1], %2, [%3];"
                 ::"r"(dst), "l"(src), "r"(bytes), "r"(bar) : "memory");
}
__device__ __forceinline__ void prefetch_l2(const void* p, uint32_t bytes) {
    asm volatile("cp.async.bulk.prefetch.L2.global [%0], %1;" ::"l"(p), "r"(bytes) : "memory");
}
__device__ __forceinline__ void tma_prefetch_l2(const CUtensorMap* m, int c0, int c1) {
    asm volatile("cp.async.bulk.prefetch.tensor.2d.L2.global.tile [%0, {%1, %2}];" ::"l"(m), "r"(c0), "r"(c1) : "memory");
}
__device__ __forceinline__ void wg_fence() { asm volatile("wgmma.fence.sync.aligned;" ::: "memory"); }
__device__ __forceinline__ void wg_commit() { asm volatile("wgmma.commit_group.sync.aligned;" ::: "memory"); }
template <int N> __device__ __forceinline__ void wg_wait() {
    asm volatile("wgmma.wait_group.sync.aligned %0;" ::"n"(N) : "memory");
}
template <int N> __device__ __forceinline__ void reg_alloc() { asm volatile("setmaxnreg.inc.sync.aligned.u32 %0;" ::"n"(N)); }
template <int N> __device__ __forceinline__ void reg_dealloc() { asm volatile("setmaxnreg.dec.sync.aligned.u32 %0;" ::"n"(N)); }
template <int N> __device__ __forceinline__ void fence_regs(float (&d)[N]) {
#pragma unroll
    for (int i = 0; i < N; i++) asm volatile("" : "+f"(d[i])::"memory");
}
__device__ __forceinline__ uint64_t make_desc(uint32_t addr, uint32_t lbo, uint32_t sbo, uint32_t swz) {
    return (uint64_t)((addr & 0x3FFFF) >> 4) | ((uint64_t)(lbo >> 4) << 16) | ((uint64_t)(sbo >> 4) << 32) |
           ((uint64_t)swz << 62);
}
__device__ __forceinline__ uint32_t pack_bf16(float lo, float hi) {
    uint32_t r;
    asm("cvt.rn.bf16x2.f32 %0, %1, %2;" : "=r"(r) : "f"(hi), "f"(lo));
    return r;
}
__device__ __forceinline__ float ex2(float x) {
    float r;
    asm("ex2.approx.ftz.f32 %0, %1;" : "=f"(r) : "f"(x));
    return r;
}
__device__ __forceinline__ float bf_lo(uint32_t v) { return __uint_as_float(v << 16); }
__device__ __forceinline__ float bf_hi(uint32_t v) { return __uint_as_float(v & 0xFFFF0000u); }
__device__ __forceinline__ void stmatrix_x4(uint32_t addr, uint32_t r0, uint32_t r1, uint32_t r2, uint32_t r3) {
    asm volatile("stmatrix.sync.aligned.m8n8.x4.shared.b16 [%0], {%1, %2, %3, %4};"
                 ::"r"(addr), "r"(r0), "r"(r1), "r"(r2), "r"(r3) : "memory");
}

__device__ __forceinline__ void wgmma_n200_ss_tb(float (&d)[100], uint64_t descA, uint64_t descB, int scaleD) {
    asm volatile("{\n.reg .pred p;\nsetp.ne.b32 p, %102, 0;\n"
        "wgmma.mma_async.sync.aligned.m64n200k16.f32.bf16.bf16 {"
        "%0, %1, %2, %3, %4, %5, %6, %7, %8, %9, %10, %11, %12, %13, %14, %15, "
        "%16, %17, %18, %19, %20, %21, %22, %23, %24, %25, %26, %27, %28, %29, %30, %31, "
        "%32, %33, %34, %35, %36, %37, %38, %39, %40, %41, %42, %43, %44, %45, %46, %47, "
        "%48, %49, %50, %51, %52, %53, %54, %55, %56, %57, %58, %59, %60, %61, %62, %63, "
        "%64, %65, %66, %67, %68, %69, %70, %71, %72, %73, %74, %75, %76, %77, %78, %79, "
        "%80, %81, %82, %83, %84, %85, %86, %87, %88, %89, %90, %91, %92, %93, %94, %95, "
        "%96, %97, %98, %99}, "
        "%100, %101, p, 1, 1, 0, 1;\n}\n"
        : "+f"(d[0]), "+f"(d[1]), "+f"(d[2]), "+f"(d[3]), "+f"(d[4]), "+f"(d[5]), "+f"(d[6]), "+f"(d[7]),
          "+f"(d[8]), "+f"(d[9]), "+f"(d[10]), "+f"(d[11]), "+f"(d[12]), "+f"(d[13]), "+f"(d[14]), "+f"(d[15]),
          "+f"(d[16]), "+f"(d[17]), "+f"(d[18]), "+f"(d[19]), "+f"(d[20]), "+f"(d[21]), "+f"(d[22]), "+f"(d[23]),
          "+f"(d[24]), "+f"(d[25]), "+f"(d[26]), "+f"(d[27]), "+f"(d[28]), "+f"(d[29]), "+f"(d[30]), "+f"(d[31]),
          "+f"(d[32]), "+f"(d[33]), "+f"(d[34]), "+f"(d[35]), "+f"(d[36]), "+f"(d[37]), "+f"(d[38]), "+f"(d[39]),
          "+f"(d[40]), "+f"(d[41]), "+f"(d[42]), "+f"(d[43]), "+f"(d[44]), "+f"(d[45]), "+f"(d[46]), "+f"(d[47]),
          "+f"(d[48]), "+f"(d[49]), "+f"(d[50]), "+f"(d[51]), "+f"(d[52]), "+f"(d[53]), "+f"(d[54]), "+f"(d[55]),
          "+f"(d[56]), "+f"(d[57]), "+f"(d[58]), "+f"(d[59]), "+f"(d[60]), "+f"(d[61]), "+f"(d[62]), "+f"(d[63]),
          "+f"(d[64]), "+f"(d[65]), "+f"(d[66]), "+f"(d[67]), "+f"(d[68]), "+f"(d[69]), "+f"(d[70]), "+f"(d[71]),
          "+f"(d[72]), "+f"(d[73]), "+f"(d[74]), "+f"(d[75]), "+f"(d[76]), "+f"(d[77]), "+f"(d[78]), "+f"(d[79]),
          "+f"(d[80]), "+f"(d[81]), "+f"(d[82]), "+f"(d[83]), "+f"(d[84]), "+f"(d[85]), "+f"(d[86]), "+f"(d[87]),
          "+f"(d[88]), "+f"(d[89]), "+f"(d[90]), "+f"(d[91]), "+f"(d[92]), "+f"(d[93]), "+f"(d[94]), "+f"(d[95]),
          "+f"(d[96]), "+f"(d[97]), "+f"(d[98]), "+f"(d[99])
        : "l"(descA), "l"(descB), "r"(scaleD));
}

__device__ __forceinline__ void wgmma_n40_ss_tb(float (&d)[20], uint64_t descA, uint64_t descB, int scaleD) {
    asm volatile("{\n.reg .pred p;\nsetp.ne.b32 p, %22, 0;\n"
        "wgmma.mma_async.sync.aligned.m64n40k16.f32.bf16.bf16 {"
        "%0, %1, %2, %3, %4, %5, %6, %7, %8, %9, %10, %11, %12, %13, %14, %15, "
        "%16, %17, %18, %19}, "
        "%20, %21, p, 1, 1, 0, 1;\n}\n"
        : "+f"(d[0]), "+f"(d[1]), "+f"(d[2]), "+f"(d[3]), "+f"(d[4]), "+f"(d[5]), "+f"(d[6]), "+f"(d[7]),
          "+f"(d[8]), "+f"(d[9]), "+f"(d[10]), "+f"(d[11]), "+f"(d[12]), "+f"(d[13]), "+f"(d[14]), "+f"(d[15]),
          "+f"(d[16]), "+f"(d[17]), "+f"(d[18]), "+f"(d[19])
        : "l"(descA), "l"(descB), "r"(scaleD));
}

__device__ __forceinline__ void wgmma_n192_ss_tb(float (&d)[96], uint64_t descA, uint64_t descB, int scaleD) {
    asm volatile("{\n.reg .pred p;\nsetp.ne.b32 p, %98, 0;\n"
        "wgmma.mma_async.sync.aligned.m64n192k16.f32.bf16.bf16 {"
        "%0, %1, %2, %3, %4, %5, %6, %7, %8, %9, %10, %11, %12, %13, %14, %15, "
        "%16, %17, %18, %19, %20, %21, %22, %23, %24, %25, %26, %27, %28, %29, %30, %31, "
        "%32, %33, %34, %35, %36, %37, %38, %39, %40, %41, %42, %43, %44, %45, %46, %47, "
        "%48, %49, %50, %51, %52, %53, %54, %55, %56, %57, %58, %59, %60, %61, %62, %63, "
        "%64, %65, %66, %67, %68, %69, %70, %71, %72, %73, %74, %75, %76, %77, %78, %79, "
        "%80, %81, %82, %83, %84, %85, %86, %87, %88, %89, %90, %91, %92, %93, %94, %95}, "
        "%96, %97, p, 1, 1, 0, 1;\n}\n"
        : "+f"(d[0]), "+f"(d[1]), "+f"(d[2]), "+f"(d[3]), "+f"(d[4]), "+f"(d[5]), "+f"(d[6]), "+f"(d[7]),
          "+f"(d[8]), "+f"(d[9]), "+f"(d[10]), "+f"(d[11]), "+f"(d[12]), "+f"(d[13]), "+f"(d[14]), "+f"(d[15]),
          "+f"(d[16]), "+f"(d[17]), "+f"(d[18]), "+f"(d[19]), "+f"(d[20]), "+f"(d[21]), "+f"(d[22]), "+f"(d[23]),
          "+f"(d[24]), "+f"(d[25]), "+f"(d[26]), "+f"(d[27]), "+f"(d[28]), "+f"(d[29]), "+f"(d[30]), "+f"(d[31]),
          "+f"(d[32]), "+f"(d[33]), "+f"(d[34]), "+f"(d[35]), "+f"(d[36]), "+f"(d[37]), "+f"(d[38]), "+f"(d[39]),
          "+f"(d[40]), "+f"(d[41]), "+f"(d[42]), "+f"(d[43]), "+f"(d[44]), "+f"(d[45]), "+f"(d[46]), "+f"(d[47]),
          "+f"(d[48]), "+f"(d[49]), "+f"(d[50]), "+f"(d[51]), "+f"(d[52]), "+f"(d[53]), "+f"(d[54]), "+f"(d[55]),
          "+f"(d[56]), "+f"(d[57]), "+f"(d[58]), "+f"(d[59]), "+f"(d[60]), "+f"(d[61]), "+f"(d[62]), "+f"(d[63]),
          "+f"(d[64]), "+f"(d[65]), "+f"(d[66]), "+f"(d[67]), "+f"(d[68]), "+f"(d[69]), "+f"(d[70]), "+f"(d[71]),
          "+f"(d[72]), "+f"(d[73]), "+f"(d[74]), "+f"(d[75]), "+f"(d[76]), "+f"(d[77]), "+f"(d[78]), "+f"(d[79]),
          "+f"(d[80]), "+f"(d[81]), "+f"(d[82]), "+f"(d[83]), "+f"(d[84]), "+f"(d[85]), "+f"(d[86]), "+f"(d[87]),
          "+f"(d[88]), "+f"(d[89]), "+f"(d[90]), "+f"(d[91]), "+f"(d[92]), "+f"(d[93]), "+f"(d[94]), "+f"(d[95])
        : "l"(descA), "l"(descB), "r"(scaleD));
}

__device__ __forceinline__ void wgmma_n192_ss_tb_z(float (&d)[96], uint64_t descA, uint64_t descB) {
    asm volatile("{\n.reg .pred p;\nsetp.ne.b32 p, 0, 0;\n"
        "wgmma.mma_async.sync.aligned.m64n192k16.f32.bf16.bf16 {"
        "%0, %1, %2, %3, %4, %5, %6, %7, %8, %9, %10, %11, %12, %13, %14, %15, "
        "%16, %17, %18, %19, %20, %21, %22, %23, %24, %25, %26, %27, %28, %29, %30, %31, "
        "%32, %33, %34, %35, %36, %37, %38, %39, %40, %41, %42, %43, %44, %45, %46, %47, "
        "%48, %49, %50, %51, %52, %53, %54, %55, %56, %57, %58, %59, %60, %61, %62, %63, "
        "%64, %65, %66, %67, %68, %69, %70, %71, %72, %73, %74, %75, %76, %77, %78, %79, "
        "%80, %81, %82, %83, %84, %85, %86, %87, %88, %89, %90, %91, %92, %93, %94, %95}, "
        "%96, %97, p, 1, 1, 0, 1;\n}\n"
        : "=f"(d[0]), "=f"(d[1]), "=f"(d[2]), "=f"(d[3]), "=f"(d[4]), "=f"(d[5]), "=f"(d[6]), "=f"(d[7]),
          "=f"(d[8]), "=f"(d[9]), "=f"(d[10]), "=f"(d[11]), "=f"(d[12]), "=f"(d[13]), "=f"(d[14]), "=f"(d[15]),
          "=f"(d[16]), "=f"(d[17]), "=f"(d[18]), "=f"(d[19]), "=f"(d[20]), "=f"(d[21]), "=f"(d[22]), "=f"(d[23]),
          "=f"(d[24]), "=f"(d[25]), "=f"(d[26]), "=f"(d[27]), "=f"(d[28]), "=f"(d[29]), "=f"(d[30]), "=f"(d[31]),
          "=f"(d[32]), "=f"(d[33]), "=f"(d[34]), "=f"(d[35]), "=f"(d[36]), "=f"(d[37]), "=f"(d[38]), "=f"(d[39]),
          "=f"(d[40]), "=f"(d[41]), "=f"(d[42]), "=f"(d[43]), "=f"(d[44]), "=f"(d[45]), "=f"(d[46]), "=f"(d[47]),
          "=f"(d[48]), "=f"(d[49]), "=f"(d[50]), "=f"(d[51]), "=f"(d[52]), "=f"(d[53]), "=f"(d[54]), "=f"(d[55]),
          "=f"(d[56]), "=f"(d[57]), "=f"(d[58]), "=f"(d[59]), "=f"(d[60]), "=f"(d[61]), "=f"(d[62]), "=f"(d[63]),
          "=f"(d[64]), "=f"(d[65]), "=f"(d[66]), "=f"(d[67]), "=f"(d[68]), "=f"(d[69]), "=f"(d[70]), "=f"(d[71]),
          "=f"(d[72]), "=f"(d[73]), "=f"(d[74]), "=f"(d[75]), "=f"(d[76]), "=f"(d[77]), "=f"(d[78]), "=f"(d[79]),
          "=f"(d[80]), "=f"(d[81]), "=f"(d[82]), "=f"(d[83]), "=f"(d[84]), "=f"(d[85]), "=f"(d[86]), "=f"(d[87]),
          "=f"(d[88]), "=f"(d[89]), "=f"(d[90]), "=f"(d[91]), "=f"(d[92]), "=f"(d[93]), "=f"(d[94]), "=f"(d[95])
        : "l"(descA), "l"(descB));
}

__device__ __forceinline__ void wgmma_n160_ss_tb(float (&d)[80], uint64_t descA, uint64_t descB, int scaleD) {
    asm volatile("{\n.reg .pred p;\nsetp.ne.b32 p, %82, 0;\n"
        "wgmma.mma_async.sync.aligned.m64n160k16.f32.bf16.bf16 {"
        "%0, %1, %2, %3, %4, %5, %6, %7, %8, %9, %10, %11, %12, %13, %14, %15, "
        "%16, %17, %18, %19, %20, %21, %22, %23, %24, %25, %26, %27, %28, %29, %30, %31, "
        "%32, %33, %34, %35, %36, %37, %38, %39, %40, %41, %42, %43, %44, %45, %46, %47, "
        "%48, %49, %50, %51, %52, %53, %54, %55, %56, %57, %58, %59, %60, %61, %62, %63, "
        "%64, %65, %66, %67, %68, %69, %70, %71, %72, %73, %74, %75, %76, %77, %78, %79}, "
        "%80, %81, p, 1, 1, 0, 1;\n}\n"
        : "+f"(d[0]), "+f"(d[1]), "+f"(d[2]), "+f"(d[3]), "+f"(d[4]), "+f"(d[5]), "+f"(d[6]), "+f"(d[7]),
          "+f"(d[8]), "+f"(d[9]), "+f"(d[10]), "+f"(d[11]), "+f"(d[12]), "+f"(d[13]), "+f"(d[14]), "+f"(d[15]),
          "+f"(d[16]), "+f"(d[17]), "+f"(d[18]), "+f"(d[19]), "+f"(d[20]), "+f"(d[21]), "+f"(d[22]), "+f"(d[23]),
          "+f"(d[24]), "+f"(d[25]), "+f"(d[26]), "+f"(d[27]), "+f"(d[28]), "+f"(d[29]), "+f"(d[30]), "+f"(d[31]),
          "+f"(d[32]), "+f"(d[33]), "+f"(d[34]), "+f"(d[35]), "+f"(d[36]), "+f"(d[37]), "+f"(d[38]), "+f"(d[39]),
          "+f"(d[40]), "+f"(d[41]), "+f"(d[42]), "+f"(d[43]), "+f"(d[44]), "+f"(d[45]), "+f"(d[46]), "+f"(d[47]),
          "+f"(d[48]), "+f"(d[49]), "+f"(d[50]), "+f"(d[51]), "+f"(d[52]), "+f"(d[53]), "+f"(d[54]), "+f"(d[55]),
          "+f"(d[56]), "+f"(d[57]), "+f"(d[58]), "+f"(d[59]), "+f"(d[60]), "+f"(d[61]), "+f"(d[62]), "+f"(d[63]),
          "+f"(d[64]), "+f"(d[65]), "+f"(d[66]), "+f"(d[67]), "+f"(d[68]), "+f"(d[69]), "+f"(d[70]), "+f"(d[71]),
          "+f"(d[72]), "+f"(d[73]), "+f"(d[74]), "+f"(d[75]), "+f"(d[76]), "+f"(d[77]), "+f"(d[78]), "+f"(d[79])
        : "l"(descA), "l"(descB), "r"(scaleD));
}

__device__ __forceinline__ void wgmma_n64_ss(float (&d)[32], uint64_t descA, uint64_t descB, int scaleD) {
    asm volatile("{\n.reg .pred p;\nsetp.ne.b32 p, %34, 0;\n"
        "wgmma.mma_async.sync.aligned.m64n64k16.f32.bf16.bf16 {"
        "%0, %1, %2, %3, %4, %5, %6, %7, %8, %9, %10, %11, %12, %13, %14, %15, "
        "%16, %17, %18, %19, %20, %21, %22, %23, %24, %25, %26, %27, %28, %29, %30, %31}, "
        "%32, %33, p, 1, 1, 0, 0;\n}\n"
        : "+f"(d[0]), "+f"(d[1]), "+f"(d[2]), "+f"(d[3]), "+f"(d[4]), "+f"(d[5]), "+f"(d[6]), "+f"(d[7]),
          "+f"(d[8]), "+f"(d[9]), "+f"(d[10]), "+f"(d[11]), "+f"(d[12]), "+f"(d[13]), "+f"(d[14]), "+f"(d[15]),
          "+f"(d[16]), "+f"(d[17]), "+f"(d[18]), "+f"(d[19]), "+f"(d[20]), "+f"(d[21]), "+f"(d[22]), "+f"(d[23]),
          "+f"(d[24]), "+f"(d[25]), "+f"(d[26]), "+f"(d[27]), "+f"(d[28]), "+f"(d[29]), "+f"(d[30]), "+f"(d[31])
        : "l"(descA), "l"(descB), "r"(scaleD));
}

__device__ __forceinline__ void wgmma_n64_ss_z(float (&d)[32], uint64_t descA, uint64_t descB) {
    asm volatile("{\n.reg .pred p;\nsetp.ne.b32 p, 0, 0;\n"
        "wgmma.mma_async.sync.aligned.m64n64k16.f32.bf16.bf16 {"
        "%0, %1, %2, %3, %4, %5, %6, %7, %8, %9, %10, %11, %12, %13, %14, %15, "
        "%16, %17, %18, %19, %20, %21, %22, %23, %24, %25, %26, %27, %28, %29, %30, %31}, "
        "%32, %33, p, 1, 1, 0, 0;\n}\n"
        : "=f"(d[0]), "=f"(d[1]), "=f"(d[2]), "=f"(d[3]), "=f"(d[4]), "=f"(d[5]), "=f"(d[6]), "=f"(d[7]),
          "=f"(d[8]), "=f"(d[9]), "=f"(d[10]), "=f"(d[11]), "=f"(d[12]), "=f"(d[13]), "=f"(d[14]), "=f"(d[15]),
          "=f"(d[16]), "=f"(d[17]), "=f"(d[18]), "=f"(d[19]), "=f"(d[20]), "=f"(d[21]), "=f"(d[22]), "=f"(d[23]),
          "=f"(d[24]), "=f"(d[25]), "=f"(d[26]), "=f"(d[27]), "=f"(d[28]), "=f"(d[29]), "=f"(d[30]), "=f"(d[31])
        : "l"(descA), "l"(descB));
}

__device__ __forceinline__ void wgmma_n24_rs_tb(float (&d)[12], uint32_t a0, uint32_t a1, uint32_t a2, uint32_t a3, uint64_t descB, int scaleD) {
    asm volatile("{\n.reg .pred p;\nsetp.ne.b32 p, %17, 0;\n"
        "wgmma.mma_async.sync.aligned.m64n24k16.f32.bf16.bf16 {"
        "%0, %1, %2, %3, %4, %5, %6, %7, %8, %9, %10, %11}, "
        "{%12, %13, %14, %15}, %16, p, 1, 1, 1;\n}\n"
        : "+f"(d[0]), "+f"(d[1]), "+f"(d[2]), "+f"(d[3]), "+f"(d[4]), "+f"(d[5]), "+f"(d[6]), "+f"(d[7]),
          "+f"(d[8]), "+f"(d[9]), "+f"(d[10]), "+f"(d[11])
        : "r"(a0), "r"(a1), "r"(a2), "r"(a3), "l"(descB), "r"(scaleD));
}

__device__ __forceinline__ void cnt_signal(int idx) {
    asm volatile("fence.acq_rel.gpu;\nred.relaxed.gpu.global.add.u32 [%0], 1;"
                 ::"l"(g_cnt + idx * 32) : "memory");
}
__device__ __forceinline__ void cnt_wait(int idx, uint32_t target) {
    const uint32_t* p = g_cnt + idx * 32;
#pragma unroll 1
    for (uint32_t i = 0; i < (1u << 22); i++) {
        uint32_t v;
        asm volatile("ld.acquire.gpu.global.u32 %0, [%1];" : "=r"(v) : "l"(p) : "memory");
        if ((int32_t)(v - target) >= 0) break;
    }
    asm volatile("fence.proxy.async.global;" ::: "memory");
}
__device__ __forceinline__ void cluster_arrive() { asm volatile("barrier.cluster.arrive.release.aligned;" ::: "memory"); }
__device__ __forceinline__ void cluster_arrive_relaxed() { asm volatile("barrier.cluster.arrive.relaxed.aligned;" ::: "memory"); }
__device__ __forceinline__ void cluster_wait() { asm volatile("barrier.cluster.wait.acquire.aligned;" ::: "memory"); }
__device__ __forceinline__ void bulk_wait_read() { asm volatile("cp.async.bulk.wait_group.read 0;" ::: "memory"); }

__device__ __forceinline__ float gelu_tanh(float x) {
    const float u = x * (0.7978845608028654f + 0.035677408136300125f * x * x);
    float t;
    asm("tanh.approx.f32 %0, %1;" : "=f"(t) : "f"(u));
    const float h = 0.5f * x;
    return fmaf(h, t, h);
}
__device__ __forceinline__ void release_stage(uint32_t bar, uint32_t peer, int lane) {
    if (lane == 0) { mbar_arrive(bar); mbar_arrive_cluster(bar, peer); }
}

constexpr int SM_RING = 163840;
constexpr int SM_Q = 2 * IMG_BYTES, SM_ZERO = SM_Q + 24576;
constexpr int G2_STAGE = 8192 + 20480;
constexpr int SM_MISC = 229376;
constexpr int SM_BIAS = SM_MISC, SM_RED = SM_BIAS + 384, SM_BAR = SM_RED + 128;
constexpr int B_A = 0, B_F1 = 10, B_E1 = 14, B_F2 = 18, B_E2 = 23, B_KV = 28, B_Q = 45, B_F3 = 47, B_E3 = 55, B_ST = 63, B_STAT = 65, B_AUX = 66, B_AUX2 = 67, B_COUNT = 68;
constexpr int SM_EPOCH = SM_BAR + 544;
constexpr int SM_CS = SM_EPOCH + 16;
constexpr int SM_DBG = SM_CS + 1728;
constexpr int SM_TOTAL = SM_DBG + 128;
static_assert(SM_TOTAL <= 232448, "shared memory budget");

struct Maps { CUtensorMap x, wqkv, w1, h, o, wo, w2; };

__device__ __forceinline__ uint32_t bf2_fma(uint32_t a, uint32_t b, uint32_t c) {
    uint32_t r;
    asm("fma.rn.bf16x2 %0, %1, %2, %3;" : "=r"(r) : "r"(a), "r"(b), "r"(c));
    return r;
}
__device__ __forceinline__ uint32_t lop_and_or(uint32_t a, uint32_t m, uint32_t o) {
    uint32_t r;
    asm("lop3.b32 %0, %1, %2, %3, 0xEA;" : "=r"(r) : "r"(a), "r"(m), "r"(o));
    return r;
}
struct ExpConst { uint32_t mask, slope; };
__device__ __forceinline__ ExpConst make_exp_const() {
    ExpConst k;
    asm volatile("mov.b32 %0, 0x007F007F;" : "=r"(k.mask));
    asm volatile("mov.b32 %0, 0x3EF83EF8;" : "=r"(k.slope));
    return k;
}
__device__ __forceinline__ uint32_t exp2_pair_fma(float t0, float t1, const ExpConst& k) {
    const uint32_t L = __byte_perm(__float_as_uint(t0), __float_as_uint(t1), 0x6521);
    const uint32_t g = lop_and_or(L, k.mask, 0x3F803F80u);
    const uint32_t u = bf2_fma(g, k.slope, 0xBF37BF37u);
    const uint32_t e = bf2_fma(u, u, 0xBD71BD71u);
    return bf2_fma(L, e, L);
}
template <int SHIFT>
__device__ __forceinline__ void exp_tile(const float (&s)[32], uint32_t (&p)[16], const ExpConst& k) {
#pragma unroll
    for (int b = 0; b < 8; b++) {
        if ((EMU_MASK >> (b + SHIFT)) & 1) {
            p[2 * b] = exp2_pair_fma(s[4 * b], s[4 * b + 1], k);
            p[2 * b + 1] = exp2_pair_fma(s[4 * b + 2], s[4 * b + 3], k);
        } else {
            p[2 * b] = pack_bf16(ex2(s[4 * b]), ex2(s[4 * b + 1]));
            p[2 * b + 1] = pack_bf16(ex2(s[4 * b + 2]), ex2(s[4 * b + 3]));
        }
    }
}

__device__ __forceinline__ void qk_tile(float (&s)[32], uint64_t dQ, uint64_t dQ2, uint64_t dK) {
    wg_fence();
    wgmma_n64_ss_z(s, dQ, dK);
    wgmma_n64_ss(s, dQ2, dK + 16, 1);
    wg_commit();
}
__device__ __forceinline__ void pv_tile(float (&o)[12], const uint32_t (&p)[16], uint64_t dV) {
    wg_fence();
#pragma unroll
    for (int ks = 0; ks < 4; ks++)
        wgmma_n24_rs_tb(o, p[4 * ks], p[4 * ks + 1], p[4 * ks + 2], p[4 * ks + 3], dV + ks * 48, 1);
    wg_commit();
}
__device__ __forceinline__ void store_o(const float (&o)[12], int h, int rbase, int lane) {
    const int g = lane >> 2, c = lane & 3;
    const bool odd = h & 1;
    const int lsrc = (lane & ~3) | (odd ? 0 : 2);
    const float i0 = 1.f / __shfl_sync(~0u, o[8], lsrc), i1 = 1.f / __shfl_sync(~0u, o[10], lsrc);
    __nv_bfloat16* dst = g_o + (size_t)(rbase + g) * DM + h * 20;
    const int d0 = (odd ? 4 : 0) + 2 * c, d1 = d0 + 8, d2 = odd ? 2 * c - 4 : 16 + 2 * c;
    *(uint32_t*)(dst + d0) = pack_bf16(o[0] * i0, o[1] * i0);
    *(uint32_t*)(dst + d1) = pack_bf16(o[4] * i0, o[5] * i0);
    *(uint32_t*)(dst + 8 * DM + d0) = pack_bf16(o[2] * i1, o[3] * i1);
    *(uint32_t*)(dst + 8 * DM + d1) = pack_bf16(o[6] * i1, o[7] * i1);
    if (odd ? (c >= 2) : (c < 2)) {
        *(uint32_t*)(dst + d2) = pack_bf16(o[8] * i0, o[9] * i0);
        *(uint32_t*)(dst + 8 * DM + d2) = pack_bf16(o[10] * i1, o[11] * i1);
    }
}

__device__ __forceinline__ void attn_rows_maxshift(uint32_t sK, uint32_t barKV, uint64_t dQ, uint64_t dQ2, int h, int rbase) {
    const int lane = threadIdx.x & 31;
    const uint64_t dK0 = make_desc(sK, 128, 384, 0), dV0 = make_desc(sK + IMG_BYTES, 384, 128, 0);
    float o[12], s[32];
    uint32_t p[16];
#pragma unroll
    for (int i = 0; i < 12; i++) o[i] = 0.f;
    float m0 = -3.0e38f, m1 = -3.0e38f;
    mbar_wait(barKV + 128, 0);
#pragma unroll 1
    for (int t = 0; t < 32; t++) {
        mbar_wait(barKV + (t >> 1) * 8, 0);
        qk_tile(s, dQ, dQ2, dK0 + t * 192);
        wg_wait<0>();
        fence_regs(s);
        const uint32_t mask = EMU_MASK >> ((t & 1) * 8);
        float n0 = m0, n1 = m1;
#pragma unroll
        for (int b = 0; b < 8; b++) {
            const bool emu = (mask >> b) & 1;
            const float f = emu ? 0.5f : 1.f, off = emu ? -383.00390625f : 0.f;
#pragma unroll
            for (int i = 0; i < 4; i++) s[4 * b + i] = fmaf(s[4 * b + i], f, off);
            n0 = fmaxf(n0, fmaxf(s[4 * b], s[4 * b + 1]));
            n1 = fmaxf(n1, fmaxf(s[4 * b + 2], s[4 * b + 3]));
        }
        n0 = fmaxf(n0, __shfl_xor_sync(~0u, n0, 1)); n0 = fmaxf(n0, __shfl_xor_sync(~0u, n0, 2));
        n1 = fmaxf(n1, __shfl_xor_sync(~0u, n1, 1)); n1 = fmaxf(n1, __shfl_xor_sync(~0u, n1, 2));
        const float c0 = ex2(m0 - n0), c1 = ex2(m1 - n1);
        m0 = n0; m1 = n1;
#pragma unroll
        for (int b = 0; b < 3; b++) { o[4 * b] *= c0; o[4 * b + 1] *= c0; o[4 * b + 2] *= c1; o[4 * b + 3] *= c1; }
#pragma unroll
        for (int b = 0; b < 8; b++) {
            p[2 * b] = pack_bf16(ex2(s[4 * b] - m0), ex2(s[4 * b + 1] - m0));
            p[2 * b + 1] = pack_bf16(ex2(s[4 * b + 2] - m1), ex2(s[4 * b + 3] - m1));
        }
        pv_tile(o, p, dV0 + t * 192);
        wg_wait<0>();
        fence_regs(o);
    }
    store_o(o, h, rbase, lane);
}

__global__ void __launch_bounds__(512, 1) __cluster_dims__(2, 1, 1)
k_fused(const __grid_constant__ Maps tm, const __nv_bfloat16* __restrict__ x, const uint8_t* __restrict__ wqkv,
        const uint8_t* __restrict__ w1, const uint8_t* __restrict__ w2, const uint8_t* __restrict__ wo,
        const __nv_bfloat16* __restrict__ b1, const __nv_bfloat16* __restrict__ b2, __nv_bfloat16* __restrict__ out) {
    extern __shared__ __align__(1024) uint8_t smem[];
    const uint32_t sb = smem_u32(smem);
    const uint32_t bar = sb + SM_BAR;
    const int warp = __shfl_sync(~0u, threadIdx.x >> 5, 0), lane = threadIdx.x & 31;
    const int wgi = warp >> 2, w4 = warp & 3, g = lane >> 2, c = lane & 3;
    const uint32_t rank = blockIdx.x & 1, peer = rank ^ 1;
    const int cl = blockIdx.x >> 1;
    const int cg = cl >> 3, rb = (cl & 7) * 2 + rank;

    if (threadIdx.x == 0) TL(0, 0);
    if (warp == 15 && lane < 4) prefetch_map(lane == 0 ? &tm.x : lane == 1 ? &tm.wqkv : lane == 2 ? &tm.w1 : &tm.h);
    if (elect_one()) {
#pragma unroll
        for (int j = 0; j < 5; j++) {
            const int i = warp * 5 + j;
            const int cnt = (i >= B_E1 && i < B_F2) || (i >= B_E2 && i < B_KV) ? 16
                          : (i >= B_E3 && i <= B_ST) || i == B_STAT ? 8 : i == B_ST + 1 ? 2 : i == B_AUX ? 4 : i == B_AUX2 ? 3 : 1;
            if (i < B_COUNT) mbar_init(bar + i * 8, cnt);
        }
        fence_barrier_init();
    }
    __syncthreads();
    if (threadIdx.x == 0) TL(0, 1);
    cluster_arrive_relaxed();
    cluster_wait();
    if (threadIdx.x == 0) TL(0, 3);

    {
        const uint32_t sB = sb + SM_RING;
        if (threadIdx.x == 0) TL(1, 0);
        if (wgi < 2) {
            reg_dealloc<56>();
            if (threadIdx.x == 0) TL(4, 2);
            if (warp == 0) {
#pragma unroll 1
                for (int it = 0; it < 20; it++) {
                    const int s = it & 3;
                    const int kb = it < 2 ? it : (it & 1) ? (it + 1) >> 1 : 10;
                    if (it >= 4) mbar_wait(bar + (B_E1 + s) * 8, ((it >> 2) - 1) & 1);
                    else if (it > 0) __nanosleep(PACE_NS);
                    if (elect_one()) {
                        if (kb < 10) {
                            mbar_expect_tx(bar + (B_A + kb) * 8, 16384);
                            tma_load(sb + kb * 16384, &tm.x, kb * 64, rb * 128, bar + (B_A + kb) * 8);
                        }
                        const uint32_t dst = sB + s * 16384 + rank * 8192, fb = bar + (B_F1 + s) * 8;
                        const int c0 = cg * 240 + rank * 128;
                        mbar_expect_tx(fb, 16384);
                        tma_load_mc(dst, &tm.wqkv, c0, it * 32, fb, 3);
                        tma_load_mc(dst + 4096, &tm.wqkv, c0 + 64, it * 32, fb, 3);
                    }
                    __syncwarp();
                    if (lane == 0 && it < 8) TL(5, it) ;
                }
#pragma unroll 1
                for (int it = 0; it < 20; it++) {
                    const int s = it % 5;
                    if (it < 5) { if (it != 3) mbar_wait(bar + (B_E1 + (it == 4 ? 3 : it)) * 8, 0); }
                    else mbar_wait(bar + (B_E2 + s) * 8, ((it / 5) - 1) & 1);
                    if (elect_one()) {
                        const uint32_t dst = sB + s * 12288, fb = bar + (B_F2 + s) * 8;
                        mbar_expect_tx(fb, 12288);
                        if ((it & 1) == (int)rank) {
                            tma_load_mc(dst, &tm.w1, cg * 192, it * 32, fb, 3);
                            tma_load_mc(dst + 4096, &tm.w1, cg * 192 + 64, it * 32, fb, 3);
                        } else {
                            tma_load_mc(dst + 8192, &tm.w1, cg * 192 + 128, it * 32, fb, 3);
                        }
                    }
                    __syncwarp();
                }
            } else {
                const int ht = threadIdx.x - 32;
                if (ht == 192) *reinterpret_cast<volatile uint32_t*>(smem + SM_EPOCH) = *(volatile uint32_t*)&g_epoch;
                auto slab_sum = [&](const uint32_t* src, int pitch) {
                    float s0 = 0.f, s1 = 0.f;
                    uint32_t v[40];
#pragma unroll
                    for (int k = 0; k < 40; k++) v[k] = __ldg(src + k * pitch);
#pragma unroll
                    for (int k = 0; k < 40; k++) { s0 += bf_lo(v[k]); s1 += bf_hi(v[k]); }
                    return make_float2(s0, s1);
                };
                auto gather = [&](int idx) {
                    float s0 = 0.f, s1 = 0.f;
#pragma unroll
                    for (int r = 0; r < 16; r++) {
                        const float2 v = __ldcg(g_csp + r * 1728 + cg * 216 + idx);
                        s0 += v.x; s1 += v.y;
                    }
                    reinterpret_cast<float2*>(smem + SM_CS)[idx] = make_float2(s0, s1);
                };
                if (warp >= 5) {
#pragma unroll 1
                    for (int r0 = (warp - 5) * 6; r0 < min(16, (warp - 5) * 6 + 6); r0 += 3) {
                        uint2 xv[3][5];
#pragma unroll
                        for (int u = 0; u < 3; u++)
#pragma unroll
                            for (int i = 0; i < 5; i++)
                                xv[u][i] = __ldg(reinterpret_cast<const uint2*>(x + (size_t)(rb * 128 + cg * 16 + min(r0 + u, 15)) * DM) + lane + 32 * i);
#pragma unroll
                        for (int u = 0; u < 3; u++) {
                            float sm = 0.f;
#pragma unroll
                            for (int i = 0; i < 5; i++) sm += (bf_lo(xv[u][i].x) + bf_hi(xv[u][i].x)) + (bf_lo(xv[u][i].y) + bf_hi(xv[u][i].y));
#pragma unroll
                            for (int o = 16; o; o >>= 1) sm += __shfl_xor_sync(~0u, sm, o);
                            const float mu = sm * (1.f / DM);
                            float q = 0.f;
#pragma unroll
                            for (int i = 0; i < 5; i++) {
                                const float d0 = bf_lo(xv[u][i].x) - mu, d1 = bf_hi(xv[u][i].x) - mu;
                                const float d2 = bf_lo(xv[u][i].y) - mu, d3 = bf_hi(xv[u][i].y) - mu;
                                q = fmaf(d0, d0, fmaf(d1, d1, fmaf(d2, d2, fmaf(d3, d3, q))));
                            }
#pragma unroll
                            for (int o = 16; o; o >>= 1) q += __shfl_xor_sync(~0u, q, o);
                            const float var = q * (1.f / DM);
                            const float r1 = 1.f / sqrtf(var + LN_EPS);
                            const float r2 = 1.f / sqrtf(var * r1 * r1 + LN_EPS);
                            if (lane == 0 && r0 + u < 16) g_stat[rb * 128 + cg * 16 + r0 + u] = make_float4(mu, r1, r1 * r2, 0.f);
                        }
                    }
                }
                if (ht < 120)
                    g_csp[rb * 1728 + cg * 216 + ht] = slab_sum(reinterpret_cast<const uint32_t*>(wqkv) + rb * 40 * 960 + cg * 120 + ht, 960);
                if (threadIdx.x == 64) IT(3, 0);
                asm volatile("bar.sync 8, 224;" ::: "memory");
                const uint32_t epoch = *reinterpret_cast<volatile uint32_t*>(smem + SM_EPOCH);
                if (warp == 6) { if (elect_one()) cnt_signal(CNT_CS + cg); __syncwarp(); }
                if (warp == 7) { if (elect_one()) cnt_signal(CNT_ST + rb); __syncwarp(); }
                if (threadIdx.x == 64) IT(3, 2);
                if (warp <= 4) {
                    if (lane == 0) { cnt_wait(CNT_CS + cg, (epoch + 1) * 16); cnt_wait(CNT_ST + rb, (epoch + 1) * 8); }
                    __syncwarp();
                    if (threadIdx.x == 64) IT(3, 4);
                    if (ht < 120) gather(ht);
                    __syncwarp();
                    if (threadIdx.x == 64) IT(3, 5);
                    if (lane == 0) mbar_arrive(bar + B_AUX * 8);
                }
                if (ht >= 128) {
                    g_csp[rb * 1728 + cg * 216 + 120 + (ht - 128)] = slab_sum(reinterpret_cast<const uint32_t*>(w1) + rb * 40 * 768 + cg * 96 + (ht - 128), 768);
                    reinterpret_cast<uint32_t*>(smem + SM_BIAS)[ht - 128] = __ldg(reinterpret_cast<const uint32_t*>(b1 + cg * 192) + (ht - 128));
                    asm volatile("bar.sync 9, 96;" ::: "memory");
                    if (warp == 5) { if (elect_one()) cnt_signal(CNT_CS2 + cg); __syncwarp(); }
                    if (warp == 6 && elect_one()) {
                        prefetch_l2(w2 + blockIdx.x * 15360, 15360);
                        prefetch_l2(wo + blockIdx.x * 6400, 6400);
                    }
                    if (lane == 0) cnt_wait(CNT_CS2 + cg, (epoch + 1) * 16);
                    __syncwarp();
                    gather(120 + (ht - 128));
                    __syncwarp();
                    if (lane == 0) mbar_arrive(bar + B_AUX2 * 8);
                }
                if (warp == 4) {
                    mbar_wait(bar + B_ST * 8, 0);
                    if (elect_one()) cnt_signal(CNT_QKV + cg);
                    __syncwarp();
                }
            }
            asm volatile("bar.sync %0, 128;" ::"r"(wgi + 3) : "memory");
            reg_alloc<128>();
        } else {
            reg_alloc<200>();
            if (threadIdx.x == 256) TL(4, 0);
            const int wi = wgi - 2;
            const int row0 = rb * 128 + wi * 64 + w4 * 16 + g;
            const uint32_t sAw = sb + wi * 8192;
            const int rbk = row0 >> 3, hs0 = cg * 12;
            if (threadIdx.x == 256) TL(4, 1);
            float accA[100], accB[20];
            const uint64_t dA0 = make_desc(sAw, 16, 1024, 1), dB0 = make_desc(sB, 4096, 1024, 1);
#pragma unroll 2
            for (int it = 0; it < 20; it++) {
                const int s = it & 3;
                if (!(it & 1)) mbar_wait(bar + (B_A + (it >> 1)) * 8, 0);
                if (threadIdx.x == 256 && it == 0) TL(0, 2);
                if (threadIdx.x == 256 && it == 2) TL(4, 3);
                if (threadIdx.x == 256) IT(0, it);
                mbar_wait(bar + (B_F1 + s) * 8, (it >> 2) & 1);
                if (threadIdx.x == 256) IT(1, it);
                const uint64_t dA = dA0 + (it >> 1) * 1024 + (it & 1) * 4, dB = dB0 + s * 1024;
                wg_fence();
                wgmma_n40_ss_tb(accB, dA, dB + 769, it > 0);
                wgmma_n40_ss_tb(accB, dA + 2, dB + 769 + 128, 1);
                wgmma_n200_ss_tb(accA, dA, dB, it > 0);
                wgmma_n200_ss_tb(accA, dA + 2, dB + 128, 1);
                wg_commit();
                if (it > 0) { wg_wait<1>(); release_stage(bar + (B_E1 + ((it - 1) & 3)) * 8, peer, lane); }
            }
            if (threadIdx.x == 256) IT(2, 0);
            mbar_wait(bar + B_AUX * 8, 0);
            if (threadIdx.x == 256) IT(2, 1);
            const float4 st0 = __ldcg(g_stat + row0), st1 = __ldcg(g_stat + row0 + 8);
            wg_wait<0>();
            release_stage(bar + (B_E1 + 3) * 8, peer, lane);
            fence_regs(accA);
            fence_regs(accB);
            if (threadIdx.x == 256) TL(1, 1);
            const float2* cs = reinterpret_cast<const float2*>(smem + SM_CS) + c;
            uint8_t* img = g_img + (size_t)hs0 * IMG_BYTES + rbk * 384 + g * 16 + c * 4;
            const bool emu0 = (EMU_MASK >> (rbk & 15)) & 1, emu1 = (EMU_MASK >> ((rbk + 1) & 15)) & 1;
            const bool low = c < 2;
            uint32_t pk[60];
#pragma unroll
            for (int m = 0; m < 6; m++) {
                const int which = (hs0 + 2 * m) >> 5;
                const float m0 = st0.y * (which == 0 ? QSCALE : (which == 1 && emu0) ? 2.f : 1.f);
                const float m1 = st1.y * (which == 0 ? QSCALE : (which == 1 && emu1) ? 2.f : 1.f);
                const float d0 = -st0.x * m0, d1 = -st1.x * m1;
                const float* a = m < 5 ? &accA[20 * m] : accB;
#pragma unroll
                for (int b = 0; b < 5; b++) {
                    const float2 cv = cs[(5 * m + b) * 4];
                    pk[10 * m + 2 * b] = pack_bf16(fmaf(a[4 * b], m0, d0 * cv.x), fmaf(a[4 * b + 1], m0, d0 * cv.y));
                    pk[10 * m + 2 * b + 1] = pack_bf16(fmaf(a[4 * b + 2], m1, d1 * cv.x), fmaf(a[4 * b + 3], m1, d1 * cv.y));
                }
            }
            const float r20 = st0.z, r21 = st1.z, e20 = -st0.x * st0.z, e21 = -st1.x * st1.z;
            if (threadIdx.x == 256) IT(2, 2);
            float acc2[96];
#pragma unroll
            for (int it = 0; it < 20; it++) {
                const int s = it % 5;
                if (threadIdx.x == 256) IT(0, 20 + it);
                mbar_wait(bar + (B_F2 + s) * 8, (it / 5) & 1);
                if (threadIdx.x == 256) IT(1, 20 + it);
                wg_fence();
                const uint64_t dA = make_desc(sAw + (it >> 1) * 16384 + (it & 1) * 64, 16, 1024, 1);
                const uint64_t dB = make_desc(sB + s * 12288, 4096, 1024, 1);
                if (it == 0) wgmma_n192_ss_tb_z(acc2, dA, dB); else wgmma_n192_ss_tb(acc2, dA, dB, 1);
                wgmma_n192_ss_tb(acc2, dA + 2, dB + 128, 1);
                wg_commit();
                if (it > 0) {
                    wg_wait<1>();
                    if (it <= 15) release_stage(bar + (B_E2 + (it - 1) % 5) * 8, peer, lane);
                }
                if (it < 12) {
                    const int m = it / 2, part = it % 2;
                    const int hs = hs0 + 2 * m, which = hs >> 5;
                    const uint32_t* a = pk + 10 * m;
                    uint8_t* pe = img + (2 * m) * IMG_BYTES;
                    uint8_t* po = pe + IMG_BYTES;
                    if (part == 0) {
                        const uint32_t padv = which == 0 ? 0x3F803F80u : which == 1 ? 0xBFFF4440u : 0x00003F80u;
                        const uint32_t p0 = ((c & 1) || (which == 1 && !emu0)) ? 0u : padv;
                        const uint32_t p1 = ((c & 1) || (which == 1 && !emu1)) ? 0u : padv;
                        *(uint32_t*)(pe) = a[0];
                        *(uint32_t*)(pe + 128) = a[2];
                        *(uint32_t*)(pe + 256) = low ? a[4] : p0;
                        *(uint32_t*)(pe + 384) = a[1];
                        *(uint32_t*)(pe + 512) = a[3];
                        *(uint32_t*)(pe + 640) = low ? a[5] : p1;
                        *(uint32_t*)(po + 256) = low ? p0 : a[4];
                        *(uint32_t*)(po + 640) = low ? p1 : a[5];
                    } else {
                        *(uint32_t*)(po) = a[6];
                        *(uint32_t*)(po + 128) = a[8];
                        *(uint32_t*)(po + 384) = a[7];
                        *(uint32_t*)(po + 512) = a[9];
                        if (which < 2) {
                            const uint32_t u0 = bf2_fma(a[4], a[4], 0u), u1 = bf2_fma(a[5], a[5], 0u);
                            const uint32_t pe0 = bf2_fma(a[0], a[0], bf2_fma(a[2], a[2], low ? u0 : 0u));
                            const uint32_t pe1 = bf2_fma(a[1], a[1], bf2_fma(a[3], a[3], low ? u1 : 0u));
                            const uint32_t po0 = bf2_fma(a[6], a[6], bf2_fma(a[8], a[8], low ? 0u : u0));
                            const uint32_t po1 = bf2_fma(a[7], a[7], bf2_fma(a[9], a[9], low ? 0u : u1));
                            const float e0 = bf_lo(pe0) + bf_hi(pe0), e1 = bf_lo(pe1) + bf_hi(pe1);
                            const float o0 = bf_lo(po0) + bf_hi(po0), o1 = bf_lo(po1) + bf_hi(po1);
                            const bool b0 = c & 1, b1_ = c & 2;
                            const float x0 = (b0 ? e1 : e0) + __shfl_xor_sync(~0u, b0 ? e0 : e1, 1);
                            const float x1 = (b0 ? o1 : o0) + __shfl_xor_sync(~0u, b0 ? o0 : o1, 1);
                            float y = (b1_ ? x1 : x0) + __shfl_xor_sync(~0u, b1_ ? x0 : x1, 2);
                            if (which == 1 && (b0 ? emu1 : emu0)) y *= 0.25f;
                            g_nrm[(hs + (c >> 1)) * SEQ + row0 + (c & 1) * 8] = y;
                        }
                    }
                    if (it == 11) { __syncwarp(); if (lane == 0) mbar_arrive(bar + B_ST * 8); }
                }
            }
            wg_wait<0>();
            fence_regs(acc2);
            if (threadIdx.x == 256) TL(1, 2);
            mbar_wait(bar + B_AUX2 * 8, 0);
            const uint32_t* bias = reinterpret_cast<const uint32_t*>(smem + SM_BIAS) + c;
            const int mrow = w4 * 16 + (lane & 15);
            const uint32_t st_row = sAw + mrow * 128;
#pragma unroll
            for (int j = 0; j < 24; j += 2) {
                const uint32_t bA = bias[j * 4], bB = bias[j * 4 + 4];
                const float2 cA = cs[(30 + j) * 4], cB = cs[(31 + j) * 4];
                const float* a = acc2 + j * 4;
                const uint32_t r00 = pack_bf16(gelu_tanh(fmaf(a[0], r20, fmaf(e20, cA.x, bf_lo(bA)))), gelu_tanh(fmaf(a[1], r20, fmaf(e20, cA.y, bf_hi(bA)))));
                const uint32_t r10 = pack_bf16(gelu_tanh(fmaf(a[2], r21, fmaf(e21, cA.x, bf_lo(bA)))), gelu_tanh(fmaf(a[3], r21, fmaf(e21, cA.y, bf_hi(bA)))));
                const uint32_t r01 = pack_bf16(gelu_tanh(fmaf(a[4], r20, fmaf(e20, cB.x, bf_lo(bB)))), gelu_tanh(fmaf(a[5], r20, fmaf(e20, cB.y, bf_hi(bB)))));
                const uint32_t r11 = pack_bf16(gelu_tanh(fmaf(a[6], r21, fmaf(e21, cB.x, bf_lo(bB)))), gelu_tanh(fmaf(a[7], r21, fmaf(e21, cB.y, bf_hi(bB)))));
                const int chunk = (j & 7) + (lane >> 4);
                stmatrix_x4(st_row + (j >> 3) * 16384 + ((chunk ^ (mrow & 7)) << 4), r00, r10, r01, r11);
            }
            fence_proxy_async();
            asm volatile("bar.sync %0, 128;" ::"r"(wgi + 3) : "memory");
            if (w4 == 0 && lane == 0) {
#pragma unroll
                for (int b = 0; b < 3; b++) tma_store(&tm.h, sAw + b * 16384, cg * 192 + b * 64, rb * 128 + wi * 64);
                bulk_commit();
                bulk_wait_read();
            }
            __syncwarp();
            reg_dealloc<128>();
        }
        __syncthreads();
        if (threadIdx.x == 0) TL(1, 3);
    }

    {
        const uint32_t epoch = *reinterpret_cast<volatile uint32_t*>(smem + SM_EPOCH);
        const int h = blockIdx.x >> 2, qb = blockIdx.x & 3;
        const uint32_t sK = sb, sV = sb + IMG_BYTES, barKV = bar + B_KV * 8;
        if (threadIdx.x == 0) TL(2, 0);
        if (threadIdx.x < 192) *reinterpret_cast<uint4*>(smem + SM_ZERO + threadIdx.x * 16) = make_uint4(0, 0, 0, 0);
        fence_proxy_async();
        if (warp == 0) {
            if (elect_one()) {
                cnt_wait(CNT_QKV + h / 12, (epoch + 1) * 16);
                cnt_wait(CNT_QKV + (32 + h) / 12, (epoch + 1) * 16);
                cnt_wait(CNT_QKV + (64 + h) / 12, (epoch + 1) * 16);
                const uint8_t* gK = g_img + (size_t)(32 + h) * IMG_BYTES;
                const uint8_t* gV = g_img + (size_t)(64 + h) * IMG_BYTES;
                const uint8_t* gQ = g_img + (size_t)h * IMG_BYTES + qb * 64 * 384;
                mbar_expect_tx(barKV + 128, 6144);
                bulk_load(sK, gK, 6144, barKV + 128);
                for (int p = 0; p < 2; p++) {
                    mbar_expect_tx(bar + (B_Q + p) * 8, 12288);
                    bulk_load(sb + SM_Q + p * 12288, gQ + p * 12288, 12288, bar + (B_Q + p) * 8);
                }
                for (int i = 0; i < 16; i++) {
                    mbar_expect_tx(barKV + i * 8, i < 15 ? 12288 : 6144);
                    bulk_load(sV + i * 6144, gV + i * 6144, 6144, barKV + i * 8);
                    if (i < 15) bulk_load(sK + (i + 1) * 6144, gK + (i + 1) * 6144, 6144, barKV + i * 8);
                }
            }
            __syncwarp();
        }
        __syncthreads();
        if (threadIdx.x == 0) TL(2, 1);
        float* red = reinterpret_cast<float*>(smem + SM_RED);
        float kmax = 0.f, qmax = __ldcg(g_nrm + h * SEQ + qb * 512 + threadIdx.x);
#pragma unroll
        for (int i = 0; i < 4; i++) kmax = fmaxf(kmax, __ldcg(g_nrm + (32 + h) * SEQ + i * 512 + threadIdx.x));
#pragma unroll
        for (int o = 16; o; o >>= 1) {
            kmax = fmaxf(kmax, __shfl_xor_sync(~0u, kmax, o));
            qmax = fmaxf(qmax, __shfl_xor_sync(~0u, qmax, o));
        }
        if (lane == 0) { red[warp] = kmax; red[16 + warp] = qmax; }
        __syncthreads();
        kmax = red[lane & 15]; qmax = red[16 + (lane & 15)];
#pragma unroll
        for (int o = 8; o; o >>= 1) {
            kmax = fmaxf(kmax, __shfl_xor_sync(~0u, kmax, o));
            qmax = fmaxf(qmax, __shfl_xor_sync(~0u, qmax, o));
        }
        const bool safe = __all_sync(~0u, kmax * qmax * 1.1f <= SAFE_BOUND * SAFE_BOUND);
        const uint64_t dK0 = make_desc(sK, 128, 384, 0), dV0 = make_desc(sV, 384, 128, 0);
        auto publish_h = [&]() {
            if (warp == 8 || warp == 12) {
                if (lane == 0) { bulk_wait_all(); cnt_signal(CNT_H + rb); }
                __syncwarp();
            }
        };
        if (!safe) {
#pragma unroll 1
            for (int pass = 0; pass < 2; pass++) {
                const uint32_t sQ = sb + SM_Q + pass * 12288 + wgi * 3072;
                mbar_wait(bar + (B_Q + pass) * 8, 0);
                if (lane < 16) *reinterpret_cast<uint32_t*>(smem + (sQ - sb) + (w4 * 2 + (lane >> 3)) * 384 + 256 + (lane & 7) * 16 + ((h & 1) ? 0 : 8)) = 0u;
                fence_proxy_async();
                asm volatile("bar.sync %0, 128;" ::"r"(wgi + 3) : "memory");
                attn_rows_maxshift(sK, barKV, make_desc(sQ, 128, 384, 0), make_desc(sQ + 256, sb + SM_ZERO - (sQ + 256), 384, 0), h,
                                   qb * 512 + pass * 256 + wgi * 64 + w4 * 16);
                if (pass == 0) publish_h();
            }
        } else {
            const ExpConst kc = make_exp_const();
#pragma unroll 1
            for (int pass = 0; pass < 2; pass++) {
                const int rbase = qb * 512 + pass * 256 + wgi * 64 + w4 * 16;
                const uint32_t sQ = sb + SM_Q + pass * 12288 + wgi * 3072;
                const uint64_t dQ = make_desc(sQ, 128, 384, 0), dQ2 = make_desc(sQ + 256, sb + SM_ZERO - (sQ + 256), 384, 0);
                float o[12], sa[32], sc[32];
                uint32_t p[16];
#pragma unroll
                for (int i = 0; i < 12; i++) o[i] = 0.f;
                fence_regs(o);
                mbar_wait(bar + (B_Q + pass) * 8, 0);
                mbar_wait(barKV + 128, 0);
                qk_tile(sa, dQ, dQ2, dK0);
                wg_wait<0>();
                fence_regs(sa);
                uint64_t dK = dK0, dV = dV0;
                uint32_t bj = barKV;
#pragma unroll 1
                for (int j = 0; j < 16; j++) {
                    mbar_wait(bj, 0);
                    qk_tile(sc, dQ, dQ2, dK + 192);
                    wg_wait<1>();
                    exp_tile<0>(sa, p, kc);
                    pv_tile(o, p, dV);
                    wg_wait<1>();
                    fence_regs(sc);
                    mbar_wait(bj, 0);
                    qk_tile(sa, dQ, dQ2, dK + 384);
                    wg_wait<1>();
                    exp_tile<8>(sc, p, kc);
                    pv_tile(o, p, dV + 192);
                    wg_wait<1>();
                    fence_regs(sa);
                    dK += 384; dV += 384; bj += 8;
                }
                wg_wait<0>();
                fence_regs(o);
                store_o(o, h, rbase, lane);
                if (threadIdx.x == 0) TL(2, 2 + pass);
                if (pass == 0) publish_h();
            }
        }
        __syncthreads();
        if (threadIdx.x == 64) cnt_signal(CNT_O + qb);
        cluster_arrive_relaxed();
    }

    {
        const uint32_t epoch = *reinterpret_cast<volatile uint32_t*>(smem + SM_EPOCH);
        const int ct = cl & 3, rt = (cl >> 2) * 2 + rank;
        if (threadIdx.x == 0) TL(3, 0);
        const int orow = threadIdx.x >> 3, oseg = threadIdx.x & 7;
        const size_t ooff = (size_t)(rt * 64 + orow) * DM + ct * 160 + oseg * 20;
        uint2 xr[5], br[5];
#pragma unroll
        for (int i = 0; i < 5; i++) {
            xr[i] = __ldg(reinterpret_cast<const uint2*>(x + ooff) + i);
            br[i] = __ldg(reinterpret_cast<const uint2*>(b2 + ct * 160 + oseg * 20) + i);
        }
        cluster_wait();
        float* stg = reinterpret_cast<float*>(smem);
        if (warp == 4) {
            if (elect_one()) { prefetch_map(&tm.h); prefetch_map(&tm.o); prefetch_map(&tm.w2); prefetch_map(&tm.wo); cnt_wait(CNT_H + (rt >> 1), (epoch + 1) * 16); }
            __syncwarp();
#pragma unroll 1
            for (int kb = 0; kb < 34; kb++) {
                const int s = kb & 7;
                if (kb >= 8) mbar_wait(bar + (B_E3 + s) * 8, ((kb >> 3) - 1) & 1);
                if (elect_one()) {
                    if (kb == 24) { cnt_wait(CNT_O + (rt >> 3), (epoch + 1) * 32); TL(3, 1); }
                    const uint32_t dst = sb + s * G2_STAGE, fb = bar + (B_F3 + s) * 8;
                    const CUtensorMap* mA = kb < 24 ? &tm.h : &tm.o;
                    const CUtensorMap* mB = kb < 24 ? &tm.w2 : &tm.wo;
                    const int k0 = (kb < 24 ? kb : kb - 24) * 64;
                    mbar_expect_tx(fb, G2_STAGE);
                    tma_load(dst, mA, k0, rt * 64, fb);
                    const int first = ((kb & 1) == (int)rank) ? 0 : 3, last = ((kb & 1) == (int)rank) ? 3 : 5;
                    for (int b = first; b < last; b++) tma_load_mc(dst + 8192 + b * 4096, mB, ct * 160 + b * 32, k0, fb, 3);
                }
                __syncwarp();
            }
        } else if (wgi == 0) {
            float acc[80];
#pragma unroll 1
            for (int kb = 0; kb < 34; kb++) {
                const int s = kb & 7;
                mbar_wait(bar + (B_F3 + s) * 8, (kb >> 3) & 1);
                wg_fence();
                const uint64_t dA = make_desc(sb + s * G2_STAGE, 16, 1024, 1);
                const uint64_t dB = make_desc(sb + s * G2_STAGE + 8192, 4096, 512, 2);
#pragma unroll
                for (int kk = 0; kk < 4; kk++) wgmma_n160_ss_tb(acc, dA + kk * 2, dB + kk * 64, (kb | kk) != 0);
                wg_commit();
                if (kb > 0) {
                    wg_wait<1>();
                    if (kb <= 26) release_stage(bar + (B_E3 + ((kb - 1) & 7)) * 8, peer, lane);
                }
            }
            wg_wait<0>();
            fence_regs(acc);
            if (threadIdx.x == 0) TL(3, 2);
            const int r = w4 * 16 + g;
#pragma unroll
            for (int j = 0; j < 20; j++) {
                *reinterpret_cast<float2*>(stg + r * 168 + j * 8 + 2 * c) = make_float2(acc[4 * j], acc[4 * j + 1]);
                *reinterpret_cast<float2*>(stg + (r + 8) * 168 + j * 8 + 2 * c) = make_float2(acc[4 * j + 2], acc[4 * j + 3]);
            }
        }
        __syncthreads();
        const float4* sp = reinterpret_cast<const float4*>(stg + orow * 168 + oseg * 20);
#pragma unroll
        for (int i = 0; i < 5; i++) {
            const float4 a = sp[i];
            uint2 w;
            w.x = pack_bf16(a.x + bf_lo(br[i].x) + bf_lo(xr[i].x), a.y + bf_hi(br[i].x) + bf_hi(xr[i].x));
            w.y = pack_bf16(a.z + bf_lo(br[i].y) + bf_lo(xr[i].y), a.w + bf_hi(br[i].y) + bf_hi(xr[i].y));
            reinterpret_cast<uint2*>(out + ooff)[i] = w;
        }
        if (blockIdx.x == 0 && threadIdx.x == 0) g_epoch = epoch + 1;
        if (threadIdx.x == 0) TL(3, 3);
    }
    cluster_arrive_relaxed();
    cluster_wait();
}

typedef CUresult (*EncodeTiledFn)(CUtensorMap*, CUtensorMapDataType, cuuint32_t, void*, const cuuint64_t*,
                                  const cuuint64_t*, const cuuint32_t*, const cuuint32_t*, CUtensorMapInterleave,
                                  CUtensorMapSwizzle, CUtensorMapL2promotion, CUtensorMapFloatOOBfill);

CUtensorMap make_map(EncodeTiledFn enc, const void* ptr, int rows, int cols, int box_rows, int box_cols,
                     CUtensorMapSwizzle swz) {
    CUtensorMap m;
    cuuint64_t gd[2] = {(cuuint64_t)cols, (cuuint64_t)rows};
    cuuint64_t gs[1] = {(cuuint64_t)cols * 2};
    cuuint32_t bd[2] = {(cuuint32_t)box_cols, (cuuint32_t)box_rows};
    cuuint32_t es[2] = {1, 1};
    enc(&m, CU_TENSOR_MAP_DATA_TYPE_BFLOAT16, 2, const_cast<void*>(ptr), gd, gs, bd, es, CU_TENSOR_MAP_INTERLEAVE_NONE,
        swz, CU_TENSOR_MAP_L2_PROMOTION_L2_128B, CU_TENSOR_MAP_FLOAT_OOB_FILL_NONE);
    return m;
}

}

extern "C" void kernel_launch(void* const* d_in, const int* in_sizes, int n_in, void* d_out, int out_size) {
    (void)in_sizes; (void)n_in; (void)out_size;
    const __nv_bfloat16* x = (const __nv_bfloat16*)d_in[0];
    const __nv_bfloat16* wqkv = (const __nv_bfloat16*)d_in[1];
    const __nv_bfloat16* wo = (const __nv_bfloat16*)d_in[2];
    const __nv_bfloat16* w1 = (const __nv_bfloat16*)d_in[4];
    const __nv_bfloat16* b1 = (const __nv_bfloat16*)d_in[5];
    const __nv_bfloat16* w2 = (const __nv_bfloat16*)d_in[6];
    const __nv_bfloat16* b2 = (const __nv_bfloat16*)d_in[7];
    __nv_bfloat16* out = (__nv_bfloat16*)d_out;

    static EncodeTiledFn enc = nullptr;
    static void *p_h, *p_o;
    if (!enc) {
        cudaDriverEntryPointQueryResult qr;
        cudaGetDriverEntryPoint("cuTensorMapEncodeTiled", (void**)&enc, cudaEnableDefault, &qr);
        cudaGetSymbolAddress(&p_h, g_h);
        cudaGetSymbolAddress(&p_o, g_o);
        cudaFuncSetAttribute(k_fused, cudaFuncAttributeMaxDynamicSharedMemorySize, SM_TOTAL);
    }
    Maps tm;
    tm.x = make_map(enc, x, SEQ, DM, 128, 64, CU_TENSOR_MAP_SWIZZLE_128B);
    tm.wqkv = make_map(enc, wqkv, DM, 3 * DM, 32, 64, CU_TENSOR_MAP_SWIZZLE_128B);
    tm.w1 = make_map(enc, w1, DM, FF, 32, 64, CU_TENSOR_MAP_SWIZZLE_128B);
    tm.h = make_map(enc, p_h, SEQ, FF, 64, 64, CU_TENSOR_MAP_SWIZZLE_128B);
    tm.o = make_map(enc, p_o, SEQ, DM, 64, 64, CU_TENSOR_MAP_SWIZZLE_128B);
    tm.wo = make_map(enc, wo, DM, DM, 64, 32, CU_TENSOR_MAP_SWIZZLE_64B);
    tm.w2 = make_map(enc, w2, FF, DM, 64, 32, CU_TENSOR_MAP_SWIZZLE_64B);
    k_fused<<<128, 512, SM_TOTAL, cudaStreamPerThread>>>(tm, x, (const uint8_t*)wqkv, (const uint8_t*)w1, (const uint8_t*)w2,
                                                         (const uint8_t*)wo, b1, b2, out);
}
```

```cpp
#include <cuda_runtime.h>
#include <cuda_bf16.h>
#include <cuda.h>
#include <stdint.h>

namespace {

constexpr int SEQ = 2048, DM = 640, FF = 1536;
constexpr float LN_EPS = 1e-5f;

constexpr int IMG_BYTES = 256 * 384;
constexpr uint32_t EMU_MASK = 0xD5D5u;
constexpr float SAFE_BOUND = 80.0f;
#define XV_IT 1
#define PACE_NS 200
constexpr float QSCALE = 0.22360679774997896f * 1.4426950408889634f;

__device__ float4 g_stat[SEQ];
__device__ float2 g_csp[16 * 1728];
__device__ __align__(1024) uint8_t g_img[96 * IMG_BYTES + 1024];
__device__ float g_nrm[64 * SEQ];
__device__ __align__(1024) __nv_bfloat16 g_h[SEQ * FF];
__device__ __align__(1024) __nv_bfloat16 g_o[SEQ * DM];
constexpr int CNT_ST = 0, CNT_QKV = 16, CNT_H = 24, CNT_O = 40, CNT_CS = 44, CNT_CS2 = 52;
__device__ uint32_t g_cnt[60 * 32];
__device__ uint32_t g_epoch;

#define TL(kern, slot) do { } while (0)
#define IT(row, i) do { } while (0)

__device__ __forceinline__ uint32_t smem_u32(const void* p) { return (uint32_t)__cvta_generic_to_shared(p); }
__device__ __forceinline__ void mbar_init(uint32_t bar, int cnt) {
    asm volatile("mbarrier.init.shared::cta.b64 [%0], %1;" ::"r"(bar), "r"(cnt));
}
__device__ __forceinline__ void mbar_expect_tx(uint32_t bar, uint32_t bytes) {
    asm volatile("mbarrier.arrive.expect_tx.shared::cta.b64 _, [%0], %1;" ::"r"(bar), "r"(bytes) : "memory");
}
__device__ __forceinline__ void mbar_wait(uint32_t bar, uint32_t parity) {
    asm volatile("{\n.reg .pred p;\n.reg .u32 n;\nmov.u32 n, 0;\n"
                 "WAIT_LOOP:\nmbarrier.try_wait.parity.shared::cta.b64 p, [%0], %1;\n@p bra WAIT_DONE;\n"
                 "add.u32 n, n, 1;\nsetp.lt.u32 p, n, 4194304;\n@p bra WAIT_LOOP;\nWAIT_DONE:\n}"
                 ::"r"(bar), "r"(parity) : "memory");
}
__device__ __forceinline__ void mbar_arrive(uint32_t bar) {
    asm volatile("mbarrier.arrive.shared::cta.b64 _, [%0];" ::"r"(bar) : "memory");
}
__device__ __forceinline__ void mbar_arrive_cluster(uint32_t bar, uint32_t cta) {
    asm volatile("{\n.reg .b32 ra;\nmapa.shared::cluster.u32 ra, %0, %1;\n"
                 "mbarrier.arrive.shared::cluster.b64 _, [ra];\n}" ::"r"(bar), "r"(cta) : "memory");
}
__device__ __forceinline__ void fence_barrier_init() { asm volatile("fence.mbarrier_init.release.cluster;" ::: "memory"); }
__device__ __forceinline__ void fence_proxy_async() { asm volatile("fence.proxy.async.shared::cta;" ::: "memory"); }
__device__ __forceinline__ void cluster_sync() {
    asm volatile("barrier.cluster.arrive.release.aligned;\nbarrier.cluster.wait.acquire.aligned;" ::: "memory");
}
__device__ __forceinline__ bool elect_one() {
    uint32_t pred;
    asm volatile("{\n.reg .pred p;\nelect.sync _|p, 0xFFFFFFFF;\nselp.b32 %0, 1, 0, p;\n}" : "=r"(pred));
    return pred != 0;
}
__device__ __forceinline__ void pdl_launch() { asm volatile("griddepcontrol.launch_dependents;" ::: "memory"); }
__device__ __forceinline__ void pdl_wait() { asm volatile("griddepcontrol.wait;" ::: "memory"); }
__device__ __forceinline__ void prefetch_map(const CUtensorMap* m) {
    asm volatile("prefetch.tensormap [%0];" ::"l"(m) : "memory");
}
__device__ __forceinline__ void tma_load(uint32_t dst, const CUtensorMap* m, int c0, int c1, uint32_t bar) {
    asm volatile("cp.async.bulk.tensor.2d.shared::cluster.global.mbarrier::complete_tx::bytes [%0], [%1, {%3, %4}], [%2];"
                 ::"r"(dst), "l"(m), "r"(bar), "r"(c0), "r"(c1) : "memory");
}
__device__ __forceinline__ void tma_load_mc(uint32_t dst, const CUtensorMap* m, int c0, int c1, uint32_t bar, uint16_t mask) {
    asm volatile("cp.async.bulk.tensor.2d.shared::cluster.global.mbarrier::complete_tx::bytes.multicast::cluster"
                 " [%0], [%1, {%3, %4}], [%2], %5;"
                 ::"r"(dst), "l"(m), "r"(bar), "r"(c0), "r"(c1), "h"(mask) : "memory");
}
__device__ __forceinline__ void tma_store(const CUtensorMap* m, uint32_t src, int c0, int c1) {
    asm volatile("cp.async.bulk.tensor.2d.global.shared::cta.bulk_group [%0, {%2, %3}], [%1];"
                 ::"l"(m), "r"(src), "r"(c0), "r"(c1) : "memory");
}
__device__ __forceinline__ void bulk_commit() { asm volatile("cp.async.bulk.commit_group;" ::: "memory"); }
__device__ __forceinline__ void bulk_wait_all() { asm volatile("cp.async.bulk.wait_group 0;" ::: "memory"); }
__device__ __forceinline__ void bulk_load(uint32_t dst, const void* src, uint32_t bytes, uint32_t bar) {
    asm volatile("cp.async.bulk.shared::cluster.global.mbarrier::complete_tx::bytes [%0], [%1], %2, [%3];"
                 ::"r"(dst), "l"(src), "r"(bytes), "r"(bar) : "memory");
}
__device__ __forceinline__ void prefetch_l2(const void* p, uint32_t bytes) {
    asm volatile("cp.async.bulk.prefetch.L2.global [%0], %1;" ::"l"(p), "r"(bytes) : "memory");
}
__device__ __forceinline__ void tma_prefetch_l2(const CUtensorMap* m, int c0, int c1) {
    asm volatile("cp.async.bulk.prefetch.tensor.2d.L2.global.tile [%0, {%1, %2}];" ::"l"(m), "r"(c0), "r"(c1) : "memory");
}
__device__ __forceinline__ void wg_fence() { asm volatile("wgmma.fence.sync.aligned;" ::: "memory"); }
__device__ __forceinline__ void wg_commit() { asm volatile("wgmma.commit_group.sync.aligned;" ::: "memory"); }
template <int N> __device__ __forceinline__ void wg_wait() {
    asm volatile("wgmma.wait_group.sync.aligned %0;" ::"n"(N) : "memory");
}
template <int N> __device__ __forceinline__ void reg_alloc() { asm volatile("setmaxnreg.inc.sync.aligned.u32 %0;" ::"n"(N)); }
template <int N> __device__ __forceinline__ void reg_dealloc() { asm volatile("setmaxnreg.dec.sync.aligned.u32 %0;" ::"n"(N)); }
template <int N> __device__ __forceinline__ void fence_regs(float (&d)[N]) {
#pragma unroll
    for (int i = 0; i < N; i++) asm volatile("" : "+f"(d[i])::"memory");
}
__device__ __forceinline__ uint64_t make_desc(uint32_t addr, uint32_t lbo, uint32_t sbo, uint32_t swz) {
    return (uint64_t)((addr & 0x3FFFF) >> 4) | ((uint64_t)(lbo >> 4) << 16) | ((uint64_t)(sbo >> 4) << 32) |
           ((uint64_t)swz << 62);
}
__device__ __forceinline__ uint32_t pack_bf16(float lo, float hi) {
    uint32_t r;
    asm("cvt.rn.bf16x2.f32 %0, %1, %2;" : "=r"(r) : "f"(hi), "f"(lo));
    return r;
}
__device__ __forceinline__ float ex2(float x) {
    float r;
    asm("ex2.approx.ftz.f32 %0, %1;" : "=f"(r) : "f"(x));
    return r;
}
__device__ __forceinline__ float bf_lo(uint32_t v) { return __uint_as_float(v << 16); }
__device__ __forceinline__ float bf_hi(uint32_t v) { return __uint_as_float(v & 0xFFFF0000u); }
__device__ __forceinline__ void stmatrix_x4(uint32_t addr, uint32_t r0, uint32_t r1, uint32_t r2, uint32_t r3) {
    asm volatile("stmatrix.sync.aligned.m8n8.x4.shared.b16 [%0], {%1, %2, %3, %4};"
                 ::"r"(addr), "r"(r0), "r"(r1), "r"(r2), "r"(r3) : "memory");
}

__device__ __forceinline__ void wgmma_n200_ss_tb(float (&d)[100], uint64_t descA, uint64_t descB, int scaleD) {
    asm volatile("{\n.reg .pred p;\nsetp.ne.b32 p, %102, 0;\n"
        "wgmma.mma_async.sync.aligned.m64n200k16.f32.bf16.bf16 {"
        "%0, %1, %2, %3, %4, %5, %6, %7, %8, %9, %10, %11, %12, %13, %14, %15, "
        "%16, %17, %18, %19, %20, %21, %22, %23, %24, %25, %26, %27, %28, %29, %30, %31, "
        "%32, %33, %34, %35, %36, %37, %38, %39, %40, %41, %42, %43, %44, %45, %46, %47, "
        "%48, %49, %50, %51, %52, %53, %54, %55, %56, %57, %58, %59, %60, %61, %62, %63, "
        "%64, %65, %66, %67, %68, %69, %70, %71, %72, %73, %74, %75, %76, %77, %78, %79, "
        "%80, %81, %82, %83, %84, %85, %86, %87, %88, %89, %90, %91, %92, %93, %94, %95, "
        "%96, %97, %98, %99}, "
        "%100, %101, p, 1, 1, 0, 1;\n}\n"
        : "+f"(d[0]), "+f"(d[1]), "+f"(d[2]), "+f"(d[3]), "+f"(d[4]), "+f"(d[5]), "+f"(d[6]), "+f"(d[7]),
          "+f"(d[8]), "+f"(d[9]), "+f"(d[10]), "+f"(d[11]), "+f"(d[12]), "+f"(d[13]), "+f"(d[14]), "+f"(d[15]),
          "+f"(d[16]), "+f"(d[17]), "+f"(d[18]), "+f"(d[19]), "+f"(d[20]), "+f"(d[21]), "+f"(d[22]), "+f"(d[23]),
          "+f"(d[24]), "+f"(d[25]), "+f"(d[26]), "+f"(d[27]), "+f"(d[28]), "+f"(d[29]), "+f"(d[30]), "+f"(d[31]),
          "+f"(d[32]), "+f"(d[33]), "+f"(d[34]), "+f"(d[35]), "+f"(d[36]), "+f"(d[37]), "+f"(d[38]), "+f"(d[39]),
          "+f"(d[40]), "+f"(d[41]), "+f"(d[42]), "+f"(d[43]), "+f"(d[44]), "+f"(d[45]), "+f"(d[46]), "+f"(d[47]),
          "+f"(d[48]), "+f"(d[49]), "+f"(d[50]), "+f"(d[51]), "+f"(d[52]), "+f"(d[53]), "+f"(d[54]), "+f"(d[55]),
          "+f"(d[56]), "+f"(d[57]), "+f"(d[58]), "+f"(d[59]), "+f"(d[60]), "+f"(d[61]), "+f"(d[62]), "+f"(d[63]),
          "+f"(d[64]), "+f"(d[65]), "+f"(d[66]), "+f"(d[67]), "+f"(d[68]), "+f"(d[69]), "+f"(d[70]), "+f"(d[71]),
          "+f"(d[72]), "+f"(d[73]), "+f"(d[74]), "+f"(d[75]), "+f"(d[76]), "+f"(d[77]), "+f"(d[78]), "+f"(d[79]),
          "+f"(d[80]), "+f"(d[81]), "+f"(d[82]), "+f"(d[83]), "+f"(d[84]), "+f"(d[85]), "+f"(d[86]), "+f"(d[87]),
          "+f"(d[88]), "+f"(d[89]), "+f"(d[90]), "+f"(d[91]), "+f"(d[92]), "+f"(d[93]), "+f"(d[94]), "+f"(d[95]),
          "+f"(d[96]), "+f"(d[97]), "+f"(d[98]), "+f"(d[99])
        : "l"(descA), "l"(descB), "r"(scaleD));
}

__device__ __forceinline__ void wgmma_n40_ss_tb(float (&d)[20], uint64_t descA, uint64_t descB, int scaleD) {
    asm volatile("{\n.reg .pred p;\nsetp.ne.b32 p, %22, 0;\n"
        "wgmma.mma_async.sync.aligned.m64n40k16.f32.bf16.bf16 {"
        "%0, %1, %2, %3, %4, %5, %6, %7, %8, %9, %10, %11, %12, %13, %14, %15, "
        "%16, %17, %18, %19}, "
        "%20, %21, p, 1, 1, 0, 1;\n}\n"
        : "+f"(d[0]), "+f"(d[1]), "+f"(d[2]), "+f"(d[3]), "+f"(d[4]), "+f"(d[5]), "+f"(d[6]), "+f"(d[7]),
          "+f"(d[8]), "+f"(d[9]), "+f"(d[10]), "+f"(d[11]), "+f"(d[12]), "+f"(d[13]), "+f"(d[14]), "+f"(d[15]),
          "+f"(d[16]), "+f"(d[17]), "+f"(d[18]), "+f"(d[19])
        : "l"(descA), "l"(descB), "r"(scaleD));
}

__device__ __forceinline__ void wgmma_n192_ss_tb(float (&d)[96], uint64_t descA, uint64_t descB, int scaleD) {
    asm volatile("{\n.reg .pred p;\nsetp.ne.b32 p, %98, 0;\n"
        "wgmma.mma_async.sync.aligned.m64n192k16.f32.bf16.bf16 {"
        "%0, %1, %2, %3, %4, %5, %6, %7, %8, %9, %10, %11, %12, %13, %14, %15, "
        "%16, %17, %18, %19, %20, %21, %22, %23, %24, %25, %26, %27, %28, %29, %30, %31, "
        "%32, %33, %34, %35, %36, %37, %38, %39, %40, %41, %42, %43, %44, %45, %46, %47, "
        "%48, %49, %50, %51, %52, %53, %54, %55, %56, %57, %58, %59, %60, %61, %62, %63, "
        "%64, %65, %66, %67, %68, %69, %70, %71, %72, %73, %74, %75, %76, %77, %78, %79, "
        "%80, %81, %82, %83, %84, %85, %86, %87, %88, %89, %90, %91, %92, %93, %94, %95}, "
        "%96, %97, p, 1, 1, 0, 1;\n}\n"
        : "+f"(d[0]), "+f"(d[1]), "+f"(d[2]), "+f"(d[3]), "+f"(d[4]), "+f"(d[5]), "+f"(d[6]), "+f"(d[7]),
          "+f"(d[8]), "+f"(d[9]), "+f"(d[10]), "+f"(d[11]), "+f"(d[12]), "+f"(d[13]), "+f"(d[14]), "+f"(d[15]),
          "+f"(d[16]), "+f"(d[17]), "+f"(d[18]), "+f"(d[19]), "+f"(d[20]), "+f"(d[21]), "+f"(d[22]), "+f"(d[23]),
          "+f"(d[24]), "+f"(d[25]), "+f"(d[26]), "+f"(d[27]), "+f"(d[28]), "+f"(d[29]), "+f"(d[30]), "+f"(d[31]),
          "+f"(d[32]), "+f"(d[33]), "+f"(d[34]), "+f"(d[35]), "+f"(d[36]), "+f"(d[37]), "+f"(d[38]), "+f"(d[39]),
          "+f"(d[40]), "+f"(d[41]), "+f"(d[42]), "+f"(d[43]), "+f"(d[44]), "+f"(d[45]), "+f"(d[46]), "+f"(d[47]),
          "+f"(d[48]), "+f"(d[49]), "+f"(d[50]), "+f"(d[51]), "+f"(d[52]), "+f"(d[53]), "+f"(d[54]), "+f"(d[55]),
          "+f"(d[56]), "+f"(d[57]), "+f"(d[58]), "+f"(d[59]), "+f"(d[60]), "+f"(d[61]), "+f"(d[62]), "+f"(d[63]),
          "+f"(d[64]), "+f"(d[65]), "+f"(d[66]), "+f"(d[67]), "+f"(d[68]), "+f"(d[69]), "+f"(d[70]), "+f"(d[71]),
          "+f"(d[72]), "+f"(d[73]), "+f"(d[74]), "+f"(d[75]), "+f"(d[76]), "+f"(d[77]), "+f"(d[78]), "+f"(d[79]),
          "+f"(d[80]), "+f"(d[81]), "+f"(d[82]), "+f"(d[83]), "+f"(d[84]), "+f"(d[85]), "+f"(d[86]), "+f"(d[87]),
          "+f"(d[88]), "+f"(d[89]), "+f"(d[90]), "+f"(d[91]), "+f"(d[92]), "+f"(d[93]), "+f"(d[94]), "+f"(d[95])
        : "l"(descA), "l"(descB), "r"(scaleD));
}

__device__ __forceinline__ void wgmma_n192_ss_tb_z(float (&d)[96], uint64_t descA, uint64_t descB) {
    asm volatile("{\n.reg .pred p;\nsetp.ne.b32 p, 0, 0;\n"
        "wgmma.mma_async.sync.aligned.m64n192k16.f32.bf16.bf16 {"
        "%0, %1, %2, %3, %4, %5, %6, %7, %8, %9, %10, %11, %12, %13, %14, %15, "
        "%16, %17, %18, %19, %20, %21, %22, %23, %24, %25, %26, %27, %28, %29, %30, %31, "
        "%32, %33, %34, %35, %36, %37, %38, %39, %40, %41, %42, %43, %44, %45, %46, %47, "
        "%48, %49, %50, %51, %52, %53, %54, %55, %56, %57, %58, %59, %60, %61, %62, %63, "
        "%64, %65, %66, %67, %68, %69, %70, %71, %72, %73, %74, %75, %76, %77, %78, %79, "
        "%80, %81, %82, %83, %84, %85, %86, %87, %88, %89, %90, %91, %92, %93, %94, %95}, "
        "%96, %97, p, 1, 1, 0, 1;\n}\n"
        : "=f"(d[0]), "=f"(d[1]), "=f"(d[2]), "=f"(d[3]), "=f"(d[4]), "=f"(d[5]), "=f"(d[6]), "=f"(d[7]),
          "=f"(d[8]), "=f"(d[9]), "=f"(d[10]), "=f"(d[11]), "=f"(d[12]), "=f"(d[13]), "=f"(d[14]), "=f"(d[15]),
          "=f"(d[16]), "=f"(d[17]), "=f"(d[18]), "=f"(d[19]), "=f"(d[20]), "=f"(d[21]), "=f"(d[22]), "=f"(d[23]),
          "=f"(d[24]), "=f"(d[25]), "=f"(d[26]), "=f"(d[27]), "=f"(d[28]), "=f"(d[29]), "=f"(d[30]), "=f"(d[31]),
          "=f"(d[32]), "=f"(d[33]), "=f"(d[34]), "=f"(d[35]), "=f"(d[36]), "=f"(d[37]), "=f"(d[38]), "=f"(d[39]),
          "=f"(d[40]), "=f"(d[41]), "=f"(d[42]), "=f"(d[43]), "=f"(d[44]), "=f"(d[45]), "=f"(d[46]), "=f"(d[47]),
          "=f"(d[48]), "=f"(d[49]), "=f"(d[50]), "=f"(d[51]), "=f"(d[52]), "=f"(d[53]), "=f"(d[54]), "=f"(d[55]),
          "=f"(d[56]), "=f"(d[57]), "=f"(d[58]), "=f"(d[59]), "=f"(d[60]), "=f"(d[61]), "=f"(d[62]), "=f"(d[63]),
          "=f"(d[64]), "=f"(d[65]), "=f"(d[66]), "=f"(d[67]), "=f"(d[68]), "=f"(d[69]), "=f"(d[70]), "=f"(d[71]),
          "=f"(d[72]), "=f"(d[73]), "=f"(d[74]), "=f"(d[75]), "=f"(d[76]), "=f"(d[77]), "=f"(d[78]), "=f"(d[79]),
          "=f"(d[80]), "=f"(d[81]), "=f"(d[82]), "=f"(d[83]), "=f"(d[84]), "=f"(d[85]), "=f"(d[86]), "=f"(d[87]),
          "=f"(d[88]), "=f"(d[89]), "=f"(d[90]), "=f"(d[91]), "=f"(d[92]), "=f"(d[93]), "=f"(d[94]), "=f"(d[95])
        : "l"(descA), "l"(descB));
}

__device__ __forceinline__ void wgmma_n160_ss_tb(float (&d)[80], uint64_t descA, uint64_t descB, int scaleD) {
    asm volatile("{\n.reg .pred p;\nsetp.ne.b32 p, %82, 0;\n"
        "wgmma.mma_async.sync.aligned.m64n160k16.f32.bf16.bf16 {"
        "%0, %1, %2, %3, %4, %5, %6, %7, %8, %9, %10, %11, %12, %13, %14, %15, "
        "%16, %17, %18, %19, %20, %21, %22, %23, %24, %25, %26, %27, %28, %29, %30, %31, "
        "%32, %33, %34, %35, %36, %37, %38, %39, %40, %41, %42, %43, %44, %45, %46, %47, "
        "%48, %49, %50, %51, %52, %53, %54, %55, %56, %57, %58, %59, %60, %61, %62, %63, "
        "%64, %65, %66, %67, %68, %69, %70, %71, %72, %73, %74, %75, %76, %77, %78, %79}, "
        "%80, %81, p, 1, 1, 0, 1;\n}\n"
        : "+f"(d[0]), "+f"(d[1]), "+f"(d[2]), "+f"(d[3]), "+f"(d[4]), "+f"(d[5]), "+f"(d[6]), "+f"(d[7]),
          "+f"(d[8]), "+f"(d[9]), "+f"(d[10]), "+f"(d[11]), "+f"(d[12]), "+f"(d[13]), "+f"(d[14]), "+f"(d[15]),
          "+f"(d[16]), "+f"(d[17]), "+f"(d[18]), "+f"(d[19]), "+f"(d[20]), "+f"(d[21]), "+f"(d[22]), "+f"(d[23]),
          "+f"(d[24]), "+f"(d[25]), "+f"(d[26]), "+f"(d[27]), "+f"(d[28]), "+f"(d[29]), "+f"(d[30]), "+f"(d[31]),
          "+f"(d[32]), "+f"(d[33]), "+f"(d[34]), "+f"(d[35]), "+f"(d[36]), "+f"(d[37]), "+f"(d[38]), "+f"(d[39]),
          "+f"(d[40]), "+f"(d[41]), "+f"(d[42]), "+f"(d[43]), "+f"(d[44]), "+f"(d[45]), "+f"(d[46]), "+f"(d[47]),
          "+f"(d[48]), "+f"(d[49]), "+f"(d[50]), "+f"(d[51]), "+f"(d[52]), "+f"(d[53]), "+f"(d[54]), "+f"(d[55]),
          "+f"(d[56]), "+f"(d[57]), "+f"(d[58]), "+f"(d[59]), "+f"(d[60]), "+f"(d[61]), "+f"(d[62]), "+f"(d[63]),
          "+f"(d[64]), "+f"(d[65]), "+f"(d[66]), "+f"(d[67]), "+f"(d[68]), "+f"(d[69]), "+f"(d[70]), "+f"(d[71]),
          "+f"(d[72]), "+f"(d[73]), "+f"(d[74]), "+f"(d[75]), "+f"(d[76]), "+f"(d[77]), "+f"(d[78]), "+f"(d[79])
        : "l"(descA), "l"(descB), "r"(scaleD));
}

__device__ __forceinline__ void wgmma_n64_ss(float (&d)[32], uint64_t descA, uint64_t descB, int scaleD) {
    asm volatile("{\n.reg .pred p;\nsetp.ne.b32 p, %34, 0;\n"
        "wgmma.mma_async.sync.aligned.m64n64k16.f32.bf16.bf16 {"
        "%0, %1, %2, %3, %4, %5, %6, %7, %8, %9, %10, %11, %12, %13, %14, %15, "
        "%16, %17, %18, %19, %20, %21, %22, %23, %24, %25, %26, %27, %28, %29, %30, %31}, "
        "%32, %33, p, 1, 1, 0, 0;\n}\n"
        : "+f"(d[0]), "+f"(d[1]), "+f"(d[2]), "+f"(d[3]), "+f"(d[4]), "+f"(d[5]), "+f"(d[6]), "+f"(d[7]),
          "+f"(d[8]), "+f"(d[9]), "+f"(d[10]), "+f"(d[11]), "+f"(d[12]), "+f"(d[13]), "+f"(d[14]), "+f"(d[15]),
          "+f"(d[16]), "+f"(d[17]), "+f"(d[18]), "+f"(d[19]), "+f"(d[20]), "+f"(d[21]), "+f"(d[22]), "+f"(d[23]),
          "+f"(d[24]), "+f"(d[25]), "+f"(d[26]), "+f"(d[27]), "+f"(d[28]), "+f"(d[29]), "+f"(d[30]), "+f"(d[31])
        : "l"(descA), "l"(descB), "r"(scaleD));
}

__device__ __forceinline__ void wgmma_n64_ss_z(float (&d)[32], uint64_t descA, uint64_t descB) {
    asm volatile("{\n.reg .pred p;\nsetp.ne.b32 p, 0, 0;\n"
        "wgmma.mma_async.sync.aligned.m64n64k16.f32.bf16.bf16 {"
        "%0, %1, %2, %3, %4, %5, %6, %7, %8, %9, %10, %11, %12, %13, %14, %15, "
        "%16, %17, %18, %19, %20, %21, %22, %23, %24, %25, %26, %27, %28, %29, %30, %31}, "
        "%32, %33, p, 1, 1, 0, 0;\n}\n"
        : "=f"(d[0]), "=f"(d[1]), "=f"(d[2]), "=f"(d[3]), "=f"(d[4]), "=f"(d[5]), "=f"(d[6]), "=f"(d[7]),
          "=f"(d[8]), "=f"(d[9]), "=f"(d[10]), "=f"(d[11]), "=f"(d[12]), "=f"(d[13]), "=f"(d[14]), "=f"(d[15]),
          "=f"(d[16]), "=f"(d[17]), "=f"(d[18]), "=f"(d[19]), "=f"(d[20]), "=f"(d[21]), "=f"(d[22]), "=f"(d[23]),
          "=f"(d[24]), "=f"(d[25]), "=f"(d[26]), "=f"(d[27]), "=f"(d[28]), "=f"(d[29]), "=f"(d[30]), "=f"(d[31])
        : "l"(descA), "l"(descB));
}

__device__ __forceinline__ void wgmma_n24_rs_tb(float (&d)[12], uint32_t a0, uint32_t a1, uint32_t a2, uint32_t a3, uint64_t descB, int scaleD) {
    asm volatile("{\n.reg .pred p;\nsetp.ne.b32 p, %17, 0;\n"
        "wgmma.mma_async.sync.aligned.m64n24k16.f32.bf16.bf16 {"
        "%0, %1, %2, %3, %4, %5, %6, %7, %8, %9, %10, %11}, "
        "{%12, %13, %14, %15}, %16, p, 1, 1, 1;\n}\n"
        : "+f"(d[0]), "+f"(d[1]), "+f"(d[2]), "+f"(d[3]), "+f"(d[4]), "+f"(d[5]), "+f"(d[6]), "+f"(d[7]),
          "+f"(d[8]), "+f"(d[9]), "+f"(d[10]), "+f"(d[11])
        : "r"(a0), "r"(a1), "r"(a2), "r"(a3), "l"(descB), "r"(scaleD));
}

__device__ __forceinline__ void cnt_signal(int idx) {
    asm volatile("fence.acq_rel.gpu;\nred.relaxed.gpu.global.add.u32 [%0], 1;"
                 ::"l"(g_cnt + idx * 32) : "memory");
}
__device__ __forceinline__ void cnt_wait(int idx, uint32_t target) {
    const uint32_t* p = g_cnt + idx * 32;
#pragma unroll 1
    for (uint32_t i = 0; i < (1u << 22); i++) {
        uint32_t v;
        asm volatile("ld.acquire.gpu.global.u32 %0, [%1];" : "=r"(v) : "l"(p) : "memory");
        if ((int32_t)(v - target) >= 0) break;
    }
    asm volatile("fence.proxy.async.global;" ::: "memory");
}
__device__ __forceinline__ void cluster_arrive() { asm volatile("barrier.cluster.arrive.release.aligned;" ::: "memory"); }
__device__ __forceinline__ void cluster_arrive_relaxed() { asm volatile("barrier.cluster.arrive.relaxed.aligned;" ::: "memory"); }
__device__ __forceinline__ void cluster_wait() { asm volatile("barrier.cluster.wait.acquire.aligned;" ::: "memory"); }
__device__ __forceinline__ void bulk_wait_read() { asm volatile("cp.async.bulk.wait_group.read 0;" ::: "memory"); }

__device__ __forceinline__ float gelu_tanh(float x) {
    const float u = x * (0.7978845608028654f + 0.035677408136300125f * x * x);
    float t;
    asm("tanh.approx.f32 %0, %1;" : "=f"(t) : "f"(u));
    const float h = 0.5f * x;
    return fmaf(h, t, h);
}
__device__ __forceinline__ void release_stage(uint32_t bar, uint32_t peer, int lane) {
    if (lane == 0) { mbar_arrive(bar); mbar_arrive_cluster(bar, peer); }
}

constexpr int SM_RING = 163840;
constexpr int SM_Q = 2 * IMG_BYTES, SM_ZERO = SM_Q + 24576;
constexpr int G2_STAGE = 8192 + 20480;
constexpr int SM_MISC = 229376;
constexpr int SM_BIAS = SM_MISC, SM_RED = SM_BIAS + 384, SM_BAR = SM_RED + 128;
constexpr int B_A = 0, B_F1 = 10, B_E1 = 14, B_F2 = 18, B_E2 = 23, B_KV = 28, B_Q = 45, B_F3 = 47, B_E3 = 55, B_ST = 63, B_STAT = 65, B_AUX = 66, B_AUX2 = 67, B_COUNT = 68;
constexpr int SM_EPOCH = SM_BAR + 544;
constexpr int SM_CS = SM_EPOCH + 16;
constexpr int SM_DBG = SM_CS + 1728;
constexpr int SM_TOTAL = SM_DBG + 128;
static_assert(SM_TOTAL <= 232448, "shared memory budget");

struct Maps { CUtensorMap x, wqkv, w1, h, o, wo, w2; };

__device__ __forceinline__ uint32_t bf2_fma(uint32_t a, uint32_t b, uint32_t c) {
    uint32_t r;
    asm("fma.rn.bf16x2 %0, %1, %2, %3;" : "=r"(r) : "r"(a), "r"(b), "r"(c));
    return r;
}
__device__ __forceinline__ uint32_t lop_and_or(uint32_t a, uint32_t m, uint32_t o) {
    uint32_t r;
    asm("lop3.b32 %0, %1, %2, %3, 0xEA;" : "=r"(r) : "r"(a), "r"(m), "r"(o));
    return r;
}
struct ExpConst { uint32_t mask, slope; };
__device__ __forceinline__ ExpConst make_exp_const() {
    ExpConst k;
    asm volatile("mov.b32 %0, 0x007F007F;" : "=r"(k.mask));
    asm volatile("mov.b32 %0, 0x3EF83EF8;" : "=r"(k.slope));
    return k;
}
__device__ __forceinline__ uint32_t exp2_pair_fma(float t0, float t1, const ExpConst& k) {
    const uint32_t L = __byte_perm(__float_as_uint(t0), __float_as_uint(t1), 0x6521);
    const uint32_t g = lop_and_or(L, k.mask, 0x3F803F80u);
    const uint32_t u = bf2_fma(g, k.slope, 0xBF37BF37u);
    const uint32_t e = bf2_fma(u, u, 0xBD71BD71u);
    return bf2_fma(L, e, L);
}
template <int SHIFT>
__device__ __forceinline__ void exp_tile(const float (&s)[32], uint32_t (&p)[16], const ExpConst& k) {
#pragma unroll
    for (int b = 0; b < 8; b++) {
        if ((EMU_MASK >> (b + SHIFT)) & 1) {
            p[2 * b] = exp2_pair_fma(s[4 * b], s[4 * b + 1], k);
            p[2 * b + 1] = exp2_pair_fma(s[4 * b + 2], s[4 * b + 3], k);
        } else {
            p[2 * b] = pack_bf16(ex2(s[4 * b]), ex2(s[4 * b + 1]));
            p[2 * b + 1] = pack_bf16(ex2(s[4 * b + 2]), ex2(s[4 * b + 3]));
        }
    }
}

__device__ __forceinline__ void qk_tile(float (&s)[32], uint64_t dQ, uint64_t dQ2, uint64_t dK) {
    wg_fence();
    wgmma_n64_ss_z(s, dQ, dK);
    wgmma_n64_ss(s, dQ2, dK + 16, 1);
    wg_commit();
}
__device__ __forceinline__ void pv_tile(float (&o)[12], const uint32_t (&p)[16], uint64_t dV) {
    wg_fence();
#pragma unroll
    for (int ks = 0; ks < 4; ks++)
        wgmma_n24_rs_tb(o, p[4 * ks], p[4 * ks + 1], p[4 * ks + 2], p[4 * ks + 3], dV + ks * 48, 1);
    wg_commit();
}
__device__ __forceinline__ void store_o(const float (&o)[12], int h, int rbase, int lane) {
    const int g = lane >> 2, c = lane & 3;
    const bool odd = h & 1;
    const int lsrc = (lane & ~3) | (odd ? 0 : 2);
    const float i0 = 1.f / __shfl_sync(~0u, o[8], lsrc), i1 = 1.f / __shfl_sync(~0u, o[10], lsrc);
    __nv_bfloat16* dst = g_o + (size_t)(rbase + g) * DM + h * 20;
    const int d0 = (odd ? 4 : 0) + 2 * c, d1 = d0 + 8, d2 = odd ? 2 * c - 4 : 16 + 2 * c;
    *(uint32_t*)(dst + d0) = pack_bf16(o[0] * i0, o[1] * i0);
    *(uint32_t*)(dst + d1) = pack_bf16(o[4] * i0, o[5] * i0);
    *(uint32_t*)(dst + 8 * DM + d0) = pack_bf16(o[2] * i1, o[3] * i1);
    *(uint32_t*)(dst + 8 * DM + d1) = pack_bf16(o[6] * i1, o[7] * i1);
    if (odd ? (c >= 2) : (c < 2)) {
        *(uint32_t*)(dst + d2) = pack_bf16(o[8] * i0, o[9] * i0);
        *(uint32_t*)(dst + 8 * DM + d2) = pack_bf16(o[10] * i1, o[11] * i1);
    }
}

__device__ __forceinline__ void attn_rows_maxshift(uint32_t sK, uint32_t barKV, uint64_t dQ, uint64_t dQ2, int h, int rbase) {
    const int lane = threadIdx.x & 31;
    const uint64_t dK0 = make_desc(sK, 128, 384, 0), dV0 = make_desc(sK + IMG_BYTES, 384, 128, 0);
    float o[12], s[32];
    uint32_t p[16];
#pragma unroll
    for (int i = 0; i < 12; i++) o[i] = 0.f;
    float m0 = -3.0e38f, m1 = -3.0e38f;
    mbar_wait(barKV + 128, 0);
#pragma unroll 1
    for (int t = 0; t < 32; t++) {
        mbar_wait(barKV + (t >> 1) * 8, 0);
        qk_tile(s, dQ, dQ2, dK0 + t * 192);
        wg_wait<0>();
        fence_regs(s);
        const uint32_t mask = EMU_MASK >> ((t & 1) * 8);
        float n0 = m0, n1 = m1;
#pragma unroll
        for (int b = 0; b < 8; b++) {
            const bool emu = (mask >> b) & 1;
            const float f = emu ? 0.5f : 1.f, off = emu ? -383.00390625f : 0.f;
#pragma unroll
            for (int i = 0; i < 4; i++) s[4 * b + i] = fmaf(s[4 * b + i], f, off);
            n0 = fmaxf(n0, fmaxf(s[4 * b], s[4 * b + 1]));
            n1 = fmaxf(n1, fmaxf(s[4 * b + 2], s[4 * b + 3]));
        }
        n0 = fmaxf(n0, __shfl_xor_sync(~0u, n0, 1)); n0 = fmaxf(n0, __shfl_xor_sync(~0u, n0, 2));
        n1 = fmaxf(n1, __shfl_xor_sync(~0u, n1, 1)); n1 = fmaxf(n1, __shfl_xor_sync(~0u, n1, 2));
        const float c0 = ex2(m0 - n0), c1 = ex2(m1 - n1);
        m0 = n0; m1 = n1;
#pragma unroll
        for (int b = 0; b < 3; b++) { o[4 * b] *= c0; o[4 * b + 1] *= c0; o[4 * b + 2] *= c1; o[4 * b + 3] *= c1; }
#pragma unroll
        for (int b = 0; b < 8; b++) {
            p[2 * b] = pack_bf16(ex2(s[4 * b] - m0), ex2(s[4 * b + 1] - m0));
            p[2 * b + 1] = pack_bf16(ex2(s[4 * b + 2] - m1), ex2(s[4 * b + 3] - m1));
        }
        pv_tile(o, p, dV0 + t * 192);
        wg_wait<0>();
        fence_regs(o);
    }
    store_o(o, h, rbase, lane);
}

__global__ void __launch_bounds__(512, 1) __cluster_dims__(2, 1, 1)
k_fused(const __grid_constant__ Maps tm, const __nv_bfloat16* __restrict__ x, const uint8_t* __restrict__ wqkv,
        const uint8_t* __restrict__ w1, const uint8_t* __restrict__ w2, const uint8_t* __restrict__ wo,
        const __nv_bfloat16* __restrict__ b1, const __nv_bfloat16* __restrict__ b2, __nv_bfloat16* __restrict__ out) {
    extern __shared__ __align__(1024) uint8_t smem[];
    const uint32_t sb = smem_u32(smem);
    const uint32_t bar = sb + SM_BAR;
    const int warp = __shfl_sync(~0u, threadIdx.x >> 5, 0), lane = threadIdx.x & 31;
    const int wgi = warp >> 2, w4 = warp & 3, g = lane >> 2, c = lane & 3;
    const uint32_t rank = blockIdx.x & 1, peer = rank ^ 1;
    const int cl = blockIdx.x >> 1;
    const int cg = cl >> 3, rb = (cl & 7) * 2 + rank;

    if (threadIdx.x == 0) TL(0, 0);
    if (warp == 15 && lane < 4) prefetch_map(lane == 0 ? &tm.x : lane == 1 ? &tm.wqkv : lane == 2 ? &tm.w1 : &tm.h);
    if (elect_one()) {
#pragma unroll
        for (int j = 0; j < 5; j++) {
            const int i = warp * 5 + j;
            const int cnt = (i >= B_E1 && i < B_F2) || (i >= B_E2 && i < B_KV) ? 16
                          : (i >= B_E3 && i <= B_ST) || i == B_STAT ? 8 : i == B_ST + 1 ? 2 : i == B_AUX ? 4 : i == B_AUX2 ? 3 : 1;
            if (i < B_COUNT) mbar_init(bar + i * 8, cnt);
        }
        fence_barrier_init();
    }
    __syncthreads();
    if (threadIdx.x == 0) TL(0, 1);
    cluster_arrive_relaxed();
    cluster_wait();
    if (threadIdx.x == 0) TL(0, 3);

    {
        const uint32_t sB = sb + SM_RING;
        if (threadIdx.x == 0) TL(1, 0);
        if (wgi < 2) {
            reg_dealloc<56>();
            if (threadIdx.x == 0) TL(4, 2);
            if (warp == 0) {
#pragma unroll 1
                for (int it = 0; it < 20; it++) {
                    const int s = it & 3;
                    const int kb = it < 2 ? it : (it & 1) ? (it + 1) >> 1 : 10;
                    if (it >= 4) mbar_wait(bar + (B_E1 + s) * 8, ((it >> 2) - 1) & 1);
                    else if (it > 0) __nanosleep(PACE_NS);
                    if (elect_one()) {
                        if (kb < 10) {
                            mbar_expect_tx(bar + (B_A + kb) * 8, 16384);
                            tma_load(sb + kb * 16384, &tm.x, kb * 64, rb * 128, bar + (B_A + kb) * 8);
                        }
                        const uint32_t dst = sB + s * 16384 + rank * 8192, fb = bar + (B_F1 + s) * 8;
                        const int c0 = cg * 240 + rank * 128;
                        mbar_expect_tx(fb, 16384);
                        tma_load_mc(dst, &tm.wqkv, c0, it * 32, fb, 3);
                        tma_load_mc(dst + 4096, &tm.wqkv, c0 + 64, it * 32, fb, 3);
                    }
                    __syncwarp();
                    if (lane == 0 && it < 8) TL(5, it) ;
                }
#pragma unroll 1
                for (int it = 0; it < 20; it++) {
                    const int s = it % 5;
                    if (it < 5) { if (it != 3) mbar_wait(bar + (B_E1 + (it == 4 ? 3 : it)) * 8, 0); }
                    else mbar_wait(bar + (B_E2 + s) * 8, ((it / 5) - 1) & 1);
                    if (elect_one()) {
                        const uint32_t dst = sB + s * 12288, fb = bar + (B_F2 + s) * 8;
                        mbar_expect_tx(fb, 12288);
                        if ((it & 1) == (int)rank) {
                            tma_load_mc(dst, &tm.w1, cg * 192, it * 32, fb, 3);
                            tma_load_mc(dst + 4096, &tm.w1, cg * 192 + 64, it * 32, fb, 3);
                        } else {
                            tma_load_mc(dst + 8192, &tm.w1, cg * 192 + 128, it * 32, fb, 3);
                        }
                    }
                    __syncwarp();
                }
            } else {
                const int ht = threadIdx.x - 32;
                if (ht == 160) *reinterpret_cast<volatile uint32_t*>(smem + SM_EPOCH) = *(volatile uint32_t*)&g_epoch;
                auto slab_sum = [&](const uint32_t* src, int pitch) {
                    float s0 = 0.f, s1 = 0.f;
                    uint32_t v[40];
#pragma unroll
                    for (int k = 0; k < 40; k++) v[k] = __ldg(src + k * pitch);
#pragma unroll
                    for (int k = 0; k < 40; k++) { s0 += bf_lo(v[k]); s1 += bf_hi(v[k]); }
                    return make_float2(s0, s1);
                };
                auto gather = [&](int idx) {
                    float s0 = 0.f, s1 = 0.f;
#pragma unroll
                    for (int r = 0; r < 16; r++) {
                        const float2 v = __ldcg(g_csp + r * 1728 + cg * 216 + idx);
                        s0 += v.x; s1 += v.y;
                    }
                    reinterpret_cast<float2*>(smem + SM_CS)[idx] = make_float2(s0, s1);
                };
                if (warp == 7) {
                    mbar_wait(bar + B_STAT * 8, 0);
                    if (elect_one()) cnt_signal(CNT_ST + rb);
                    __syncwarp();
                }
                if (ht < 120)
                    g_csp[rb * 1728 + cg * 216 + ht] = slab_sum(reinterpret_cast<const uint32_t*>(wqkv) + rb * 40 * 960 + cg * 120 + ht, 960);
                if (threadIdx.x == 64) IT(3, 0);
                if (threadIdx.x == 192) IT(3, 1);
                if (warp != 7) asm volatile("bar.sync 8, 192;" ::: "memory");
                const uint32_t epoch = *reinterpret_cast<volatile uint32_t*>(smem + SM_EPOCH);
                if (warp == 6) { if (elect_one()) cnt_signal(CNT_CS + cg); __syncwarp(); }

                if (threadIdx.x == 64) IT(3, 2);
                if (warp <= 4) {
                    if (lane == 0) { cnt_wait(CNT_CS + cg, (epoch + 1) * 16); cnt_wait(CNT_ST + rb, (epoch + 1) * 8); }
                    __syncwarp();
                    if (threadIdx.x == 64) IT(3, 4);
                    if (ht < 120) gather(ht);
                    __syncwarp();
                    if (threadIdx.x == 64) IT(3, 5);
                    if (lane == 0) mbar_arrive(bar + B_AUX * 8);
                }
                if (ht >= 128) {
                    g_csp[rb * 1728 + cg * 216 + 120 + (ht - 128)] = slab_sum(reinterpret_cast<const uint32_t*>(w1) + rb * 40 * 768 + cg * 96 + (ht - 128), 768);
                    reinterpret_cast<uint32_t*>(smem + SM_BIAS)[ht - 128] = __ldg(reinterpret_cast<const uint32_t*>(b1 + cg * 192) + (ht - 128));
                    asm volatile("bar.sync 9, 96;" ::: "memory");
                    const uint32_t epoch2 = *reinterpret_cast<volatile uint32_t*>(smem + SM_EPOCH);
                    if (warp == 5) { if (elect_one()) cnt_signal(CNT_CS2 + cg); __syncwarp(); }
                    if (warp == 6 && elect_one()) {
                        prefetch_l2(w2 + blockIdx.x * 15360, 15360);
                        prefetch_l2(wo + blockIdx.x * 6400, 6400);
                    }
                    if (lane == 0) cnt_wait(CNT_CS2 + cg, (epoch2 + 1) * 16);
                    __syncwarp();
                    gather(120 + (ht - 128));
                    __syncwarp();
                    if (lane == 0) mbar_arrive(bar + B_AUX2 * 8);
                }
                if (warp == 4) {
                    mbar_wait(bar + B_ST * 8, 0);
                    if (elect_one()) cnt_signal(CNT_QKV + cg);
                    __syncwarp();
                }
            }
            asm volatile("bar.sync %0, 128;" ::"r"(wgi + 3) : "memory");
            reg_alloc<128>();
        } else {
            reg_alloc<200>();
            if (threadIdx.x == 256) TL(4, 0);
            const int wi = wgi - 2;
            const int row0 = rb * 128 + wi * 64 + w4 * 16 + g;
            const uint32_t sAw = sb + wi * 8192;
            const int rbk = row0 >> 3, hs0 = cg * 12;
            {
                const int srow = rb * 128 + cg * 16 + (warp - 8) * 2 + (lane >> 4);
                uint4 xv[5];
#pragma unroll
                for (int i = 0; i < 5; i++) xv[i] = __ldg(reinterpret_cast<const uint4*>(x + (size_t)srow * DM) + (lane & 15) + 16 * i);
                float sm = 0.f;
#pragma unroll
                for (int i = 0; i < 5; i++)
                    sm += ((bf_lo(xv[i].x) + bf_hi(xv[i].x)) + (bf_lo(xv[i].y) + bf_hi(xv[i].y))) +
                          ((bf_lo(xv[i].z) + bf_hi(xv[i].z)) + (bf_lo(xv[i].w) + bf_hi(xv[i].w)));
#pragma unroll
                for (int o = 8; o; o >>= 1) sm += __shfl_xor_sync(~0u, sm, o);
                const float mu = sm * (1.f / DM);
                float q0 = 0.f, q1 = 0.f;
#pragma unroll
                for (int i = 0; i < 5; i++) {
                    const uint32_t w[4] = {xv[i].x, xv[i].y, xv[i].z, xv[i].w};
#pragma unroll
                    for (int j = 0; j < 4; j++) {
                        const float d0 = bf_lo(w[j]) - mu, d1 = bf_hi(w[j]) - mu;
                        q0 = fmaf(d0, d0, q0); q1 = fmaf(d1, d1, q1);
                    }
                }
                float q = q0 + q1;
#pragma unroll
                for (int o = 8; o; o >>= 1) q += __shfl_xor_sync(~0u, q, o);
                const float var = q * (1.f / DM);
                const float r1 = rsqrtf(var + LN_EPS);
                const float r2 = rsqrtf(var * r1 * r1 + LN_EPS);
                if ((lane & 15) == 0) g_stat[srow] = make_float4(mu, r1, r1 * r2, 0.f);
                __syncwarp();
                if (lane == 0) mbar_arrive(bar + B_STAT * 8);
            }
            if (threadIdx.x == 256) TL(4, 1);
            float accA[100], accB[20];
            const uint64_t dA0 = make_desc(sAw, 16, 1024, 1), dB0 = make_desc(sB, 4096, 1024, 1);
#pragma unroll 2
            for (int it = 0; it < 20; it++) {
                const int s = it & 3;
                if (!(it & 1)) mbar_wait(bar + (B_A + (it >> 1)) * 8, 0);
                if (threadIdx.x == 256 && it == 0) TL(0, 2);
                if (threadIdx.x == 256 && it == 2) TL(4, 3);
                if (threadIdx.x == 256) IT(0, it);
                mbar_wait(bar + (B_F1 + s) * 8, (it >> 2) & 1);
                if (threadIdx.x == 256) IT(1, it);
                const uint64_t dA = dA0 + (it >> 1) * 1024 + (it & 1) * 4, dB = dB0 + s * 1024;
                wg_fence();
                wgmma_n40_ss_tb(accB, dA, dB + 769, it > 0);
                wgmma_n40_ss_tb(accB, dA + 2, dB + 769 + 128, 1);
                wgmma_n200_ss_tb(accA, dA, dB, it > 0);
                wgmma_n200_ss_tb(accA, dA + 2, dB + 128, 1);
                wg_commit();
                if (it > 0) { wg_wait<1>(); release_stage(bar + (B_E1 + ((it - 1) & 3)) * 8, peer, lane); }
            }
            if (threadIdx.x == 256) IT(2, 0);
            mbar_wait(bar + B_AUX * 8, 0);
            if (threadIdx.x == 256) IT(2, 1);
            const float4 st0 = __ldcg(g_stat + row0), st1 = __ldcg(g_stat + row0 + 8);
            wg_wait<0>();
            release_stage(bar + (B_E1 + 3) * 8, peer, lane);
            fence_regs(accA);
            fence_regs(accB);
            if (threadIdx.x == 256) TL(1, 1);
            const float2* cs = reinterpret_cast<const float2*>(smem + SM_CS) + c;
            uint8_t* img = g_img + (size_t)hs0 * IMG_BYTES + rbk * 384 + g * 16 + c * 4;
            const bool emu0 = (EMU_MASK >> (rbk & 15)) & 1, emu1 = (EMU_MASK >> ((rbk + 1) & 15)) & 1;
            const bool low = c < 2;
            uint32_t pk[60];
#pragma unroll
            for (int m = 0; m < 6; m++) {
                const int which = (hs0 + 2 * m) >> 5;
                const float m0 = st0.y * (which == 0 ? QSCALE : (which == 1 && emu0) ? 2.f : 1.f);
                const float m1 = st1.y * (which == 0 ? QSCALE : (which == 1 && emu1) ? 2.f : 1.f);
                const float d0 = -st0.x * m0, d1 = -st1.x * m1;
                const float* a = m < 5 ? &accA[20 * m] : accB;
#pragma unroll
                for (int b = 0; b < 5; b++) {
                    const float2 cv = cs[(5 * m + b) * 4];
                    pk[10 * m + 2 * b] = pack_bf16(fmaf(a[4 * b], m0, d0 * cv.x), fmaf(a[4 * b + 1], m0, d0 * cv.y));
                    pk[10 * m + 2 * b + 1] = pack_bf16(fmaf(a[4 * b + 2], m1, d1 * cv.x), fmaf(a[4 * b + 3], m1, d1 * cv.y));
                }
            }
            const float r20 = st0.z, r21 = st1.z, e20 = -st0.x * st0.z, e21 = -st1.x * st1.z;
            if (threadIdx.x == 256) IT(2, 2);
            float acc2[96];
#pragma unroll
            for (int it = 0; it < 20; it++) {
                const int s = it % 5;
                if (threadIdx.x == 256) IT(0, 20 + it);
                mbar_wait(bar + (B_F2 + s) * 8, (it / 5) & 1);
                if (threadIdx.x == 256) IT(1, 20 + it);
                wg_fence();
                const uint64_t dA = make_desc(sAw + (it >> 1) * 16384 + (it & 1) * 64, 16, 1024, 1);
                const uint64_t dB = make_desc(sB + s * 12288, 4096, 1024, 1);
                if (it == 0) wgmma_n192_ss_tb_z(acc2, dA, dB); else wgmma_n192_ss_tb(acc2, dA, dB, 1);
                wgmma_n192_ss_tb(acc2, dA + 2, dB + 128, 1);
                wg_commit();
                if (it > 0) {
                    wg_wait<1>();
                    if (it <= 15) release_stage(bar + (B_E2 + (it - 1) % 5) * 8, peer, lane);
                }
                if (it < 12) {
                    const int m = it / 2, part = it % 2;
                    const int hs = hs0 + 2 * m, which = hs >> 5;
                    const uint32_t* a = pk + 10 * m;
                    uint8_t* pe = img + (2 * m) * IMG_BYTES;
                    uint8_t* po = pe + IMG_BYTES;
                    if (part == 0) {
                        const uint32_t padv = which == 0 ? 0x3F803F80u : which == 1 ? 0xBFFF4440u : 0x00003F80u;
                        const uint32_t p0 = ((c & 1) || (which == 1 && !emu0)) ? 0u : padv;
                        const uint32_t p1 = ((c & 1) || (which == 1 && !emu1)) ? 0u : padv;
                        *(uint32_t*)(pe) = a[0];
                        *(uint32_t*)(pe + 128) = a[2];
                        *(uint32_t*)(pe + 256) = low ? a[4] : p0;
                        *(uint32_t*)(pe + 384) = a[1];
                        *(uint32_t*)(pe + 512) = a[3];
                        *(uint32_t*)(pe + 640) = low ? a[5] : p1;
                        *(uint32_t*)(po + 256) = low ? p0 : a[4];
                        *(uint32_t*)(po + 640) = low ? p1 : a[5];
                    } else {
                        *(uint32_t*)(po) = a[6];
                        *(uint32_t*)(po + 128) = a[8];
                        *(uint32_t*)(po + 384) = a[7];
                        *(uint32_t*)(po + 512) = a[9];
                        if (which < 2) {
                            const uint32_t u0 = bf2_fma(a[4], a[4], 0u), u1 = bf2_fma(a[5], a[5], 0u);
                            const uint32_t pe0 = bf2_fma(a[0], a[0], bf2_fma(a[2], a[2], low ? u0 : 0u));
                            const uint32_t pe1 = bf2_fma(a[1], a[1], bf2_fma(a[3], a[3], low ? u1 : 0u));
                            const uint32_t po0 = bf2_fma(a[6], a[6], bf2_fma(a[8], a[8], low ? 0u : u0));
                            const uint32_t po1 = bf2_fma(a[7], a[7], bf2_fma(a[9], a[9], low ? 0u : u1));
                            const float e0 = bf_lo(pe0) + bf_hi(pe0), e1 = bf_lo(pe1) + bf_hi(pe1);
                            const float o0 = bf_lo(po0) + bf_hi(po0), o1 = bf_lo(po1) + bf_hi(po1);
                            const bool b0 = c & 1, b1_ = c & 2;
                            const float x0 = (b0 ? e1 : e0) + __shfl_xor_sync(~0u, b0 ? e0 : e1, 1);
                            const float x1 = (b0 ? o1 : o0) + __shfl_xor_sync(~0u, b0 ? o0 : o1, 1);
                            float y = (b1_ ? x1 : x0) + __shfl_xor_sync(~0u, b1_ ? x0 : x1, 2);
                            if (which == 1 && (b0 ? emu1 : emu0)) y *= 0.25f;
                            g_nrm[(hs + (c >> 1)) * SEQ + row0 + (c & 1) * 8] = y;
                        }
                    }
                    if (it == 11) { __syncwarp(); if (lane == 0) mbar_arrive(bar + B_ST * 8); }
                }
            }
            wg_wait<0>();
            fence_regs(acc2);
            if (threadIdx.x == 256) TL(1, 2);
            mbar_wait(bar + B_AUX2 * 8, 0);
            const uint32_t* bias = reinterpret_cast<const uint32_t*>(smem + SM_BIAS) + c;
            const int mrow = w4 * 16 + (lane & 15);
            const uint32_t st_row = sAw + mrow * 128;
#pragma unroll
            for (int j = 0; j < 24; j += 2) {
                const uint32_t bA = bias[j * 4], bB = bias[j * 4 + 4];
                const float2 cA = cs[(30 + j) * 4], cB = cs[(31 + j) * 4];
                const float* a = acc2 + j * 4;
                const uint32_t r00 = pack_bf16(gelu_tanh(fmaf(a[0], r20, fmaf(e20, cA.x, bf_lo(bA)))), gelu_tanh(fmaf(a[1], r20, fmaf(e20, cA.y, bf_hi(bA)))));
                const uint32_t r10 = pack_bf16(gelu_tanh(fmaf(a[2], r21, fmaf(e21, cA.x, bf_lo(bA)))), gelu_tanh(fmaf(a[3], r21, fmaf(e21, cA.y, bf_hi(bA)))));
                const uint32_t r01 = pack_bf16(gelu_tanh(fmaf(a[4], r20, fmaf(e20, cB.x, bf_lo(bB)))), gelu_tanh(fmaf(a[5], r20, fmaf(e20, cB.y, bf_hi(bB)))));
                const uint32_t r11 = pack_bf16(gelu_tanh(fmaf(a[6], r21, fmaf(e21, cB.x, bf_lo(bB)))), gelu_tanh(fmaf(a[7], r21, fmaf(e21, cB.y, bf_hi(bB)))));
                const int chunk = (j & 7) + (lane >> 4);
                stmatrix_x4(st_row + (j >> 3) * 16384 + ((chunk ^ (mrow & 7)) << 4), r00, r10, r01, r11);
            }
            fence_proxy_async();
            asm volatile("bar.sync %0, 128;" ::"r"(wgi + 3) : "memory");
            if (w4 == 0 && lane == 0) {
#pragma unroll
                for (int b = 0; b < 3; b++) tma_store(&tm.h, sAw + b * 16384, cg * 192 + b * 64, rb * 128 + wi * 64);
                bulk_commit();
                bulk_wait_read();
            }
            __syncwarp();
            reg_dealloc<128>();
        }
        __syncthreads();
        if (threadIdx.x == 0) TL(1, 3);
    }

    {
        const uint32_t epoch = *reinterpret_cast<volatile uint32_t*>(smem + SM_EPOCH);
        const int h = blockIdx.x >> 2, qb = blockIdx.x & 3;
        const uint32_t sK = sb, sV = sb + IMG_BYTES, barKV = bar + B_KV * 8;
        if (threadIdx.x == 0) TL(2, 0);
        if (threadIdx.x < 192) *reinterpret_cast<uint4*>(smem + SM_ZERO + threadIdx.x * 16) = make_uint4(0, 0, 0, 0);
        fence_proxy_async();
        if (warp == 0) {
            if (elect_one()) {
                cnt_wait(CNT_QKV + h / 12, (epoch + 1) * 16);
                cnt_wait(CNT_QKV + (32 + h) / 12, (epoch + 1) * 16);
                cnt_wait(CNT_QKV + (64 + h) / 12, (epoch + 1) * 16);
                const uint8_t* gK = g_img + (size_t)(32 + h) * IMG_BYTES;
                const uint8_t* gV = g_img + (size_t)(64 + h) * IMG_BYTES;
                const uint8_t* gQ = g_img + (size_t)h * IMG_BYTES + qb * 64 * 384;
                mbar_expect_tx(barKV + 128, 6144);
                bulk_load(sK, gK, 6144, barKV + 128);
                for (int p = 0; p < 2; p++) {
                    mbar_expect_tx(bar + (B_Q + p) * 8, 12288);
                    bulk_load(sb + SM_Q + p * 12288, gQ + p * 12288, 12288, bar + (B_Q + p) * 8);
                }
                for (int i = 0; i < 16; i++) {
                    mbar_expect_tx(barKV + i * 8, i < 15 ? 12288 : 6144);
                    bulk_load(sV + i * 6144, gV + i * 6144, 6144, barKV + i * 8);
                    if (i < 15) bulk_load(sK + (i + 1) * 6144, gK + (i + 1) * 6144, 6144, barKV + i * 8);
                }
            }
            __syncwarp();
        }
        __syncthreads();
        if (threadIdx.x == 0) TL(2, 1);
        float* red = reinterpret_cast<float*>(smem + SM_RED);
        float kmax = 0.f, qmax = __ldcg(g_nrm + h * SEQ + qb * 512 + threadIdx.x);
#pragma unroll
        for (int i = 0; i < 4; i++) kmax = fmaxf(kmax, __ldcg(g_nrm + (32 + h) * SEQ + i * 512 + threadIdx.x));
#pragma unroll
        for (int o = 16; o; o >>= 1) {
            kmax = fmaxf(kmax, __shfl_xor_sync(~0u, kmax, o));
            qmax = fmaxf(qmax, __shfl_xor_sync(~0u, qmax, o));
        }
        if (lane == 0) { red[warp] = kmax; red[16 + warp] = qmax; }
        __syncthreads();
        kmax = red[lane & 15]; qmax = red[16 + (lane & 15)];
#pragma unroll
        for (int o = 8; o; o >>= 1) {
            kmax = fmaxf(kmax, __shfl_xor_sync(~0u, kmax, o));
            qmax = fmaxf(qmax, __shfl_xor_sync(~0u, qmax, o));
        }
        const bool safe = __all_sync(~0u, kmax * qmax * 1.1f <= SAFE_BOUND * SAFE_BOUND);
        const uint64_t dK0 = make_desc(sK, 128, 384, 0), dV0 = make_desc(sV, 384, 128, 0);
        auto publish_h = [&]() {
            if (warp == 8 || warp == 12) {
                if (lane == 0) { bulk_wait_all(); cnt_signal(CNT_H + rb); }
                __syncwarp();
            }
        };
        if (!safe) {
#pragma unroll 1
            for (int pass = 0; pass < 2; pass++) {
                const uint32_t sQ = sb + SM_Q + pass * 12288 + wgi * 3072;
                mbar_wait(bar + (B_Q + pass) * 8, 0);
                if (lane < 16) *reinterpret_cast<uint32_t*>(smem + (sQ - sb) + (w4 * 2 + (lane >> 3)) * 384 + 256 + (lane & 7) * 16 + ((h & 1) ? 0 : 8)) = 0u;
                fence_proxy_async();
                asm volatile("bar.sync %0, 128;" ::"r"(wgi + 3) : "memory");
                attn_rows_maxshift(sK, barKV, make_desc(sQ, 128, 384, 0), make_desc(sQ + 256, sb + SM_ZERO - (sQ + 256), 384, 0), h,
                                   qb * 512 + pass * 256 + wgi * 64 + w4 * 16);
                if (pass == 0) publish_h();
            }
        } else {
            const ExpConst kc = make_exp_const();
#pragma unroll 1
            for (int pass = 0; pass < 2; pass++) {
                const int rbase = qb * 512 + pass * 256 + wgi * 64 + w4 * 16;
                const uint32_t sQ = sb + SM_Q + pass * 12288 + wgi * 3072;
                const uint64_t dQ = make_desc(sQ, 128, 384, 0), dQ2 = make_desc(sQ + 256, sb + SM_ZERO - (sQ + 256), 384, 0);
                float o[12], sa[32], sc[32];
                uint32_t p[16];
#pragma unroll
                for (int i = 0; i < 12; i++) o[i] = 0.f;
                fence_regs(o);
                mbar_wait(bar + (B_Q + pass) * 8, 0);
                mbar_wait(barKV + 128, 0);
                qk_tile(sa, dQ, dQ2, dK0);
                wg_wait<0>();
                fence_regs(sa);
                uint64_t dK = dK0, dV = dV0;
                uint32_t bj = barKV;
#pragma unroll 1
                for (int j = 0; j < 16; j++) {
                    mbar_wait(bj, 0);
                    qk_tile(sc, dQ, dQ2, dK + 192);
                    wg_wait<1>();
                    exp_tile<0>(sa, p, kc);
                    pv_tile(o, p, dV);
                    wg_wait<1>();
                    fence_regs(sc);
                    mbar_wait(bj, 0);
                    qk_tile(sa, dQ, dQ2, dK + 384);
                    wg_wait<1>();
                    exp_tile<8>(sc, p, kc);
                    pv_tile(o, p, dV + 192);
                    wg_wait<1>();
                    fence_regs(sa);
                    dK += 384; dV += 384; bj += 8;
                }
                wg_wait<0>();
                fence_regs(o);
                store_o(o, h, rbase, lane);
                if (threadIdx.x == 0) TL(2, 2 + pass);
                if (pass == 0) publish_h();
            }
        }
        __syncthreads();
        if (threadIdx.x == 64) cnt_signal(CNT_O + qb);
        cluster_arrive_relaxed();
    }

    {
        const uint32_t epoch = *reinterpret_cast<volatile uint32_t*>(smem + SM_EPOCH);
        const int ct = cl & 3, rt = (cl >> 2) * 2 + rank;
        if (threadIdx.x == 0) TL(3, 0);
        const int orow = threadIdx.x >> 3, oseg = threadIdx.x & 7;
        const size_t ooff = (size_t)(rt * 64 + orow) * DM + ct * 160 + oseg * 20;
        uint2 xr[5], br[5];
#pragma unroll
        for (int i = 0; i < 5; i++) {
            xr[i] = __ldg(reinterpret_cast<const uint2*>(x + ooff) + i);
            br[i] = __ldg(reinterpret_cast<const uint2*>(b2 + ct * 160 + oseg * 20) + i);
        }
        cluster_wait();
        float* stg = reinterpret_cast<float*>(smem);
        if (warp == 4) {
            if (elect_one()) { prefetch_map(&tm.h); prefetch_map(&tm.o); prefetch_map(&tm.w2); prefetch_map(&tm.wo); cnt_wait(CNT_H + (rt >> 1), (epoch + 1) * 16); }
            __syncwarp();
#pragma unroll 1
            for (int kb = 0; kb < 34; kb++) {
                const int s = kb & 7;
                if (kb >= 8) mbar_wait(bar + (B_E3 + s) * 8, ((kb >> 3) - 1) & 1);
                if (elect_one()) {
                    if (kb == 24) { cnt_wait(CNT_O + (rt >> 3), (epoch + 1) * 32); TL(3, 1); }
                    const uint32_t dst = sb + s * G2_STAGE, fb = bar + (B_F3 + s) * 8;
                    const CUtensorMap* mA = kb < 24 ? &tm.h : &tm.o;
                    const CUtensorMap* mB = kb < 24 ? &tm.w2 : &tm.wo;
                    const int k0 = (kb < 24 ? kb : kb - 24) * 64;
                    mbar_expect_tx(fb, G2_STAGE);
                    tma_load(dst, mA, k0, rt * 64, fb);
                    const int first = ((kb & 1) == (int)rank) ? 0 : 3, last = ((kb & 1) == (int)rank) ? 3 : 5;
                    for (int b = first; b < last; b++) tma_load_mc(dst + 8192 + b * 4096, mB, ct * 160 + b * 32, k0, fb, 3);
                }
                __syncwarp();
            }
        } else if (wgi == 0) {
            float acc[80];
#pragma unroll 1
            for (int kb = 0; kb < 34; kb++) {
                const int s = kb & 7;
                mbar_wait(bar + (B_F3 + s) * 8, (kb >> 3) & 1);
                wg_fence();
                const uint64_t dA = make_desc(sb + s * G2_STAGE, 16, 1024, 1);
                const uint64_t dB = make_desc(sb + s * G2_STAGE + 8192, 4096, 512, 2);
#pragma unroll
                for (int kk = 0; kk < 4; kk++) wgmma_n160_ss_tb(acc, dA + kk * 2, dB + kk * 64, (kb | kk) != 0);
                wg_commit();
                if (kb > 0) {
                    wg_wait<1>();
                    if (kb <= 26) release_stage(bar + (B_E3 + ((kb - 1) & 7)) * 8, peer, lane);
                }
            }
            wg_wait<0>();
            fence_regs(acc);
            if (threadIdx.x == 0) TL(3, 2);
            const int r = w4 * 16 + g;
#pragma unroll
            for (int j = 0; j < 20; j++) {
                *reinterpret_cast<float2*>(stg + r * 168 + j * 8 + 2 * c) = make_float2(acc[4 * j], acc[4 * j + 1]);
                *reinterpret_cast<float2*>(stg + (r + 8) * 168 + j * 8 + 2 * c) = make_float2(acc[4 * j + 2], acc[4 * j + 3]);
            }
        }
        __syncthreads();
        const float4* sp = reinterpret_cast<const float4*>(stg + orow * 168 + oseg * 20);
#pragma unroll
        for (int i = 0; i < 5; i++) {
            const float4 a = sp[i];
            uint2 w;
            w.x = pack_bf16(a.x + bf_lo(br[i].x) + bf_lo(xr[i].x), a.y + bf_hi(br[i].x) + bf_hi(xr[i].x));
            w.y = pack_bf16(a.z + bf_lo(br[i].y) + bf_lo(xr[i].y), a.w + bf_hi(br[i].y) + bf_hi(xr[i].y));
            reinterpret_cast<uint2*>(out + ooff)[i] = w;
        }
        if (blockIdx.x == 0 && threadIdx.x == 0) g_epoch = epoch + 1;
        if (threadIdx.x == 0) TL(3, 3);
    }
    cluster_arrive_relaxed();
    cluster_wait();
}

typedef CUresult (*EncodeTiledFn)(CUtensorMap*, CUtensorMapDataType, cuuint32_t, void*, const cuuint64_t*,
                                  const cuuint64_t*, const cuuint32_t*, const cuuint32_t*, CUtensorMapInterleave,
                                  CUtensorMapSwizzle, CUtensorMapL2promotion, CUtensorMapFloatOOBfill);

CUtensorMap make_map(EncodeTiledFn enc, const void* ptr, int rows, int cols, int box_rows, int box_cols,
                     CUtensorMapSwizzle swz) {
    CUtensorMap m;
    cuuint64_t gd[2] = {(cuuint64_t)cols, (cuuint64_t)rows};
    cuuint64_t gs[1] = {(cuuint64_t)cols * 2};
    cuuint32_t bd[2] = {(cuuint32_t)box_cols, (cuuint32_t)box_rows};
    cuuint32_t es[2] = {1, 1};
    enc(&m, CU_TENSOR_MAP_DATA_TYPE_BFLOAT16, 2, const_cast<void*>(ptr), gd, gs, bd, es, CU_TENSOR_MAP_INTERLEAVE_NONE,
        swz, CU_TENSOR_MAP_L2_PROMOTION_L2_128B, CU_TENSOR_MAP_FLOAT_OOB_FILL_NONE);
    return m;
}

}

extern "C" void kernel_launch(void* const* d_in, const int* in_sizes, int n_in, void* d_out, int out_size) {
    (void)in_sizes; (void)n_in; (void)out_size;
    const __nv_bfloat16* x = (const __nv_bfloat16*)d_in[0];
    const __nv_bfloat16* wqkv = (const __nv_bfloat16*)d_in[1];
    const __nv_bfloat16* wo = (const __nv_bfloat16*)d_in[2];
    const __nv_bfloat16* w1 = (const __nv_bfloat16*)d_in[4];
    const __nv_bfloat16* b1 = (const __nv_bfloat16*)d_in[5];
    const __nv_bfloat16* w2 = (const __nv_bfloat16*)d_in[6];
    const __nv_bfloat16* b2 = (const __nv_bfloat16*)d_in[7];
    __nv_bfloat16* out = (__nv_bfloat16*)d_out;

    static EncodeTiledFn enc = nullptr;
    static void *p_h, *p_o;
    if (!enc) {
        cudaDriverEntryPointQueryResult qr;
        cudaGetDriverEntryPoint("cuTensorMapEncodeTiled", (void**)&enc, cudaEnableDefault, &qr);
        cudaGetSymbolAddress(&p_h, g_h);
        cudaGetSymbolAddress(&p_o, g_o);
        cudaFuncSetAttribute(k_fused, cudaFuncAttributeMaxDynamicSharedMemorySize, SM_TOTAL);
    }
    Maps tm;
    tm.x = make_map(enc, x, SEQ, DM, 128, 64, CU_TENSOR_MAP_SWIZZLE_128B);
    tm.wqkv = make_map(enc, wqkv, DM, 3 * DM, 32, 64, CU_TENSOR_MAP_SWIZZLE_128B);
    tm.w1 = make_map(enc, w1, DM, FF, 32, 64, CU_TENSOR_MAP_SWIZZLE_128B);
    tm.h = make_map(enc, p_h, SEQ, FF, 64, 64, CU_TENSOR_MAP_SWIZZLE_128B);
    tm.o = make_map(enc, p_o, SEQ, DM, 64, 64, CU_TENSOR_MAP_SWIZZLE_128B);
    tm.wo = make_map(enc, wo, DM, DM, 64, 32, CU_TENSOR_MAP_SWIZZLE_64B);
    tm.w2 = make_map(enc, w2, FF, DM, 64, 32, CU_TENSOR_MAP_SWIZZLE_64B);
    k_fused<<<128, 512, SM_TOTAL, cudaStreamPerThread>>>(tm, x, (const uint8_t*)wqkv, (const uint8_t*)w1, (const uint8_t*)w2,
                                                         (const uint8_t*)wo, b1, b2, out);
}
```

```cpp
#include <cuda_runtime.h>
#include <cuda_bf16.h>
#include <cuda.h>
#include <stdint.h>

namespace {

constexpr int SEQ = 2048, DM = 640, FF = 1536;
constexpr float LN_EPS = 1e-5f;

constexpr int IMG_BYTES = 256 * 384;
constexpr uint32_t EMU_MASK = 0xD5D5u;
constexpr float SAFE_BOUND = 80.0f;
#define XV_IT 1
#define PACE_NS 200
constexpr float QSCALE = 0.22360679774997896f * 1.4426950408889634f;

__device__ float4 g_stat[SEQ];
__device__ float2 g_csp[16 * 1728];
__device__ __align__(1024) uint8_t g_img[96 * IMG_BYTES + 1024];
__device__ float g_nrm[64 * SEQ];
__device__ __align__(1024) __nv_bfloat16 g_h[SEQ * FF];
__device__ __align__(1024) __nv_bfloat16 g_o[SEQ * DM];
constexpr int CNT_ST = 0, CNT_QKV = 16, CNT_H = 24, CNT_O = 40, CNT_CS = 44, CNT_CS2 = 52;
__device__ uint32_t g_cnt[60 * 32];
__device__ uint32_t g_epoch;

#define TL(kern, slot) do { } while (0)
#define IT(row, i) do { } while (0)

__device__ __forceinline__ uint32_t smem_u32(const void* p) { return (uint32_t)__cvta_generic_to_shared(p); }
__device__ __forceinline__ void mbar_init(uint32_t bar, int cnt) {
    asm volatile("mbarrier.init.shared::cta.b64 [%0], %1;" ::"r"(bar), "r"(cnt));
}
__device__ __forceinline__ void mbar_expect_tx(uint32_t bar, uint32_t bytes) {
    asm volatile("mbarrier.arrive.expect_tx.shared::cta.b64 _, [%0], %1;" ::"r"(bar), "r"(bytes) : "memory");
}
__device__ __forceinline__ void mbar_wait(uint32_t bar, uint32_t parity) {
    asm volatile("{\n.reg .pred p;\n.reg .u32 n;\nmov.u32 n, 0;\n"
                 "WAIT_LOOP:\nmbarrier.try_wait.parity.shared::cta.b64 p, [%0], %1;\n@p bra WAIT_DONE;\n"
                 "add.u32 n, n, 1;\nsetp.lt.u32 p, n, 4194304;\n@p bra WAIT_LOOP;\nWAIT_DONE:\n}"
                 ::"r"(bar), "r"(parity) : "memory");
}
__device__ __forceinline__ void mbar_arrive(uint32_t bar) {
    asm volatile("mbarrier.arrive.shared::cta.b64 _, [%0];" ::"r"(bar) : "memory");
}
__device__ __forceinline__ void mbar_arrive_cluster(uint32_t bar, uint32_t cta) {
    asm volatile("{\n.reg .b32 ra;\nmapa.shared::cluster.u32 ra, %0, %1;\n"
                 "mbarrier.arrive.shared::cluster.b64 _, [ra];\n}" ::"r"(bar), "r"(cta) : "memory");
}
__device__ __forceinline__ void fence_barrier_init() { asm volatile("fence.mbarrier_init.release.cluster;" ::: "memory"); }
__device__ __forceinline__ void fence_proxy_async() { asm volatile("fence.proxy.async.shared::cta;" ::: "memory"); }
__device__ __forceinline__ void cluster_sync() {
    asm volatile("barrier.cluster.arrive.release.aligned;\nbarrier.cluster.wait.acquire.aligned;" ::: "memory");
}
__device__ __forceinline__ bool elect_one() {
    uint32_t pred;
    asm volatile("{\n.reg .pred p;\nelect.sync _|p, 0xFFFFFFFF;\nselp.b32 %0, 1, 0, p;\n}" : "=r"(pred));
    return pred != 0;
}
__device__ __forceinline__ void pdl_launch() { asm volatile("griddepcontrol.launch_dependents;" ::: "memory"); }
__device__ __forceinline__ void pdl_wait() { asm volatile("griddepcontrol.wait;" ::: "memory"); }
__device__ __forceinline__ void prefetch_map(const CUtensorMap* m) {
    asm volatile("prefetch.tensormap [%0];" ::"l"(m) : "memory");
}
__device__ __forceinline__ void tma_load(uint32_t dst, const CUtensorMap* m, int c0, int c1, uint32_t bar) {
    asm volatile("cp.async.bulk.tensor.2d.shared::cluster.global.mbarrier::complete_tx::bytes [%0], [%1, {%3, %4}], [%2];"
                 ::"r"(dst), "l"(m), "r"(bar), "r"(c0), "r"(c1) : "memory");
}
__device__ __forceinline__ void tma_load_mc(uint32_t dst, const CUtensorMap* m, int c0, int c1, uint32_t bar, uint16_t mask) {
    asm volatile("cp.async.bulk.tensor.2d.shared::cluster.global.mbarrier::complete_tx::bytes.multicast::cluster"
                 " [%0], [%1, {%3, %4}], [%2], %5;"
                 ::"r"(dst), "l"(m), "r"(bar), "r"(c0), "r"(c1), "h"(mask) : "memory");
}
__device__ __forceinline__ void tma_store(const CUtensorMap* m, uint32_t src, int c0, int c1) {
    asm volatile("cp.async.bulk.tensor.2d.global.shared::cta.bulk_group [%0, {%2, %3}], [%1];"
                 ::"l"(m), "r"(src), "r"(c0), "r"(c1) : "memory");
}
__device__ __forceinline__ void bulk_commit() { asm volatile("cp.async.bulk.commit_group;" ::: "memory"); }
__device__ __forceinline__ void bulk_wait_all() { asm volatile("cp.async.bulk.wait_group 0;" ::: "memory"); }
__device__ __forceinline__ void bulk_load(uint32_t dst, const void* src, uint32_t bytes, uint32_t bar) {
    asm volatile("cp.async.bulk.shared::cluster.global.mbarrier::complete_tx::bytes [%0], [%1], %2, [%3];"
                 ::"r"(dst), "l"(src), "r"(bytes), "r"(bar) : "memory");
}
__device__ __forceinline__ void prefetch_l2(const void* p, uint32_t bytes) {
    asm volatile("cp.async.bulk.prefetch.L2.global [%0], %1;" ::"l"(p), "r"(bytes) : "memory");
}
__device__ __forceinline__ void tma_prefetch_l2(const CUtensorMap* m, int c0, int c1) {
    asm volatile("cp.async.bulk.prefetch.tensor.2d.L2.global.tile [%0, {%1, %2}];" ::"l"(m), "r"(c0), "r"(c1) : "memory");
}
__device__ __forceinline__ void wg_fence() { asm volatile("wgmma.fence.sync.aligned;" ::: "memory"); }
__device__ __forceinline__ void wg_commit() { asm volatile("wgmma.commit_group.sync.aligned;" ::: "memory"); }
template <int N> __device__ __forceinline__ void wg_wait() {
    asm volatile("wgmma.wait_group.sync.aligned %0;" ::"n"(N) : "memory");
}
template <int N> __device__ __forceinline__ void reg_alloc() { asm volatile("setmaxnreg.inc.sync.aligned.u32 %0;" ::"n"(N)); }
template <int N> __device__ __forceinline__ void reg_dealloc() { asm volatile("setmaxnreg.dec.sync.aligned.u32 %0;" ::"n"(N)); }
template <int N> __device__ __forceinline__ void fence_regs(float (&d)[N]) {
#pragma unroll
    for (int i = 0; i < N; i++) asm volatile("" : "+f"(d[i])::"memory");
}
__device__ __forceinline__ uint64_t make_desc(uint32_t addr, uint32_t lbo, uint32_t sbo, uint32_t swz) {
    return (uint64_t)((addr & 0x3FFFF) >> 4) | ((uint64_t)(lbo >> 4) << 16) | ((uint64_t)(sbo >> 4) << 32) |
           ((uint64_t)swz << 62);
}
__device__ __forceinline__ uint32_t pack_bf16(float lo, float hi) {
    uint32_t r;
    asm("cvt.rn.bf16x2.f32 %0, %1, %2;" : "=r"(r) : "f"(hi), "f"(lo));
    return r;
}
__device__ __forceinline__ float ex2(float x) {
    float r;
    asm("ex2.approx.ftz.f32 %0, %1;" : "=f"(r) : "f"(x));
    return r;
}
__device__ __forceinline__ float bf_lo(uint32_t v) { return __uint_as_float(v << 16); }
__device__ __forceinline__ float bf_hi(uint32_t v) { return __uint_as_float(v & 0xFFFF0000u); }
__device__ __forceinline__ void stmatrix_x4(uint32_t addr, uint32_t r0, uint32_t r1, uint32_t r2, uint32_t r3) {
    asm volatile("stmatrix.sync.aligned.m8n8.x4.shared.b16 [%0], {%1, %2, %3, %4};"
                 ::"r"(addr), "r"(r0), "r"(r1), "r"(r2), "r"(r3) : "memory");
}

__device__ __forceinline__ void wgmma_n200_ss_tb(float (&d)[100], uint64_t descA, uint64_t descB, int scaleD) {
    asm volatile("{\n.reg .pred p;\nsetp.ne.b32 p, %102, 0;\n"
        "wgmma.mma_async.sync.aligned.m64n200k16.f32.bf16.bf16 {"
        "%0, %1, %2, %3, %4, %5, %6, %7, %8, %9, %10, %11, %12, %13, %14, %15, "
        "%16, %17, %18, %19, %20, %21, %22, %23, %24, %25, %26, %27, %28, %29, %30, %31, "
        "%32, %33, %34, %35, %36, %37, %38, %39, %40, %41, %42, %43, %44, %45, %46, %47, "
        "%48, %49, %50, %51, %52, %53, %54, %55, %56, %57, %58, %59, %60, %61, %62, %63, "
        "%64, %65, %66, %67, %68, %69, %70, %71, %72, %73, %74, %75, %76, %77, %78, %79, "
        "%80, %81, %82, %83, %84, %85, %86, %87, %88, %89, %90, %91, %92, %93, %94, %95, "
        "%96, %97, %98, %99}, "
        "%100, %101, p, 1, 1, 0, 1;\n}\n"
        : "+f"(d[0]), "+f"(d[1]), "+f"(d[2]), "+f"(d[3]), "+f"(d[4]), "+f"(d[5]), "+f"(d[6]), "+f"(d[7]),
          "+f"(d[8]), "+f"(d[9]), "+f"(d[10]), "+f"(d[11]), "+f"(d[12]), "+f"(d[13]), "+f"(d[14]), "+f"(d[15]),
          "+f"(d[16]), "+f"(d[17]), "+f"(d[18]), "+f"(d[19]), "+f"(d[20]), "+f"(d[21]), "+f"(d[22]), "+f"(d[23]),
          "+f"(d[24]), "+f"(d[25]), "+f"(d[26]), "+f"(d[27]), "+f"(d[28]), "+f"(d[29]), "+f"(d[30]), "+f"(d[31]),
          "+f"(d[32]), "+f"(d[33]), "+f"(d[34]), "+f"(d[35]), "+f"(d[36]), "+f"(d[37]), "+f"(d[38]), "+f"(d[39]),
          "+f"(d[40]), "+f"(d[41]), "+f"(d[42]), "+f"(d[43]), "+f"(d[44]), "+f"(d[45]), "+f"(d[46]), "+f"(d[47]),
          "+f"(d[48]), "+f"(d[49]), "+f"(d[50]), "+f"(d[51]), "+f"(d[52]), "+f"(d[53]), "+f"(d[54]), "+f"(d[55]),
          "+f"(d[56]), "+f"(d[57]), "+f"(d[58]), "+f"(d[59]), "+f"(d[60]), "+f"(d[61]), "+f"(d[62]), "+f"(d[63]),
          "+f"(d[64]), "+f"(d[65]), "+f"(d[66]), "+f"(d[67]), "+f"(d[68]), "+f"(d[69]), "+f"(d[70]), "+f"(d[71]),
          "+f"(d[72]), "+f"(d[73]), "+f"(d[74]), "+f"(d[75]), "+f"(d[76]), "+f"(d[77]), "+f"(d[78]), "+f"(d[79]),
          "+f"(d[80]), "+f"(d[81]), "+f"(d[82]), "+f"(d[83]), "+f"(d[84]), "+f"(d[85]), "+f"(d[86]), "+f"(d[87]),
          "+f"(d[88]), "+f"(d[89]), "+f"(d[90]), "+f"(d[91]), "+f"(d[92]), "+f"(d[93]), "+f"(d[94]), "+f"(d[95]),
          "+f"(d[96]), "+f"(d[97]), "+f"(d[98]), "+f"(d[99])
        : "l"(descA), "l"(descB), "r"(scaleD));
}

__device__ __forceinline__ void wgmma_n40_ss_tb(float (&d)[20], uint64_t descA, uint64_t descB, int scaleD) {
    asm volatile("{\n.reg .pred p;\nsetp.ne.b32 p, %22, 0;\n"
        "wgmma.mma_async.sync.aligned.m64n40k16.f32.bf16.bf16 {"
        "%0, %1, %2, %3, %4, %5, %6, %7, %8, %9, %10, %11, %12, %13, %14, %15, "
        "%16, %17, %18, %19}, "
        "%20, %21, p, 1, 1, 0, 1;\n}\n"
        : "+f"(d[0]), "+f"(d[1]), "+f"(d[2]), "+f"(d[3]), "+f"(d[4]), "+f"(d[5]), "+f"(d[6]), "+f"(d[7]),
          "+f"(d[8]), "+f"(d[9]), "+f"(d[10]), "+f"(d[11]), "+f"(d[12]), "+f"(d[13]), "+f"(d[14]), "+f"(d[15]),
          "+f"(d[16]), "+f"(d[17]), "+f"(d[18]), "+f"(d[19])
        : "l"(descA), "l"(descB), "r"(scaleD));
}

__device__ __forceinline__ void wgmma_n192_ss_tb(float (&d)[96], uint64_t descA, uint64_t descB, int scaleD) {
    asm volatile("{\n.reg .pred p;\nsetp.ne.b32 p, %98, 0;\n"
        "wgmma.mma_async.sync.aligned.m64n192k16.f32.bf16.bf16 {"
        "%0, %1, %2, %3, %4, %5, %6, %7, %8, %9, %10, %11, %12, %13, %14, %15, "
        "%16, %17, %18, %19, %20, %21, %22, %23, %24, %25, %26, %27, %28, %29, %30, %31, "
        "%32, %33, %34, %35, %36, %37, %38, %39, %40, %41, %42, %43, %44, %45, %46, %47, "
        "%48, %49, %50, %51, %52, %53, %54, %55, %56, %57, %58, %59, %60, %61, %62, %63, "
        "%64, %65, %66, %67, %68, %69, %70, %71, %72, %73, %74, %75, %76, %77, %78, %79, "
        "%80, %81, %82, %83, %84, %85, %86, %87, %88, %89, %90, %91, %92, %93, %94, %95}, "
        "%96, %97, p, 1, 1, 0, 1;\n}\n"
        : "+f"(d[0]), "+f"(d[1]), "+f"(d[2]), "+f"(d[3]), "+f"(d[4]), "+f"(d[5]), "+f"(d[6]), "+f"(d[7]),
          "+f"(d[8]), "+f"(d[9]), "+f"(d[10]), "+f"(d[11]), "+f"(d[12]), "+f"(d[13]), "+f"(d[14]), "+f"(d[15]),
          "+f"(d[16]), "+f"(d[17]), "+f"(d[18]), "+f"(d[19]), "+f"(d[20]), "+f"(d[21]), "+f"(d[22]), "+f"(d[23]),
          "+f"(d[24]), "+f"(d[25]), "+f"(d[26]), "+f"(d[27]), "+f"(d[28]), "+f"(d[29]), "+f"(d[30]), "+f"(d[31]),
          "+f"(d[32]), "+f"(d[33]), "+f"(d[34]), "+f"(d[35]), "+f"(d[36]), "+f"(d[37]), "+f"(d[38]), "+f"(d[39]),
          "+f"(d[40]), "+f"(d[41]), "+f"(d[42]), "+f"(d[43]), "+f"(d[44]), "+f"(d[45]), "+f"(d[46]), "+f"(d[47]),
          "+f"(d[48]), "+f"(d[49]), "+f"(d[50]), "+f"(d[51]), "+f"(d[52]), "+f"(d[53]), "+f"(d[54]), "+f"(d[55]),
          "+f"(d[56]), "+f"(d[57]), "+f"(d[58]), "+f"(d[59]), "+f"(d[60]), "+f"(d[61]), "+f"(d[62]), "+f"(d[63]),
          "+f"(d[64]), "+f"(d[65]), "+f"(d[66]), "+f"(d[67]), "+f"(d[68]), "+f"(d[69]), "+f"(d[70]), "+f"(d[71]),
          "+f"(d[72]), "+f"(d[73]), "+f"(d[74]), "+f"(d[75]), "+f"(d[76]), "+f"(d[77]), "+f"(d[78]), "+f"(d[79]),
          "+f"(d[80]), "+f"(d[81]), "+f"(d[82]), "+f"(d[83]), "+f"(d[84]), "+f"(d[85]), "+f"(d[86]), "+f"(d[87]),
          "+f"(d[88]), "+f"(d[89]), "+f"(d[90]), "+f"(d[91]), "+f"(d[92]), "+f"(d[93]), "+f"(d[94]), "+f"(d[95])
        : "l"(descA), "l"(descB), "r"(scaleD));
}

__device__ __forceinline__ void wgmma_n192_ss_tb_z(float (&d)[96], uint64_t descA, uint64_t descB) {
    asm volatile("{\n.reg .pred p;\nsetp.ne.b32 p, 0, 0;\n"
        "wgmma.mma_async.sync.aligned.m64n192k16.f32.bf16.bf16 {"
        "%0, %1, %2, %3, %4, %5, %6, %7, %8, %9, %10, %11, %12, %13, %14, %15, "
        "%16, %17, %18, %19, %20, %21, %22, %23, %24, %25, %26, %27, %28, %29, %30, %31, "
        "%32, %33, %34, %35, %36, %37, %38, %39, %40, %41, %42, %43, %44, %45, %46, %47, "
        "%48, %49, %50, %51, %52, %53, %54, %55, %56, %57, %58, %59, %60, %61, %62, %63, "
        "%64, %65, %66, %67, %68, %69, %70, %71, %72, %73, %74, %75, %76, %77, %78, %79, "
        "%80, %81, %82, %83, %84, %85, %86, %87, %88, %89, %90, %91, %92, %93, %94, %95}, "
        "%96, %97, p, 1, 1, 0, 1;\n}\n"
        : "=f"(d[0]), "=f"(d[1]), "=f"(d[2]), "=f"(d[3]), "=f"(d[4]), "=f"(d[5]), "=f"(d[6]), "=f"(d[7]),
          "=f"(d[8]), "=f"(d[9]), "=f"(d[10]), "=f"(d[11]), "=f"(d[12]), "=f"(d[13]), "=f"(d[14]), "=f"(d[15]),
          "=f"(d[16]), "=f"(d[17]), "=f"(d[18]), "=f"(d[19]), "=f"(d[20]), "=f"(d[21]), "=f"(d[22]), "=f"(d[23]),
          "=f"(d[24]), "=f"(d[25]), "=f"(d[26]), "=f"(d[27]), "=f"(d[28]), "=f"(d[29]), "=f"(d[30]), "=f"(d[31]),
          "=f"(d[32]), "=f"(d[33]), "=f"(d[34]), "=f"(d[35]), "=f"(d[36]), "=f"(d[37]), "=f"(d[38]), "=f"(d[39]),
          "=f"(d[40]), "=f"(d[41]), "=f"(d[42]), "=f"(d[43]), "=f"(d[44]), "=f"(d[45]), "=f"(d[46]), "=f"(d[47]),
          "=f"(d[48]), "=f"(d[49]), "=f"(d[50]), "=f"(d[51]), "=f"(d[52]), "=f"(d[53]), "=f"(d[54]), "=f"(d[55]),
          "=f"(d[56]), "=f"(d[57]), "=f"(d[58]), "=f"(d[59]), "=f"(d[60]), "=f"(d[61]), "=f"(d[62]), "=f"(d[63]),
          "=f"(d[64]), "=f"(d[65]), "=f"(d[66]), "=f"(d[67]), "=f"(d[68]), "=f"(d[69]), "=f"(d[70]), "=f"(d[71]),
          "=f"(d[72]), "=f"(d[73]), "=f"(d[74]), "=f"(d[75]), "=f"(d[76]), "=f"(d[77]), "=f"(d[78]), "=f"(d[79]),
          "=f"(d[80]), "=f"(d[81]), "=f"(d[82]), "=f"(d[83]), "=f"(d[84]), "=f"(d[85]), "=f"(d[86]), "=f"(d[87]),
          "=f"(d[88]), "=f"(d[89]), "=f"(d[90]), "=f"(d[91]), "=f"(d[92]), "=f"(d[93]), "=f"(d[94]), "=f"(d[95])
        : "l"(descA), "l"(descB));
}

__device__ __forceinline__ void wgmma_n160_ss_tb(float (&d)[80], uint64_t descA, uint64_t descB, int scaleD) {
    asm volatile("{\n.reg .pred p;\nsetp.ne.b32 p, %82, 0;\n"
        "wgmma.mma_async.sync.aligned.m64n160k16.f32.bf16.bf16 {"
        "%0, %1, %2, %3, %4, %5, %6, %7, %8, %9, %10, %11, %12, %13, %14, %15, "
        "%16, %17, %18, %19, %20, %21, %22, %23, %24, %25, %26, %27, %28, %29, %30, %31, "
        "%32, %33, %34, %35, %36, %37, %38, %39, %40, %41, %42, %43, %44, %45, %46, %47, "
        "%48, %49, %50, %51, %52, %53, %54, %55, %56, %57, %58, %59, %60, %61, %62, %63, "
        "%64, %65, %66, %67, %68, %69, %70, %71, %72, %73, %74, %75, %76, %77, %78, %79}, "
        "%80, %81, p, 1, 1, 0, 1;\n}\n"
        : "+f"(d[0]), "+f"(d[1]), "+f"(d[2]), "+f"(d[3]), "+f"(d[4]), "+f"(d[5]), "+f"(d[6]), "+f"(d[7]),
          "+f"(d[8]), "+f"(d[9]), "+f"(d[10]), "+f"(d[11]), "+f"(d[12]), "+f"(d[13]), "+f"(d[14]), "+f"(d[15]),
          "+f"(d[16]), "+f"(d[17]), "+f"(d[18]), "+f"(d[19]), "+f"(d[20]), "+f"(d[21]), "+f"(d[22]), "+f"(d[23]),
          "+f"(d[24]), "+f"(d[25]), "+f"(d[26]), "+f"(d[27]), "+f"(d[28]), "+f"(d[29]), "+f"(d[30]), "+f"(d[31]),
          "+f"(d[32]), "+f"(d[33]), "+f"(d[34]), "+f"(d[35]), "+f"(d[36]), "+f"(d[37]), "+f"(d[38]), "+f"(d[39]),
          "+f"(d[40]), "+f"(d[41]), "+f"(d[42]), "+f"(d[43]), "+f"(d[44]), "+f"(d[45]), "+f"(d[46]), "+f"(d[47]),
          "+f"(d[48]), "+f"(d[49]), "+f"(d[50]), "+f"(d[51]), "+f"(d[52]), "+f"(d[53]), "+f"(d[54]), "+f"(d[55]),
          "+f"(d[56]), "+f"(d[57]), "+f"(d[58]), "+f"(d[59]), "+f"(d[60]), "+f"(d[61]), "+f"(d[62]), "+f"(d[63]),
          "+f"(d[64]), "+f"(d[65]), "+f"(d[66]), "+f"(d[67]), "+f"(d[68]), "+f"(d[69]), "+f"(d[70]), "+f"(d[71]),
          "+f"(d[72]), "+f"(d[73]), "+f"(d[74]), "+f"(d[75]), "+f"(d[76]), "+f"(d[77]), "+f"(d[78]), "+f"(d[79])
        : "l"(descA), "l"(descB), "r"(scaleD));
}

__device__ __forceinline__ void wgmma_n64_ss(float (&d)[32], uint64_t descA, uint64_t descB, int scaleD) {
    asm volatile("{\n.reg .pred p;\nsetp.ne.b32 p, %34, 0;\n"
        "wgmma.mma_async.sync.aligned.m64n64k16.f32.bf16.bf16 {"
        "%0, %1, %2, %3, %4, %5, %6, %7, %8, %9, %10, %11, %12, %13, %14, %15, "
        "%16, %17, %18, %19, %20, %21, %22, %23, %24, %25, %26, %27, %28, %29, %30, %31}, "
        "%32, %33, p, 1, 1, 0, 0;\n}\n"
        : "+f"(d[0]), "+f"(d[1]), "+f"(d[2]), "+f"(d[3]), "+f"(d[4]), "+f"(d[5]), "+f"(d[6]), "+f"(d[7]),
          "+f"(d[8]), "+f"(d[9]), "+f"(d[10]), "+f"(d[11]), "+f"(d[12]), "+f"(d[13]), "+f"(d[14]), "+f"(d[15]),
          "+f"(d[16]), "+f"(d[17]), "+f"(d[18]), "+f"(d[19]), "+f"(d[20]), "+f"(d[21]), "+f"(d[22]), "+f"(d[23]),
          "+f"(d[24]), "+f"(d[25]), "+f"(d[26]), "+f"(d[27]), "+f"(d[28]), "+f"(d[29]), "+f"(d[30]), "+f"(d[31])
        : "l"(descA), "l"(descB), "r"(scaleD));
}

__device__ __forceinline__ void wgmma_n64_ss_z(float (&d)[32], uint64_t descA, uint64_t descB) {
    asm volatile("{\n.reg .pred p;\nsetp.ne.b32 p, 0, 0;\n"
        "wgmma.mma_async.sync.aligned.m64n64k16.f32.bf16.bf16 {"
        "%0, %1, %2, %3, %4, %5, %6, %7, %8, %9, %10, %11, %12, %13, %14, %15, "
        "%16, %17, %18, %19, %20, %21, %22, %23, %24, %25, %26, %27, %28, %29, %30, %31}, "
        "%32, %33, p, 1, 1, 0, 0;\n}\n"
        : "=f"(d[0]), "=f"(d[1]), "=f"(d[2]), "=f"(d[3]), "=f"(d[4]), "=f"(d[5]), "=f"(d[6]), "=f"(d[7]),
          "=f"(d[8]), "=f"(d[9]), "=f"(d[10]), "=f"(d[11]), "=f"(d[12]), "=f"(d[13]), "=f"(d[14]), "=f"(d[15]),
          "=f"(d[16]), "=f"(d[17]), "=f"(d[18]), "=f"(d[19]), "=f"(d[20]), "=f"(d[21]), "=f"(d[22]), "=f"(d[23]),
          "=f"(d[24]), "=f"(d[25]), "=f"(d[26]), "=f"(d[27]), "=f"(d[28]), "=f"(d[29]), "=f"(d[30]), "=f"(d[31])
        : "l"(descA), "l"(descB));
}

__device__ __forceinline__ void wgmma_n24_rs_tb(float (&d)[12], uint32_t a0, uint32_t a1, uint32_t a2, uint32_t a3, uint64_t descB, int scaleD) {
    asm volatile("{\n.reg .pred p;\nsetp.ne.b32 p, %17, 0;\n"
        "wgmma.mma_async.sync.aligned.m64n24k16.f32.bf16.bf16 {"
        "%0, %1, %2, %3, %4, %5, %6, %7, %8, %9, %10, %11}, "
        "{%12, %13, %14, %15}, %16, p, 1, 1, 1;\n}\n"
        : "+f"(d[0]), "+f"(d[1]), "+f"(d[2]), "+f"(d[3]), "+f"(d[4]), "+f"(d[5]), "+f"(d[6]), "+f"(d[7]),
          "+f"(d[8]), "+f"(d[9]), "+f"(d[10]), "+f"(d[11])
        : "r"(a0), "r"(a1), "r"(a2), "r"(a3), "l"(descB), "r"(scaleD));
}

__device__ __forceinline__ void cnt_signal(int idx) {
    asm volatile("fence.acq_rel.gpu;\nred.relaxed.gpu.global.add.u32 [%0], 1;"
                 ::"l"(g_cnt + idx * 32) : "memory");
}
__device__ __forceinline__ void cnt_wait(int idx, uint32_t target) {
    const uint32_t* p = g_cnt + idx * 32;
#pragma unroll 1
    for (uint32_t i = 0; i < (1u << 22); i++) {
        uint32_t v;
        asm volatile("ld.acquire.gpu.global.u32 %0, [%1];" : "=r"(v) : "l"(p) : "memory");
        if ((int32_t)(v - target) >= 0) break;
    }
    asm volatile("fence.proxy.async.global;" ::: "memory");
}
__device__ __forceinline__ void cluster_arrive() { asm volatile("barrier.cluster.arrive.release.aligned;" ::: "memory"); }
__device__ __forceinline__ void cluster_arrive_relaxed() { asm volatile("barrier.cluster.arrive.relaxed.aligned;" ::: "memory"); }
__device__ __forceinline__ void cluster_wait() { asm volatile("barrier.cluster.wait.acquire.aligned;" ::: "memory"); }
__device__ __forceinline__ void bulk_wait_read() { asm volatile("cp.async.bulk.wait_group.read 0;" ::: "memory"); }

__device__ __forceinline__ float gelu_tanh(float x) {
    const float u = x * (0.7978845608028654f + 0.035677408136300125f * x * x);
    float t;
    asm("tanh.approx.f32 %0, %1;" : "=f"(t) : "f"(u));
    const float h = 0.5f * x;
    return fmaf(h, t, h);
}
__device__ __forceinline__ void release_stage(uint32_t bar, uint32_t peer, int lane) {
    if (lane == 0) { mbar_arrive(bar); mbar_arrive_cluster(bar, peer); }
}

constexpr int SM_RING = 163840;
constexpr int SM_Q = 0, SM_ZERO = 24576, SM_K = SM_ZERO + 3072, SM_V = SM_K + IMG_BYTES;
constexpr int G2_STAGE = 8192 + 20480;
constexpr int SM_MISC = 229376;
constexpr int SM_BIAS = SM_MISC, SM_RED = SM_BIAS + 384, SM_BAR = SM_RED + 128;
constexpr int B_A = 0, B_F1 = 10, B_E1 = 14, B_F2 = 18, B_E2 = 23, B_KV = 28, B_Q = 45, B_F3 = 47, B_E3 = 55, B_ST = 63, B_STAT = 65, B_AUX = 66, B_AUX2 = 67, B_DEAD = 68, B_COUNT = 70;
constexpr int SM_EPOCH = SM_BAR + 560, SM_SAFE = SM_EPOCH + 4;
constexpr int SM_CS = SM_EPOCH + 16;
constexpr int SM_TOTAL = SM_CS + 1728;
static_assert(SM_TOTAL <= 232448, "shared memory budget");

struct Maps { CUtensorMap x, wqkv, w1, h, o, wo, w2; };

__device__ __forceinline__ uint32_t bf2_fma(uint32_t a, uint32_t b, uint32_t c) {
    uint32_t r;
    asm("fma.rn.bf16x2 %0, %1, %2, %3;" : "=r"(r) : "r"(a), "r"(b), "r"(c));
    return r;
}
__device__ __forceinline__ uint32_t lop_and_or(uint32_t a, uint32_t m, uint32_t o) {
    uint32_t r;
    asm("lop3.b32 %0, %1, %2, %3, 0xEA;" : "=r"(r) : "r"(a), "r"(m), "r"(o));
    return r;
}
struct ExpConst { uint32_t mask, slope; };
__device__ __forceinline__ ExpConst make_exp_const() {
    ExpConst k;
    asm volatile("mov.b32 %0, 0x007F007F;" : "=r"(k.mask));
    asm volatile("mov.b32 %0, 0x3EF83EF8;" : "=r"(k.slope));
    return k;
}
__device__ __forceinline__ uint32_t exp2_pair_fma(float t0, float t1, const ExpConst& k) {
    const uint32_t L = __byte_perm(__float_as_uint(t0), __float_as_uint(t1), 0x6521);
    const uint32_t g = lop_and_or(L, k.mask, 0x3F803F80u);
    const uint32_t u = bf2_fma(g, k.slope, 0xBF37BF37u);
    const uint32_t e = bf2_fma(u, u, 0xBD71BD71u);
    return bf2_fma(L, e, L);
}
template <int SHIFT>
__device__ __forceinline__ void exp_tile(const float (&s)[32], uint32_t (&p)[16], const ExpConst& k) {
#pragma unroll
    for (int b = 0; b < 8; b++) {
        if ((EMU_MASK >> (b + SHIFT)) & 1) {
            p[2 * b] = exp2_pair_fma(s[4 * b], s[4 * b + 1], k);
            p[2 * b + 1] = exp2_pair_fma(s[4 * b + 2], s[4 * b + 3], k);
        } else {
            p[2 * b] = pack_bf16(ex2(s[4 * b]), ex2(s[4 * b + 1]));
            p[2 * b + 1] = pack_bf16(ex2(s[4 * b + 2]), ex2(s[4 * b + 3]));
        }
    }
}

__device__ __forceinline__ void qk_tile(float (&s)[32], uint64_t dQ, uint64_t dQ2, uint64_t dK) {
    wg_fence();
    wgmma_n64_ss_z(s, dQ, dK);
    wgmma_n64_ss(s, dQ2, dK + 16, 1);
    wg_commit();
}
__device__ __forceinline__ void pv_tile(float (&o)[12], const uint32_t (&p)[16], uint64_t dV) {
    wg_fence();
#pragma unroll
    for (int ks = 0; ks < 4; ks++)
        wgmma_n24_rs_tb(o, p[4 * ks], p[4 * ks + 1], p[4 * ks + 2], p[4 * ks + 3], dV + ks * 48, 1);
    wg_commit();
}
__device__ __forceinline__ void store_o(const float (&o)[12], int h, int rbase, int lane) {
    const int g = lane >> 2, c = lane & 3;
    const bool odd = h & 1;
    const int lsrc = (lane & ~3) | (odd ? 0 : 2);
    const float i0 = 1.f / __shfl_sync(~0u, o[8], lsrc), i1 = 1.f / __shfl_sync(~0u, o[10], lsrc);
    __nv_bfloat16* dst = g_o + (size_t)(rbase + g) * DM + h * 20;
    const int d0 = (odd ? 4 : 0) + 2 * c, d1 = d0 + 8, d2 = odd ? 2 * c - 4 : 16 + 2 * c;
    *(uint32_t*)(dst + d0) = pack_bf16(o[0] * i0, o[1] * i0);
    *(uint32_t*)(dst + d1) = pack_bf16(o[4] * i0, o[5] * i0);
    *(uint32_t*)(dst + 8 * DM + d0) = pack_bf16(o[2] * i1, o[3] * i1);
    *(uint32_t*)(dst + 8 * DM + d1) = pack_bf16(o[6] * i1, o[7] * i1);
    if (odd ? (c >= 2) : (c < 2)) {
        *(uint32_t*)(dst + d2) = pack_bf16(o[8] * i0, o[9] * i0);
        *(uint32_t*)(dst + 8 * DM + d2) = pack_bf16(o[10] * i1, o[11] * i1);
    }
}

__device__ __forceinline__ void attn_rows_maxshift(uint32_t sK, uint32_t barKV, uint64_t dQ, uint64_t dQ2, int h, int rbase) {
    const int lane = threadIdx.x & 31;
    const uint64_t dK0 = make_desc(sK, 128, 384, 0), dV0 = make_desc(sK + IMG_BYTES, 384, 128, 0);
    float o[12], s[32];
    uint32_t p[16];
#pragma unroll
    for (int i = 0; i < 12; i++) o[i] = 0.f;
    float m0 = -3.0e38f, m1 = -3.0e38f;
    mbar_wait(barKV + 128, 0);
#pragma unroll 1
    for (int t = 0; t < 32; t++) {
        mbar_wait(barKV + (t >> 1) * 8, 0);
        qk_tile(s, dQ, dQ2, dK0 + t * 192);
        wg_wait<0>();
        fence_regs(s);
        const uint32_t mask = EMU_MASK >> ((t & 1) * 8);
        float n0 = m0, n1 = m1;
#pragma unroll
        for (int b = 0; b < 8; b++) {
            const bool emu = (mask >> b) & 1;
            const float f = emu ? 0.5f : 1.f, off = emu ? -383.00390625f : 0.f;
#pragma unroll
            for (int i = 0; i < 4; i++) s[4 * b + i] = fmaf(s[4 * b + i], f, off);
            n0 = fmaxf(n0, fmaxf(s[4 * b], s[4 * b + 1]));
            n1 = fmaxf(n1, fmaxf(s[4 * b + 2], s[4 * b + 3]));
        }
        n0 = fmaxf(n0, __shfl_xor_sync(~0u, n0, 1)); n0 = fmaxf(n0, __shfl_xor_sync(~0u, n0, 2));
        n1 = fmaxf(n1, __shfl_xor_sync(~0u, n1, 1)); n1 = fmaxf(n1, __shfl_xor_sync(~0u, n1, 2));
        const float c0 = ex2(m0 - n0), c1 = ex2(m1 - n1);
        m0 = n0; m1 = n1;
#pragma unroll
        for (int b = 0; b < 3; b++) { o[4 * b] *= c0; o[4 * b + 1] *= c0; o[4 * b + 2] *= c1; o[4 * b + 3] *= c1; }
#pragma unroll
        for (int b = 0; b < 8; b++) {
            p[2 * b] = pack_bf16(ex2(s[4 * b] - m0), ex2(s[4 * b + 1] - m0));
            p[2 * b + 1] = pack_bf16(ex2(s[4 * b + 2] - m1), ex2(s[4 * b + 3] - m1));
        }
        pv_tile(o, p, dV0 + (((t >> 1) + 7) & 15) * 384 + (t & 1) * 192);
        wg_wait<0>();
        fence_regs(o);
    }
    store_o(o, h, rbase, lane);
}

__global__ void __launch_bounds__(512, 1) __cluster_dims__(2, 1, 1)
k_fused(const __grid_constant__ Maps tm, const __nv_bfloat16* __restrict__ x, const uint8_t* __restrict__ wqkv,
        const uint8_t* __restrict__ w1, const uint8_t* __restrict__ w2, const uint8_t* __restrict__ wo,
        const __nv_bfloat16* __restrict__ b1, const __nv_bfloat16* __restrict__ b2, __nv_bfloat16* __restrict__ out) {
    extern __shared__ __align__(1024) uint8_t smem[];
    const uint32_t sb = smem_u32(smem);
    const uint32_t bar = sb + SM_BAR;
    const int warp = __shfl_sync(~0u, threadIdx.x >> 5, 0), lane = threadIdx.x & 31;
    const int wgi = warp >> 2, w4 = warp & 3, g = lane >> 2, c = lane & 3;
    const uint32_t rank = blockIdx.x & 1, peer = rank ^ 1;
    const int cl = blockIdx.x >> 1;
    const int cg = cl >> 3, rb = (cl & 7) * 2 + rank;

    if (threadIdx.x == 0) TL(0, 0);
    if (warp == 15 && lane < 4) prefetch_map(lane == 0 ? &tm.x : lane == 1 ? &tm.wqkv : lane == 2 ? &tm.w1 : &tm.h);
    if (elect_one()) {
#pragma unroll
        for (int j = 0; j < 5; j++) {
            const int i = warp * 5 + j;
            const int cnt = (i >= B_E1 && i < B_F2) || (i >= B_E2 && i < B_KV) ? 16
                          : (i >= B_E3 && i <= B_ST) || i == B_STAT || i >= B_DEAD ? 8 : i == B_ST + 1 ? 2 : i == B_AUX ? 4 : i == B_AUX2 ? 3 : 1;
            if (i < B_COUNT) mbar_init(bar + i * 8, cnt);
        }
        fence_barrier_init();
    }
    __syncthreads();
    if (threadIdx.x == 0) TL(0, 1);
    cluster_arrive_relaxed();
    cluster_wait();
    if (threadIdx.x == 0) TL(0, 3);

    {
        const uint32_t sB = sb + SM_RING;
        if (threadIdx.x == 0) TL(1, 0);
        if (wgi < 2) {
            reg_dealloc<56>();
            if (threadIdx.x == 0) TL(4, 2);
            if (warp == 0) {
#pragma unroll 1
                for (int it = 0; it < 20; it++) {
                    const int s = it & 3;
                    const int kb = it < 2 ? it : (it & 1) ? (it + 1) >> 1 : 10;
                    if (it >= 4) mbar_wait(bar + (B_E1 + s) * 8, ((it >> 2) - 1) & 1);
                    else if (it > 0) __nanosleep(PACE_NS);
                    if (elect_one()) {
                        if (kb < 10) {
                            mbar_expect_tx(bar + (B_A + kb) * 8, 16384);
                            tma_load(sb + kb * 16384, &tm.x, kb * 64, rb * 128, bar + (B_A + kb) * 8);
                        }
                        const uint32_t dst = sB + s * 16384 + rank * 8192, fb = bar + (B_F1 + s) * 8;
                        const int c0 = cg * 240 + rank * 128;
                        mbar_expect_tx(fb, 16384);
                        tma_load_mc(dst, &tm.wqkv, c0, it * 32, fb, 3);
                        tma_load_mc(dst + 4096, &tm.wqkv, c0 + 64, it * 32, fb, 3);
                    }
                    __syncwarp();
                    if (lane == 0 && it < 8) TL(5, it) ;
                }
#pragma unroll 1
                for (int it = 0; it < 20; it++) {
                    const int s = it % 5;
                    if (it < 5) { if (it != 3) mbar_wait(bar + (B_E1 + (it == 4 ? 3 : it)) * 8, 0); }
                    else mbar_wait(bar + (B_E2 + s) * 8, ((it / 5) - 1) & 1);
                    if (elect_one()) {
                        const uint32_t dst = sB + s * 12288, fb = bar + (B_F2 + s) * 8;
                        mbar_expect_tx(fb, 12288);
                        if ((it & 1) == (int)rank) {
                            tma_load_mc(dst, &tm.w1, cg * 192, it * 32, fb, 3);
                            tma_load_mc(dst + 4096, &tm.w1, cg * 192 + 64, it * 32, fb, 3);
                        } else {
                            tma_load_mc(dst + 8192, &tm.w1, cg * 192 + 128, it * 32, fb, 3);
                        }
                    }
                    __syncwarp();
                }
            } else {
                const int ht = threadIdx.x - 32;
                if (ht == 160) *reinterpret_cast<volatile uint32_t*>(smem + SM_EPOCH) = *(volatile uint32_t*)&g_epoch;
                auto slab_sum = [&](const uint32_t* src, int pitch) {
                    float s0 = 0.f, s1 = 0.f;
                    uint32_t v[40];
#pragma unroll
                    for (int k = 0; k < 40; k++) v[k] = __ldg(src + k * pitch);
#pragma unroll
                    for (int k = 0; k < 40; k++) { s0 += bf_lo(v[k]); s1 += bf_hi(v[k]); }
                    return make_float2(s0, s1);
                };
                auto gather = [&](int idx) {
                    float s0 = 0.f, s1 = 0.f;
#pragma unroll
                    for (int r = 0; r < 16; r++) {
                        const float2 v = __ldcg(g_csp + r * 1728 + cg * 216 + idx);
                        s0 += v.x; s1 += v.y;
                    }
                    reinterpret_cast<float2*>(smem + SM_CS)[idx] = make_float2(s0, s1);
                };
                if (warp == 7) {
                    mbar_wait(bar + B_STAT * 8, 0);
                    if (elect_one()) cnt_signal(CNT_ST + rb);
                    __syncwarp();
                }
                if (ht < 120)
                    g_csp[rb * 1728 + cg * 216 + ht] = slab_sum(reinterpret_cast<const uint32_t*>(wqkv) + rb * 40 * 960 + cg * 120 + ht, 960);
                if (threadIdx.x == 64) IT(3, 0);
                if (threadIdx.x == 192) IT(3, 1);
                if (warp != 7) asm volatile("bar.sync 8, 192;" ::: "memory");
                const uint32_t epoch = *reinterpret_cast<volatile uint32_t*>(smem + SM_EPOCH);
                if (warp == 6) { if (elect_one()) cnt_signal(CNT_CS + cg); __syncwarp(); }

                if (threadIdx.x == 64) IT(3, 2);
                if (warp <= 4) {
                    if (lane == 0) { cnt_wait(CNT_CS + cg, (epoch + 1) * 16); cnt_wait(CNT_ST + rb, (epoch + 1) * 8); }
                    __syncwarp();
                    if (threadIdx.x == 64) IT(3, 4);
                    if (ht < 120) gather(ht);
                    __syncwarp();
                    if (threadIdx.x == 64) IT(3, 5);
                    if (lane == 0) mbar_arrive(bar + B_AUX * 8);
                }
                if (ht >= 128) {
                    g_csp[rb * 1728 + cg * 216 + 120 + (ht - 128)] = slab_sum(reinterpret_cast<const uint32_t*>(w1) + rb * 40 * 768 + cg * 96 + (ht - 128), 768);
                    reinterpret_cast<uint32_t*>(smem + SM_BIAS)[ht - 128] = __ldg(reinterpret_cast<const uint32_t*>(b1 + cg * 192) + (ht - 128));
                    asm volatile("bar.sync 9, 96;" ::: "memory");
                    const uint32_t epoch2 = *reinterpret_cast<volatile uint32_t*>(smem + SM_EPOCH);
                    if (warp == 5) { if (elect_one()) cnt_signal(CNT_CS2 + cg); __syncwarp(); }
                    if (warp == 6 && elect_one()) {
                        prefetch_l2(w2 + blockIdx.x * 15360, 15360);
                        prefetch_l2(wo + blockIdx.x * 6400, 6400);
                    }
                    if (lane == 0) cnt_wait(CNT_CS2 + cg, (epoch2 + 1) * 16);
                    __syncwarp();
                    gather(120 + (ht - 128));
                    __syncwarp();
                    if (lane == 0) mbar_arrive(bar + B_AUX2 * 8);
                }
                if (warp == 4) {
                    mbar_wait(bar + B_ST * 8, 0);
                    if (elect_one()) cnt_signal(CNT_QKV + cg);
                    __syncwarp();
                }
                const int h = blockIdx.x >> 2, qb = blockIdx.x & 3;
                asm volatile("bar.sync 8, 224;" ::: "memory");
                const uint32_t ep = *reinterpret_cast<volatile uint32_t*>(smem + SM_EPOCH);
                if (lane == 0) {
                    cnt_wait(CNT_QKV + h / 12, (ep + 1) * 16);
                    cnt_wait(CNT_QKV + (32 + h) / 12, (ep + 1) * 16);
                    cnt_wait(CNT_QKV + (64 + h) / 12, (ep + 1) * 16);
                }
                __syncwarp();
                {
                    float kmax = 0.f, qmax = 0.f;
#pragma unroll
                    for (int i = 0; i < 10; i++) if (ht + i * 224 < 2048) kmax = fmaxf(kmax, __ldcg(g_nrm + (32 + h) * SEQ + ht + i * 224));
#pragma unroll
                    for (int i = 0; i < 3; i++) if (ht + i * 224 < 512) qmax = fmaxf(qmax, __ldcg(g_nrm + h * SEQ + qb * 512 + ht + i * 224));
#pragma unroll
                    for (int o = 16; o; o >>= 1) {
                        kmax = fmaxf(kmax, __shfl_xor_sync(~0u, kmax, o));
                        qmax = fmaxf(qmax, __shfl_xor_sync(~0u, qmax, o));
                    }
                    float* red = reinterpret_cast<float*>(smem + SM_RED);
                    if (lane == 0) { red[warp] = kmax; red[8 + warp] = qmax; }
                    asm volatile("bar.sync 8, 224;" ::: "memory");
                    if (ht == 0) {
                        for (int w = 2; w < 8; w++) { kmax = fmaxf(kmax, red[w]); qmax = fmaxf(qmax, red[8 + w]); }
                        *reinterpret_cast<volatile uint32_t*>(smem + SM_SAFE) = kmax * qmax * 1.1f <= SAFE_BOUND * SAFE_BOUND;
                    }
                }
                const uint32_t barKV = bar + B_KV * 8;
                const uint8_t* gK = g_img + (size_t)(32 + h) * IMG_BYTES;
                const uint8_t* gV = g_img + (size_t)(64 + h) * IMG_BYTES;
                if (warp == 2) {
                    mbar_wait(bar + B_DEAD * 8, 0);
                    for (int i = lane; i < 192; i += 32) *reinterpret_cast<uint4*>(smem + SM_ZERO + i * 16) = make_uint4(0, 0, 0, 0);
                    fence_proxy_async();
                    __syncwarp();
                    if (elect_one()) {
                        asm volatile("fence.proxy.async.global;" ::: "memory");
                        const uint8_t* gQ = g_img + (size_t)h * IMG_BYTES + qb * 64 * 384;
                        mbar_expect_tx(barKV + 128, 6144);
                        bulk_load(sb + SM_K, gK, 6144, barKV + 128);
                        for (int p = 0; p < 2; p++) {
                            mbar_expect_tx(bar + (B_Q + p) * 8, 12288);
                            bulk_load(sb + SM_Q + p * 12288, gQ + p * 12288, 12288, bar + (B_Q + p) * 8);
                        }
                        for (int i = 0; i < 13; i++) {
                            mbar_expect_tx(barKV + i * 8, 12288);
                            bulk_load(sb + SM_K + (i + 1) * 6144, gK + (i + 1) * 6144, 6144, barKV + i * 8);
                        }
                    }
                    __syncwarp();
                } else if (warp == 3) {
                    mbar_wait(bar + (B_DEAD + 1) * 8, 0);
                    if (elect_one()) {
                        asm volatile("fence.proxy.async.global;" ::: "memory");
                        for (int i = 0; i < 9; i++) bulk_load(sb + SM_V + (i + 7) * 6144, gV + i * 6144, 6144, barKV + i * 8);
                    }
                    __syncwarp();
                }
            }
            asm volatile("bar.sync %0, 128;" ::"r"(wgi + 3) : "memory");
            reg_alloc<128>();
        } else {
            reg_alloc<200>();
            if (threadIdx.x == 256) TL(4, 0);
            const int wi = wgi - 2;
            const int row0 = rb * 128 + wi * 64 + w4 * 16 + g;
            const uint32_t sAw = sb + wi * 8192;
            const int rbk = row0 >> 3, hs0 = cg * 12;
            {
                const int srow = rb * 128 + cg * 16 + (warp - 8) * 2 + (lane >> 4);
                uint4 xv[5];
#pragma unroll
                for (int i = 0; i < 5; i++) xv[i] = __ldg(reinterpret_cast<const uint4*>(x + (size_t)srow * DM) + (lane & 15) + 16 * i);
                float sm = 0.f;
#pragma unroll
                for (int i = 0; i < 5; i++)
                    sm += ((bf_lo(xv[i].x) + bf_hi(xv[i].x)) + (bf_lo(xv[i].y) + bf_hi(xv[i].y))) +
                          ((bf_lo(xv[i].z) + bf_hi(xv[i].z)) + (bf_lo(xv[i].w) + bf_hi(xv[i].w)));
#pragma unroll
                for (int o = 8; o; o >>= 1) sm += __shfl_xor_sync(~0u, sm, o);
                const float mu = sm * (1.f / DM);
                float q0 = 0.f, q1 = 0.f;
#pragma unroll
                for (int i = 0; i < 5; i++) {
                    const uint32_t w[4] = {xv[i].x, xv[i].y, xv[i].z, xv[i].w};
#pragma unroll
                    for (int j = 0; j < 4; j++) {
                        const float d0 = bf_lo(w[j]) - mu, d1 = bf_hi(w[j]) - mu;
                        q0 = fmaf(d0, d0, q0); q1 = fmaf(d1, d1, q1);
                    }
                }
                float q = q0 + q1;
#pragma unroll
                for (int o = 8; o; o >>= 1) q += __shfl_xor_sync(~0u, q, o);
                const float var = q * (1.f / DM);
                const float r1 = rsqrtf(var + LN_EPS);
                const float r2 = rsqrtf(var * r1 * r1 + LN_EPS);
                if ((lane & 15) == 0) g_stat[srow] = make_float4(mu, r1, r1 * r2, 0.f);
                __syncwarp();
                if (lane == 0) mbar_arrive(bar + B_STAT * 8);
            }
            if (threadIdx.x == 256) TL(4, 1);
            float accA[100], accB[20];
            const uint64_t dA0 = make_desc(sAw, 16, 1024, 1), dB0 = make_desc(sB, 4096, 1024, 1);
#pragma unroll 2
            for (int it = 0; it < 20; it++) {
                const int s = it & 3;
                if (!(it & 1)) mbar_wait(bar + (B_A + (it >> 1)) * 8, 0);
                if (threadIdx.x == 256 && it == 0) TL(0, 2);
                if (threadIdx.x == 256 && it == 2) TL(4, 3);
                if (threadIdx.x == 256) IT(0, it);
                mbar_wait(bar + (B_F1 + s) * 8, (it >> 2) & 1);
                if (threadIdx.x == 256) IT(1, it);
                const uint64_t dA = dA0 + (it >> 1) * 1024 + (it & 1) * 4, dB = dB0 + s * 1024;
                wg_fence();
                wgmma_n40_ss_tb(accB, dA, dB + 769, it > 0);
                wgmma_n40_ss_tb(accB, dA + 2, dB + 769 + 128, 1);
                wgmma_n200_ss_tb(accA, dA, dB, it > 0);
                wgmma_n200_ss_tb(accA, dA + 2, dB + 128, 1);
                wg_commit();
                if (it > 0) { wg_wait<1>(); release_stage(bar + (B_E1 + ((it - 1) & 3)) * 8, peer, lane); }
            }
            if (threadIdx.x == 256) IT(2, 0);
            mbar_wait(bar + B_AUX * 8, 0);
            if (threadIdx.x == 256) IT(2, 1);
            const float4 st0 = __ldcg(g_stat + row0), st1 = __ldcg(g_stat + row0 + 8);
            wg_wait<0>();
            release_stage(bar + (B_E1 + 3) * 8, peer, lane);
            fence_regs(accA);
            fence_regs(accB);
            if (threadIdx.x == 256) TL(1, 1);
            const float2* cs = reinterpret_cast<const float2*>(smem + SM_CS) + c;
            uint8_t* img = g_img + (size_t)hs0 * IMG_BYTES + rbk * 384 + g * 16 + c * 4;
            const bool emu0 = (EMU_MASK >> (rbk & 15)) & 1, emu1 = (EMU_MASK >> ((rbk + 1) & 15)) & 1;
            const bool low = c < 2;
            uint32_t pk[60];
#pragma unroll
            for (int m = 0; m < 6; m++) {
                const int which = (hs0 + 2 * m) >> 5;
                const float m0 = st0.y * (which == 0 ? QSCALE : (which == 1 && emu0) ? 2.f : 1.f);
                const float m1 = st1.y * (which == 0 ? QSCALE : (which == 1 && emu1) ? 2.f : 1.f);
                const float d0 = -st0.x * m0, d1 = -st1.x * m1;
                const float* a = m < 5 ? &accA[20 * m] : accB;
#pragma unroll
                for (int b = 0; b < 5; b++) {
                    const float2 cv = cs[(5 * m + b) * 4];
                    pk[10 * m + 2 * b] = pack_bf16(fmaf(a[4 * b], m0, d0 * cv.x), fmaf(a[4 * b + 1], m0, d0 * cv.y));
                    pk[10 * m + 2 * b + 1] = pack_bf16(fmaf(a[4 * b + 2], m1, d1 * cv.x), fmaf(a[4 * b + 3], m1, d1 * cv.y));
                }
            }
            const float r20 = st0.z, r21 = st1.z, e20 = -st0.x * st0.z, e21 = -st1.x * st1.z;
            if (threadIdx.x == 256) IT(2, 2);
            float acc2[96];
#pragma unroll
            for (int it = 0; it < 20; it++) {
                const int s = it % 5;
                if (threadIdx.x == 256) IT(0, 20 + it);
                mbar_wait(bar + (B_F2 + s) * 8, (it / 5) & 1);
                if (threadIdx.x == 256) IT(1, 20 + it);
                wg_fence();
                const uint64_t dA = make_desc(sAw + (it >> 1) * 16384 + (it & 1) * 64, 16, 1024, 1);
                const uint64_t dB = make_desc(sB + s * 12288, 4096, 1024, 1);
                if (it == 0) wgmma_n192_ss_tb_z(acc2, dA, dB); else wgmma_n192_ss_tb(acc2, dA, dB, 1);
                wgmma_n192_ss_tb(acc2, dA + 2, dB + 128, 1);
                wg_commit();
                if (it > 0) {
                    wg_wait<1>();
                    if (it <= 15) release_stage(bar + (B_E2 + (it - 1) % 5) * 8, peer, lane);
                    if (it == 14 && lane == 0) mbar_arrive(bar + B_DEAD * 8);
                }
                if (it < 12) {
                    const int m = it / 2, part = it % 2;
                    const int hs = hs0 + 2 * m, which = hs >> 5;
                    const uint32_t* a = pk + 10 * m;
                    uint8_t* pe = img + (2 * m) * IMG_BYTES;
                    uint8_t* po = pe + IMG_BYTES;
                    if (part == 0) {
                        const uint32_t padv = which == 0 ? 0x3F803F80u : which == 1 ? 0xBFFF4440u : 0x00003F80u;
                        const uint32_t p0 = ((c & 1) || (which == 1 && !emu0)) ? 0u : padv;
                        const uint32_t p1 = ((c & 1) || (which == 1 && !emu1)) ? 0u : padv;
                        *(uint32_t*)(pe) = a[0];
                        *(uint32_t*)(pe + 128) = a[2];
                        *(uint32_t*)(pe + 256) = low ? a[4] : p0;
                        *(uint32_t*)(pe + 384) = a[1];
                        *(uint32_t*)(pe + 512) = a[3];
                        *(uint32_t*)(pe + 640) = low ? a[5] : p1;
                        *(uint32_t*)(po + 256) = low ? p0 : a[4];
                        *(uint32_t*)(po + 640) = low ? p1 : a[5];
                    } else {
                        *(uint32_t*)(po) = a[6];
                        *(uint32_t*)(po + 128) = a[8];
                        *(uint32_t*)(po + 384) = a[7];
                        *(uint32_t*)(po + 512) = a[9];
                        if (which < 2) {
                            const uint32_t u0 = bf2_fma(a[4], a[4], 0u), u1 = bf2_fma(a[5], a[5], 0u);
                            const uint32_t pe0 = bf2_fma(a[0], a[0], bf2_fma(a[2], a[2], low ? u0 : 0u));
                            const uint32_t pe1 = bf2_fma(a[1], a[1], bf2_fma(a[3], a[3], low ? u1 : 0u));
                            const uint32_t po0 = bf2_fma(a[6], a[6], bf2_fma(a[8], a[8], low ? 0u : u0));
                            const uint32_t po1 = bf2_fma(a[7], a[7], bf2_fma(a[9], a[9], low ? 0u : u1));
                            const float e0 = bf_lo(pe0) + bf_hi(pe0), e1 = bf_lo(pe1) + bf_hi(pe1);
                            const float o0 = bf_lo(po0) + bf_hi(po0), o1 = bf_lo(po1) + bf_hi(po1);
                            const bool b0 = c & 1, b1_ = c & 2;
                            const float x0 = (b0 ? e1 : e0) + __shfl_xor_sync(~0u, b0 ? e0 : e1, 1);
                            const float x1 = (b0 ? o1 : o0) + __shfl_xor_sync(~0u, b0 ? o0 : o1, 1);
                            float y = (b1_ ? x1 : x0) + __shfl_xor_sync(~0u, b1_ ? x0 : x1, 2);
                            if (which == 1 && (b0 ? emu1 : emu0)) y *= 0.25f;
                            g_nrm[(hs + (c >> 1)) * SEQ + row0 + (c & 1) * 8] = y;
                        }
                    }
                    if (it == 11) { __syncwarp(); if (lane == 0) mbar_arrive(bar + B_ST * 8); }
                }
            }
            wg_wait<0>();
            fence_regs(acc2);
            if (lane == 0) mbar_arrive(bar + (B_DEAD + 1) * 8);
            if (threadIdx.x == 256) TL(1, 2);
            mbar_wait(bar + B_AUX2 * 8, 0);
            const uint32_t* bias = reinterpret_cast<const uint32_t*>(smem + SM_BIAS) + c;
            const int mrow = w4 * 16 + (lane & 15);
            const uint32_t stage = sAw + 7 * 16384;
            const uint32_t st_row = stage + mrow * 128;
#pragma unroll
            for (int j = 0; j < 24; j += 2) {
                const uint32_t bA = bias[j * 4], bB = bias[j * 4 + 4];
                const float2 cA = cs[(30 + j) * 4], cB = cs[(31 + j) * 4];
                const float* a = acc2 + j * 4;
                const uint32_t r00 = pack_bf16(gelu_tanh(fmaf(a[0], r20, fmaf(e20, cA.x, bf_lo(bA)))), gelu_tanh(fmaf(a[1], r20, fmaf(e20, cA.y, bf_hi(bA)))));
                const uint32_t r10 = pack_bf16(gelu_tanh(fmaf(a[2], r21, fmaf(e21, cA.x, bf_lo(bA)))), gelu_tanh(fmaf(a[3], r21, fmaf(e21, cA.y, bf_hi(bA)))));
                const uint32_t r01 = pack_bf16(gelu_tanh(fmaf(a[4], r20, fmaf(e20, cB.x, bf_lo(bB)))), gelu_tanh(fmaf(a[5], r20, fmaf(e20, cB.y, bf_hi(bB)))));
                const uint32_t r11 = pack_bf16(gelu_tanh(fmaf(a[6], r21, fmaf(e21, cB.x, bf_lo(bB)))), gelu_tanh(fmaf(a[7], r21, fmaf(e21, cB.y, bf_hi(bB)))));
                const int chunk = (j & 7) + (lane >> 4);
                stmatrix_x4(st_row + (j >> 3) * 16384 + ((chunk ^ (mrow & 7)) << 4), r00, r10, r01, r11);
            }
            fence_proxy_async();
            asm volatile("bar.sync %0, 128;" ::"r"(wgi + 3) : "memory");
            if (w4 == 0 && lane == 0) {
#pragma unroll
                for (int b = 0; b < 3; b++) tma_store(&tm.h, stage + b * 16384, cg * 192 + b * 64, rb * 128 + wi * 64);
                bulk_commit();
                bulk_wait_read();
            }
            __syncwarp();
            reg_dealloc<128>();
        }
        __syncthreads();
        if (threadIdx.x == 0) TL(1, 3);
    }

    {
        const int h = blockIdx.x >> 2, qb = blockIdx.x & 3;
        const uint32_t sK = sb + SM_K, sV = sb + SM_V, barKV = bar + B_KV * 8;
        if (threadIdx.x == 0) TL(2, 0);
        if (warp == 5 && elect_one()) {
            asm volatile("fence.proxy.async.global;" ::: "memory");
            const uint8_t* gK = g_img + (size_t)(32 + h) * IMG_BYTES;
            const uint8_t* gV = g_img + (size_t)(64 + h) * IMG_BYTES;
            for (int i = 9; i < 16; i++) {
                if (i >= 13) mbar_expect_tx(barKV + i * 8, i < 15 ? 12288 : 6144);
                bulk_load(sV + ((i + 7) & 15) * 6144, gV + i * 6144, 6144, barKV + i * 8);
                if (i >= 13 && i < 15) bulk_load(sK + (i + 1) * 6144, gK + (i + 1) * 6144, 6144, barKV + i * 8);
            }
        }
        __syncwarp();
        const bool safe = __all_sync(~0u, *reinterpret_cast<volatile uint32_t*>(smem + SM_SAFE) != 0);
        if (threadIdx.x == 0) TL(2, 1);
        const uint64_t dK0 = make_desc(sK, 128, 384, 0), dV0 = make_desc(sV, 384, 128, 0);
        auto publish_h = [&]() {
            if (warp == 8 || warp == 12) {
                if (lane == 0) { bulk_wait_all(); cnt_signal(CNT_H + rb); }
                __syncwarp();
            }
        };
        if (!safe) {
#pragma unroll 1
            for (int pass = 0; pass < 2; pass++) {
                const uint32_t sQ = sb + SM_Q + pass * 12288 + wgi * 3072;
                mbar_wait(bar + (B_Q + pass) * 8, 0);
                if (lane < 16) *reinterpret_cast<uint32_t*>(smem + (sQ - sb) + (w4 * 2 + (lane >> 3)) * 384 + 256 + (lane & 7) * 16 + ((h & 1) ? 0 : 8)) = 0u;
                fence_proxy_async();
                asm volatile("bar.sync %0, 128;" ::"r"(wgi + 3) : "memory");
                attn_rows_maxshift(sK, barKV, make_desc(sQ, 128, 384, 0), make_desc(sQ + 256, sb + SM_ZERO - (sQ + 256), 384, 0), h,
                                   qb * 512 + pass * 256 + wgi * 64 + w4 * 16);
                if (pass == 0) publish_h();
            }
        } else {
            const ExpConst kc = make_exp_const();
#pragma unroll 1
            for (int pass = 0; pass < 2; pass++) {
                const int rbase = qb * 512 + pass * 256 + wgi * 64 + w4 * 16;
                const uint32_t sQ = sb + SM_Q + pass * 12288 + wgi * 3072;
                const uint64_t dQ = make_desc(sQ, 128, 384, 0), dQ2 = make_desc(sQ + 256, sb + SM_ZERO - (sQ + 256), 384, 0);
                float o[12], sa[32], sc[32];
                uint32_t p[16];
#pragma unroll
                for (int i = 0; i < 12; i++) o[i] = 0.f;
                fence_regs(o);
                mbar_wait(bar + (B_Q + pass) * 8, 0);
                mbar_wait(barKV + 128, 0);
                qk_tile(sa, dQ, dQ2, dK0);
                wg_wait<0>();
                fence_regs(sa);
                uint64_t dK = dK0, dV = dV0 + 7 * 384;
                uint32_t bj = barKV;
#pragma unroll 1
                for (int j = 0; j < 16; j++) {
                    mbar_wait(bj, 0);
                    qk_tile(sc, dQ, dQ2, dK + 192);
                    wg_wait<1>();
                    exp_tile<0>(sa, p, kc);
                    pv_tile(o, p, dV);
                    wg_wait<1>();
                    fence_regs(sc);
                    mbar_wait(bj, 0);
                    qk_tile(sa, dQ, dQ2, dK + 384);
                    wg_wait<1>();
                    exp_tile<8>(sc, p, kc);
                    pv_tile(o, p, dV + 192);
                    wg_wait<1>();
                    fence_regs(sa);
                    dK += 384; dV = j == 8 ? dV0 : dV + 384; bj += 8;
                }
                wg_wait<0>();
                fence_regs(o);
                store_o(o, h, rbase, lane);
                if (threadIdx.x == 0) TL(2, 2 + pass);
                if (pass == 0) publish_h();
            }
        }
        __syncthreads();
        if (threadIdx.x == 64) cnt_signal(CNT_O + qb);
        cluster_arrive_relaxed();
    }

    {
        const uint32_t epoch = *reinterpret_cast<volatile uint32_t*>(smem + SM_EPOCH);
        const int ct = cl & 3, rt = (cl >> 2) * 2 + rank;
        if (threadIdx.x == 0) TL(3, 0);
        const int orow = threadIdx.x >> 3, oseg = threadIdx.x & 7;
        const size_t ooff = (size_t)(rt * 64 + orow) * DM + ct * 160 + oseg * 20;
        uint2 xr[5], br[5];
#pragma unroll
        for (int i = 0; i < 5; i++) {
            xr[i] = __ldg(reinterpret_cast<const uint2*>(x + ooff) + i);
            br[i] = __ldg(reinterpret_cast<const uint2*>(b2 + ct * 160 + oseg * 20) + i);
        }
        cluster_wait();
        float* stg = reinterpret_cast<float*>(smem);
        if (warp == 4) {
            if (elect_one()) { prefetch_map(&tm.h); prefetch_map(&tm.o); prefetch_map(&tm.w2); prefetch_map(&tm.wo); cnt_wait(CNT_H + (rt >> 1), (epoch + 1) * 16); }
            __syncwarp();
#pragma unroll 1
            for (int kb = 0; kb < 34; kb++) {
                const int s = kb & 7;
                if (kb >= 8) mbar_wait(bar + (B_E3 + s) * 8, ((kb >> 3) - 1) & 1);
                if (elect_one()) {
                    if (kb == 24) { cnt_wait(CNT_O + (rt >> 3), (epoch + 1) * 32); TL(3, 1); }
                    const uint32_t dst = sb + s * G2_STAGE, fb = bar + (B_F3 + s) * 8;
                    const CUtensorMap* mA = kb < 24 ? &tm.h : &tm.o;
                    const CUtensorMap* mB = kb < 24 ? &tm.w2 : &tm.wo;
                    const int k0 = (kb < 24 ? kb : kb - 24) * 64;
                    mbar_expect_tx(fb, G2_STAGE);
                    tma_load(dst, mA, k0, rt * 64, fb);
                    const int first = ((kb & 1) == (int)rank) ? 0 : 3, last = ((kb & 1) == (int)rank) ? 3 : 5;
                    for (int b = first; b < last; b++) tma_load_mc(dst + 8192 + b * 4096, mB, ct * 160 + b * 32, k0, fb, 3);
                }
                __syncwarp();
            }
        } else if (wgi == 0) {
            float acc[80];
#pragma unroll 1
            for (int kb = 0; kb < 34; kb++) {
                const int s = kb & 7;
                mbar_wait(bar + (B_F3 + s) * 8, (kb >> 3) & 1);
                wg_fence();
                const uint64_t dA = make_desc(sb + s * G2_STAGE, 16, 1024, 1);
                const uint64_t dB = make_desc(sb + s * G2_STAGE + 8192, 4096, 512, 2);
#pragma unroll
                for (int kk = 0; kk < 4; kk++) wgmma_n160_ss_tb(acc, dA + kk * 2, dB + kk * 64, (kb | kk) != 0);
                wg_commit();
                if (kb > 0) {
                    wg_wait<1>();
                    if (kb <= 26) release_stage(bar + (B_E3 + ((kb - 1) & 7)) * 8, peer, lane);
                }
            }
            wg_wait<0>();
            fence_regs(acc);
            if (threadIdx.x == 0) TL(3, 2);
            const int r = w4 * 16 + g;
#pragma unroll
            for (int j = 0; j < 20; j++) {
                *reinterpret_cast<float2*>(stg + r * 168 + j * 8 + 2 * c) = make_float2(acc[4 * j], acc[4 * j + 1]);
                *reinterpret_cast<float2*>(stg + (r + 8) * 168 + j * 8 + 2 * c) = make_float2(acc[4 * j + 2], acc[4 * j + 3]);
            }
        }
        __syncthreads();
        const float4* sp = reinterpret_cast<const float4*>(stg + orow * 168 + oseg * 20);
#pragma unroll
        for (int i = 0; i < 5; i++) {
            const float4 a = sp[i];
            uint2 w;
            w.x = pack_bf16(a.x + bf_lo(br[i].x) + bf_lo(xr[i].x), a.y + bf_hi(br[i].x) + bf_hi(xr[i].x));
            w.y = pack_bf16(a.z + bf_lo(br[i].y) + bf_lo(xr[i].y), a.w + bf_hi(br[i].y) + bf_hi(xr[i].y));
            reinterpret_cast<uint2*>(out + ooff)[i] = w;
        }
        if (blockIdx.x == 0 && threadIdx.x == 0) g_epoch = epoch + 1;
        if (threadIdx.x == 0) TL(3, 3);
    }
    cluster_arrive_relaxed();
    cluster_wait();
}

typedef CUresult (*EncodeTiledFn)(CUtensorMap*, CUtensorMapDataType, cuuint32_t, void*, const cuuint64_t*,
                                  const cuuint64_t*, const cuuint32_t*, const cuuint32_t*, CUtensorMapInterleave,
                                  CUtensorMapSwizzle, CUtensorMapL2promotion, CUtensorMapFloatOOBfill);

CUtensorMap make_map(EncodeTiledFn enc, const void* ptr, int rows, int cols, int box_rows, int box_cols,
                     CUtensorMapSwizzle swz) {
    CUtensorMap m;
    cuuint64_t gd[2] = {(cuuint64_t)cols, (cuuint64_t)rows};
    cuuint64_t gs[1] = {(cuuint64_t)cols * 2};
    cuuint32_t bd[2] = {(cuuint32_t)box_cols, (cuuint32_t)box_rows};
    cuuint32_t es[2] = {1, 1};
    enc(&m, CU_TENSOR_MAP_DATA_TYPE_BFLOAT16, 2, const_cast<void*>(ptr), gd, gs, bd, es, CU_TENSOR_MAP_INTERLEAVE_NONE,
        swz, CU_TENSOR_MAP_L2_PROMOTION_L2_128B, CU_TENSOR_MAP_FLOAT_OOB_FILL_NONE);
    return m;
}

}

extern "C" void kernel_launch(void* const* d_in, const int* in_sizes, int n_in, void* d_out, int out_size) {
    (void)in_sizes; (void)n_in; (void)out_size;
    const __nv_bfloat16* x = (const __nv_bfloat16*)d_in[0];
    const __nv_bfloat16* wqkv = (const __nv_bfloat16*)d_in[1];
    const __nv_bfloat16* wo = (const __nv_bfloat16*)d_in[2];
    const __nv_bfloat16* w1 = (const __nv_bfloat16*)d_in[4];
    const __nv_bfloat16* b1 = (const __nv_bfloat16*)d_in[5];
    const __nv_bfloat16* w2 = (const __nv_bfloat16*)d_in[6];
    const __nv_bfloat16* b2 = (const __nv_bfloat16*)d_in[7];
    __nv_bfloat16* out = (__nv_bfloat16*)d_out;

    static EncodeTiledFn enc = nullptr;
    static void *p_h, *p_o;
    if (!enc) {
        cudaDriverEntryPointQueryResult qr;
        cudaGetDriverEntryPoint("cuTensorMapEncodeTiled", (void**)&enc, cudaEnableDefault, &qr);
        cudaGetSymbolAddress(&p_h, g_h);
        cudaGetSymbolAddress(&p_o, g_o);
        cudaFuncSetAttribute(k_fused, cudaFuncAttributeMaxDynamicSharedMemorySize, SM_TOTAL);
    }
    Maps tm;
    tm.x = make_map(enc, x, SEQ, DM, 128, 64, CU_TENSOR_MAP_SWIZZLE_128B);
    tm.wqkv = make_map(enc, wqkv, DM, 3 * DM, 32, 64, CU_TENSOR_MAP_SWIZZLE_128B);
    tm.w1 = make_map(enc, w1, DM, FF, 32, 64, CU_TENSOR_MAP_SWIZZLE_128B);
    tm.h = make_map(enc, p_h, SEQ, FF, 64, 64, CU_TENSOR_MAP_SWIZZLE_128B);
    tm.o = make_map(enc, p_o, SEQ, DM, 64, 64, CU_TENSOR_MAP_SWIZZLE_128B);
    tm.wo = make_map(enc, wo, DM, DM, 64, 32, CU_TENSOR_MAP_SWIZZLE_64B);
    tm.w2 = make_map(enc, w2, FF, DM, 64, 32, CU_TENSOR_MAP_SWIZZLE_64B);
    k_fused<<<128, 512, SM_TOTAL, cudaStreamPerThread>>>(tm, x, (const uint8_t*)wqkv, (const uint8_t*)w1, (const uint8_t*)w2,
                                                         (const uint8_t*)wo, b1, b2, out);
}
```

```cpp
#include <cuda_runtime.h>
#include <cuda_bf16.h>
#include <cuda.h>
#include <stdint.h>

namespace {

constexpr int SEQ = 2048, DM = 640, FF = 1536;
constexpr float LN_EPS = 1e-5f;

constexpr int IMG_BYTES = 256 * 384;
constexpr uint32_t EMU_MASK = 0xD5D5u;
constexpr float SAFE_BOUND = 80.0f;
#define XV_IT 1
#define PACE_NS 200
constexpr float QSCALE = 0.22360679774997896f * 1.4426950408889634f;

__device__ float4 g_stat[SEQ];
__device__ float2 g_csp[16 * 1728];
__device__ __align__(1024) uint8_t g_img[96 * IMG_BYTES + 1024];
__device__ float g_nrm[64 * SEQ];
__device__ __align__(1024) __nv_bfloat16 g_h[SEQ * FF];
__device__ __align__(1024) __nv_bfloat16 g_o[SEQ * DM];
constexpr int CNT_ST = 0, CNT_QKV = 16, CNT_H = 24, CNT_O = 40, CNT_CS = 44, CNT_CS2 = 52;
__device__ uint32_t g_cnt[60 * 32];
__device__ uint32_t g_epoch;

#define TL(kern, slot) do { } while (0)
#define IT(row, i) do { } while (0)

__device__ __forceinline__ uint32_t smem_u32(const void* p) { return (uint32_t)__cvta_generic_to_shared(p); }
__device__ __forceinline__ void mbar_init(uint32_t bar, int cnt) {
    asm volatile("mbarrier.init.shared::cta.b64 [%0], %1;" ::"r"(bar), "r"(cnt));
}
__device__ __forceinline__ void mbar_expect_tx(uint32_t bar, uint32_t bytes) {
    asm volatile("mbarrier.arrive.expect_tx.shared::cta.b64 _, [%0], %1;" ::"r"(bar), "r"(bytes) : "memory");
}
__device__ __forceinline__ void mbar_wait(uint32_t bar, uint32_t parity) {
    asm volatile("{\n.reg .pred p;\n.reg .u32 n;\nmov.u32 n, 0;\n"
                 "WAIT_LOOP:\nmbarrier.try_wait.parity.shared::cta.b64 p, [%0], %1;\n@p bra WAIT_DONE;\n"
                 "add.u32 n, n, 1;\nsetp.lt.u32 p, n, 4194304;\n@p bra WAIT_LOOP;\nWAIT_DONE:\n}"
                 ::"r"(bar), "r"(parity) : "memory");
}
__device__ __forceinline__ void mbar_arrive(uint32_t bar) {
    asm volatile("mbarrier.arrive.shared::cta.b64 _, [%0];" ::"r"(bar) : "memory");
}
__device__ __forceinline__ void mbar_arrive_cluster(uint32_t bar, uint32_t cta) {
    asm volatile("{\n.reg .b32 ra;\nmapa.shared::cluster.u32 ra, %0, %1;\n"
                 "mbarrier.arrive.shared::cluster.b64 _, [ra];\n}" ::"r"(bar), "r"(cta) : "memory");
}
__device__ __forceinline__ void fence_barrier_init() { asm volatile("fence.mbarrier_init.release.cluster;" ::: "memory"); }
__device__ __forceinline__ void fence_proxy_async() { asm volatile("fence.proxy.async.shared::cta;" ::: "memory"); }
__device__ __forceinline__ void cluster_sync() {
    asm volatile("barrier.cluster.arrive.release.aligned;\nbarrier.cluster.wait.acquire.aligned;" ::: "memory");
}
__device__ __forceinline__ bool elect_one() {
    uint32_t pred;
    asm volatile("{\n.reg .pred p;\nelect.sync _|p, 0xFFFFFFFF;\nselp.b32 %0, 1, 0, p;\n}" : "=r"(pred));
    return pred != 0;
}
__device__ __forceinline__ void pdl_launch() { asm volatile("griddepcontrol.launch_dependents;" ::: "memory"); }
__device__ __forceinline__ void pdl_wait() { asm volatile("griddepcontrol.wait;" ::: "memory"); }
__device__ __forceinline__ void prefetch_map(const CUtensorMap* m) {
    asm volatile("prefetch.tensormap [%0];" ::"l"(m) : "memory");
}
__device__ __forceinline__ void tma_load(uint32_t dst, const CUtensorMap* m, int c0, int c1, uint32_t bar) {
    asm volatile("cp.async.bulk.tensor.2d.shared::cluster.global.mbarrier::complete_tx::bytes [%0], [%1, {%3, %4}], [%2];"
                 ::"r"(dst), "l"(m), "r"(bar), "r"(c0), "r"(c1) : "memory");
}
__device__ __forceinline__ void tma_load_mc(uint32_t dst, const CUtensorMap* m, int c0, int c1, uint32_t bar, uint16_t mask) {
    asm volatile("cp.async.bulk.tensor.2d.shared::cluster.global.mbarrier::complete_tx::bytes.multicast::cluster"
                 " [%0], [%1, {%3, %4}], [%2], %5;"
                 ::"r"(dst), "l"(m), "r"(bar), "r"(c0), "r"(c1), "h"(mask) : "memory");
}
__device__ __forceinline__ void tma_store(const CUtensorMap* m, uint32_t src, int c0, int c1) {
    asm volatile("cp.async.bulk.tensor.2d.global.shared::cta.bulk_group [%0, {%2, %3}], [%1];"
                 ::"l"(m), "r"(src), "r"(c0), "r"(c1) : "memory");
}
__device__ __forceinline__ void bulk_commit() { asm volatile("cp.async.bulk.commit_group;" ::: "memory"); }
__device__ __forceinline__ void bulk_wait_all() { asm volatile("cp.async.bulk.wait_group 0;" ::: "memory"); }
__device__ __forceinline__ void bulk_load(uint32_t dst, const void* src, uint32_t bytes, uint32_t bar) {
    asm volatile("cp.async.bulk.shared::cluster.global.mbarrier::complete_tx::bytes [%0], [%1], %2, [%3];"
                 ::"r"(dst), "l"(src), "r"(bytes), "r"(bar) : "memory");
}
__device__ __forceinline__ void prefetch_l2(const void* p, uint32_t bytes) {
    asm volatile("cp.async.bulk.prefetch.L2.global [%0], %1;" ::"l"(p), "r"(bytes) : "memory");
}
__device__ __forceinline__ void tma_prefetch_l2(const CUtensorMap* m, int c0, int c1) {
    asm volatile("cp.async.bulk.prefetch.tensor.2d.L2.global.tile [%0, {%1, %2}];" ::"l"(m), "r"(c0), "r"(c1) : "memory");
}
__device__ __forceinline__ void wg_fence() { asm volatile("wgmma.fence.sync.aligned;" ::: "memory"); }
__device__ __forceinline__ void wg_commit() { asm volatile("wgmma.commit_group.sync.aligned;" ::: "memory"); }
template <int N> __device__ __forceinline__ void wg_wait() {
    asm volatile("wgmma.wait_group.sync.aligned %0;" ::"n"(N) : "memory");
}
template <int N> __device__ __forceinline__ void reg_alloc() { asm volatile("setmaxnreg.inc.sync.aligned.u32 %0;" ::"n"(N)); }
template <int N> __device__ __forceinline__ void reg_dealloc() { asm volatile("setmaxnreg.dec.sync.aligned.u32 %0;" ::"n"(N)); }
template <int N> __device__ __forceinline__ void fence_regs(float (&d)[N]) {
#pragma unroll
    for (int i = 0; i < N; i++) asm volatile("" : "+f"(d[i])::"memory");
}
__device__ __forceinline__ uint64_t make_desc(uint32_t addr, uint32_t lbo, uint32_t sbo, uint32_t swz) {
    return (uint64_t)((addr & 0x3FFFF) >> 4) | ((uint64_t)(lbo >> 4) << 16) | ((uint64_t)(sbo >> 4) << 32) |
           ((uint64_t)swz << 62);
}
__device__ __forceinline__ uint32_t pack_bf16(float lo, float hi) {
    uint32_t r;
    asm("cvt.rn.bf16x2.f32 %0, %1, %2;" : "=r"(r) : "f"(hi), "f"(lo));
    return r;
}
__device__ __forceinline__ float ex2(float x) {
    float r;
    asm("ex2.approx.ftz.f32 %0, %1;" : "=f"(r) : "f"(x));
    return r;
}
__device__ __forceinline__ float bf_lo(uint32_t v) { return __uint_as_float(v << 16); }
__device__ __forceinline__ float bf_hi(uint32_t v) { return __uint_as_float(v & 0xFFFF0000u); }
__device__ __forceinline__ void stmatrix_x4(uint32_t addr, uint32_t r0, uint32_t r1, uint32_t r2, uint32_t r3) {
    asm volatile("stmatrix.sync.aligned.m8n8.x4.shared.b16 [%0], {%1, %2, %3, %4};"
                 ::"r"(addr), "r"(r0), "r"(r1), "r"(r2), "r"(r3) : "memory");
}

__device__ __forceinline__ void wgmma_n200_ss_tb(float (&d)[100], uint64_t descA, uint64_t descB, int scaleD) {
    asm volatile("{\n.reg .pred p;\nsetp.ne.b32 p, %102, 0;\n"
        "wgmma.mma_async.sync.aligned.m64n200k16.f32.bf16.bf16 {"
        "%0, %1, %2, %3, %4, %5, %6, %7, %8, %9, %10, %11, %12, %13, %14, %15, "
        "%16, %17, %18, %19, %20, %21, %22, %23, %24, %25, %26, %27, %28, %29, %30, %31, "
        "%32, %33, %34, %35, %36, %37, %38, %39, %40, %41, %42, %43, %44, %45, %46, %47, "
        "%48, %49, %50, %51, %52, %53, %54, %55, %56, %57, %58, %59, %60, %61, %62, %63, "
        "%64, %65, %66, %67, %68, %69, %70, %71, %72, %73, %74, %75, %76, %77, %78, %79, "
        "%80, %81, %82, %83, %84, %85, %86, %87, %88, %89, %90, %91, %92, %93, %94, %95, "
        "%96, %97, %98, %99}, "
        "%100, %101, p, 1, 1, 0, 1;\n}\n"
        : "+f"(d[0]), "+f"(d[1]), "+f"(d[2]), "+f"(d[3]), "+f"(d[4]), "+f"(d[5]), "+f"(d[6]), "+f"(d[7]),
          "+f"(d[8]), "+f"(d[9]), "+f"(d[10]), "+f"(d[11]), "+f"(d[12]), "+f"(d[13]), "+f"(d[14]), "+f"(d[15]),
          "+f"(d[16]), "+f"(d[17]), "+f"(d[18]), "+f"(d[19]), "+f"(d[20]), "+f"(d[21]), "+f"(d[22]), "+f"(d[23]),
          "+f"(d[24]), "+f"(d[25]), "+f"(d[26]), "+f"(d[27]), "+f"(d[28]), "+f"(d[29]), "+f"(d[30]), "+f"(d[31]),
          "+f"(d[32]), "+f"(d[33]), "+f"(d[34]), "+f"(d[35]), "+f"(d[36]), "+f"(d[37]), "+f"(d[38]), "+f"(d[39]),
          "+f"(d[40]), "+f"(d[41]), "+f"(d[42]), "+f"(d[43]), "+f"(d[44]), "+f"(d[45]), "+f"(d[46]), "+f"(d[47]),
          "+f"(d[48]), "+f"(d[49]), "+f"(d[50]), "+f"(d[51]), "+f"(d[52]), "+f"(d[53]), "+f"(d[54]), "+f"(d[55]),
          "+f"(d[56]), "+f"(d[57]), "+f"(d[58]), "+f"(d[59]), "+f"(d[60]), "+f"(d[61]), "+f"(d[62]), "+f"(d[63]),
          "+f"(d[64]), "+f"(d[65]), "+f"(d[66]), "+f"(d[67]), "+f"(d[68]), "+f"(d[69]), "+f"(d[70]), "+f"(d[71]),
          "+f"(d[72]), "+f"(d[73]), "+f"(d[74]), "+f"(d[75]), "+f"(d[76]), "+f"(d[77]), "+f"(d[78]), "+f"(d[79]),
          "+f"(d[80]), "+f"(d[81]), "+f"(d[82]), "+f"(d[83]), "+f"(d[84]), "+f"(d[85]), "+f"(d[86]), "+f"(d[87]),
          "+f"(d[88]), "+f"(d[89]), "+f"(d[90]), "+f"(d[91]), "+f"(d[92]), "+f"(d[93]), "+f"(d[94]), "+f"(d[95]),
          "+f"(d[96]), "+f"(d[97]), "+f"(d[98]), "+f"(d[99])
        : "l"(descA), "l"(descB), "r"(scaleD));
}

__device__ __forceinline__ void wgmma_n40_ss_tb(float (&d)[20], uint64_t descA, uint64_t descB, int scaleD) {
    asm volatile("{\n.reg .pred p;\nsetp.ne.b32 p, %22, 0;\n"
        "wgmma.mma_async.sync.aligned.m64n40k16.f32.bf16.bf16 {"
        "%0, %1, %2, %3, %4, %5, %6, %7, %8, %9, %10, %11, %12, %13, %14, %15, "
        "%16, %17, %18, %19}, "
        "%20, %21, p, 1, 1, 0, 1;\n}\n"
        : "+f"(d[0]), "+f"(d[1]), "+f"(d[2]), "+f"(d[3]), "+f"(d[4]), "+f"(d[5]), "+f"(d[6]), "+f"(d[7]),
          "+f"(d[8]), "+f"(d[9]), "+f"(d[10]), "+f"(d[11]), "+f"(d[12]), "+f"(d[13]), "+f"(d[14]), "+f"(d[15]),
          "+f"(d[16]), "+f"(d[17]), "+f"(d[18]), "+f"(d[19])
        : "l"(descA), "l"(descB), "r"(scaleD));
}

__device__ __forceinline__ void wgmma_n192_ss_tb(float (&d)[96], uint64_t descA, uint64_t descB, int scaleD) {
    asm volatile("{\n.reg .pred p;\nsetp.ne.b32 p, %98, 0;\n"
        "wgmma.mma_async.sync.aligned.m64n192k16.f32.bf16.bf16 {"
        "%0, %1, %2, %3, %4, %5, %6, %7, %8, %9, %10, %11, %12, %13, %14, %15, "
        "%16, %17, %18, %19, %20, %21, %22, %23, %24, %25, %26, %27, %28, %29, %30, %31, "
        "%32, %33, %34, %35, %36, %37, %38, %39, %40, %41, %42, %43, %44, %45, %46, %47, "
        "%48, %49, %50, %51, %52, %53, %54, %55, %56, %57, %58, %59, %60, %61, %62, %63, "
        "%64, %65, %66, %67, %68, %69, %70, %71, %72, %73, %74, %75, %76, %77, %78, %79, "
        "%80, %81, %82, %83, %84, %85, %86, %87, %88, %89, %90, %91, %92, %93, %94, %95}, "
        "%96, %97, p, 1, 1, 0, 1;\n}\n"
        : "+f"(d[0]), "+f"(d[1]), "+f"(d[2]), "+f"(d[3]), "+f"(d[4]), "+f"(d[5]), "+f"(d[6]), "+f"(d[7]),
          "+f"(d[8]), "+f"(d[9]), "+f"(d[10]), "+f"(d[11]), "+f"(d[12]), "+f"(d[13]), "+f"(d[14]), "+f"(d[15]),
          "+f"(d[16]), "+f"(d[17]), "+f"(d[18]), "+f"(d[19]), "+f"(d[20]), "+f"(d[21]), "+f"(d[22]), "+f"(d[23]),
          "+f"(d[24]), "+f"(d[25]), "+f"(d[26]), "+f"(d[27]), "+f"(d[28]), "+f"(d[29]), "+f"(d[30]), "+f"(d[31]),
          "+f"(d[32]), "+f"(d[33]), "+f"(d[34]), "+f"(d[35]), "+f"(d[36]), "+f"(d[37]), "+f"(d[38]), "+f"(d[39]),
          "+f"(d[40]), "+f"(d[41]), "+f"(d[42]), "+f"(d[43]), "+f"(d[44]), "+f"(d[45]), "+f"(d[46]), "+f"(d[47]),
          "+f"(d[48]), "+f"(d[49]), "+f"(d[50]), "+f"(d[51]), "+f"(d[52]), "+f"(d[53]), "+f"(d[54]), "+f"(d[55]),
          "+f"(d[56]), "+f"(d[57]), "+f"(d[58]), "+f"(d[59]), "+f"(d[60]), "+f"(d[61]), "+f"(d[62]), "+f"(d[63]),
          "+f"(d[64]), "+f"(d[65]), "+f"(d[66]), "+f"(d[67]), "+f"(d[68]), "+f"(d[69]), "+f"(d[70]), "+f"(d[71]),
          "+f"(d[72]), "+f"(d[73]), "+f"(d[74]), "+f"(d[75]), "+f"(d[76]), "+f"(d[77]), "+f"(d[78]), "+f"(d[79]),
          "+f"(d[80]), "+f"(d[81]), "+f"(d[82]), "+f"(d[83]), "+f"(d[84]), "+f"(d[85]), "+f"(d[86]), "+f"(d[87]),
          "+f"(d[88]), "+f"(d[89]), "+f"(d[90]), "+f"(d[91]), "+f"(d[92]), "+f"(d[93]), "+f"(d[94]), "+f"(d[95])
        : "l"(descA), "l"(descB), "r"(scaleD));
}

__device__ __forceinline__ void wgmma_n192_ss_tb_z(float (&d)[96], uint64_t descA, uint64_t descB) {
    asm volatile("{\n.reg .pred p;\nsetp.ne.b32 p, 0, 0;\n"
        "wgmma.mma_async.sync.aligned.m64n192k16.f32.bf16.bf16 {"
        "%0, %1, %2, %3, %4, %5, %6, %7, %8, %9, %10, %11, %12, %13, %14, %15, "
        "%16, %17, %18, %19, %20, %21, %22, %23, %24, %25, %26, %27, %28, %29, %30, %31, "
        "%32, %33, %34, %35, %36, %37, %38, %39, %40, %41, %42, %43, %44, %45, %46, %47, "
        "%48, %49, %50, %51, %52, %53, %54, %55, %56, %57, %58, %59, %60, %61, %62, %63, "
        "%64, %65, %66, %67, %68, %69, %70, %71, %72, %73, %74, %75, %76, %77, %78, %79, "
        "%80, %81, %82, %83, %84, %85, %86, %87, %88, %89, %90, %91, %92, %93, %94, %95}, "
        "%96, %97, p, 1, 1, 0, 1;\n}\n"
        : "=f"(d[0]), "=f"(d[1]), "=f"(d[2]), "=f"(d[3]), "=f"(d[4]), "=f"(d[5]), "=f"(d[6]), "=f"(d[7]),
          "=f"(d[8]), "=f"(d[9]), "=f"(d[10]), "=f"(d[11]), "=f"(d[12]), "=f"(d[13]), "=f"(d[14]), "=f"(d[15]),
          "=f"(d[16]), "=f"(d[17]), "=f"(d[18]), "=f"(d[19]), "=f"(d[20]), "=f"(d[21]), "=f"(d[22]), "=f"(d[23]),
          "=f"(d[24]), "=f"(d[25]), "=f"(d[26]), "=f"(d[27]), "=f"(d[28]), "=f"(d[29]), "=f"(d[30]), "=f"(d[31]),
          "=f"(d[32]), "=f"(d[33]), "=f"(d[34]), "=f"(d[35]), "=f"(d[36]), "=f"(d[37]), "=f"(d[38]), "=f"(d[39]),
          "=f"(d[40]), "=f"(d[41]), "=f"(d[42]), "=f"(d[43]), "=f"(d[44]), "=f"(d[45]), "=f"(d[46]), "=f"(d[47]),
          "=f"(d[48]), "=f"(d[49]), "=f"(d[50]), "=f"(d[51]), "=f"(d[52]), "=f"(d[53]), "=f"(d[54]), "=f"(d[55]),
          "=f"(d[56]), "=f"(d[57]), "=f"(d[58]), "=f"(d[59]), "=f"(d[60]), "=f"(d[61]), "=f"(d[62]), "=f"(d[63]),
          "=f"(d[64]), "=f"(d[65]), "=f"(d[66]), "=f"(d[67]), "=f"(d[68]), "=f"(d[69]), "=f"(d[70]), "=f"(d[71]),
          "=f"(d[72]), "=f"(d[73]), "=f"(d[74]), "=f"(d[75]), "=f"(d[76]), "=f"(d[77]), "=f"(d[78]), "=f"(d[79]),
          "=f"(d[80]), "=f"(d[81]), "=f"(d[82]), "=f"(d[83]), "=f"(d[84]), "=f"(d[85]), "=f"(d[86]), "=f"(d[87]),
          "=f"(d[88]), "=f"(d[89]), "=f"(d[90]), "=f"(d[91]), "=f"(d[92]), "=f"(d[93]), "=f"(d[94]), "=f"(d[95])
        : "l"(descA), "l"(descB));
}

__device__ __forceinline__ void wgmma_n160_ss_tb(float (&d)[80], uint64_t descA, uint64_t descB, int scaleD) {
    asm volatile("{\n.reg .pred p;\nsetp.ne.b32 p, %82, 0;\n"
        "wgmma.mma_async.sync.aligned.m64n160k16.f32.bf16.bf16 {"
        "%0, %1, %2, %3, %4, %5, %6, %7, %8, %9, %10, %11, %12, %13, %14, %15, "
        "%16, %17, %18, %19, %20, %21, %22, %23, %24, %25, %26, %27, %28, %29, %30, %31, "
        "%32, %33, %34, %35, %36, %37, %38, %39, %40, %41, %42, %43, %44, %45, %46, %47, "
        "%48, %49, %50, %51, %52, %53, %54, %55, %56, %57, %58, %59, %60, %61, %62, %63, "
        "%64, %65, %66, %67, %68, %69, %70, %71, %72, %73, %74, %75, %76, %77, %78, %79}, "
        "%80, %81, p, 1, 1, 0, 1;\n}\n"
        : "+f"(d[0]), "+f"(d[1]), "+f"(d[2]), "+f"(d[3]), "+f"(d[4]), "+f"(d[5]), "+f"(d[6]), "+f"(d[7]),
          "+f"(d[8]), "+f"(d[9]), "+f"(d[10]), "+f"(d[11]), "+f"(d[12]), "+f"(d[13]), "+f"(d[14]), "+f"(d[15]),
          "+f"(d[16]), "+f"(d[17]), "+f"(d[18]), "+f"(d[19]), "+f"(d[20]), "+f"(d[21]), "+f"(d[22]), "+f"(d[23]),
          "+f"(d[24]), "+f"(d[25]), "+f"(d[26]), "+f"(d[27]), "+f"(d[28]), "+f"(d[29]), "+f"(d[30]), "+f"(d[31]),
          "+f"(d[32]), "+f"(d[33]), "+f"(d[34]), "+f"(d[35]), "+f"(d[36]), "+f"(d[37]), "+f"(d[38]), "+f"(d[39]),
          "+f"(d[40]), "+f"(d[41]), "+f"(d[42]), "+f"(d[43]), "+f"(d[44]), "+f"(d[45]), "+f"(d[46]), "+f"(d[47]),
          "+f"(d[48]), "+f"(d[49]), "+f"(d[50]), "+f"(d[51]), "+f"(d[52]), "+f"(d[53]), "+f"(d[54]), "+f"(d[55]),
          "+f"(d[56]), "+f"(d[57]), "+f"(d[58]), "+f"(d[59]), "+f"(d[60]), "+f"(d[61]), "+f"(d[62]), "+f"(d[63]),
          "+f"(d[64]), "+f"(d[65]), "+f"(d[66]), "+f"(d[67]), "+f"(d[68]), "+f"(d[69]), "+f"(d[70]), "+f"(d[71]),
          "+f"(d[72]), "+f"(d[73]), "+f"(d[74]), "+f"(d[75]), "+f"(d[76]), "+f"(d[77]), "+f"(d[78]), "+f"(d[79])
        : "l"(descA), "l"(descB), "r"(scaleD));
}

__device__ __forceinline__ void wgmma_n64_ss(float (&d)[32], uint64_t descA, uint64_t descB, int scaleD) {
    asm volatile("{\n.reg .pred p;\nsetp.ne.b32 p, %34, 0;\n"
        "wgmma.mma_async.sync.aligned.m64n64k16.f32.bf16.bf16 {"
        "%0, %1, %2, %3, %4, %5, %6, %7, %8, %9, %10, %11, %12, %13, %14, %15, "
        "%16, %17, %18, %19, %20, %21, %22, %23, %24, %25, %26, %27, %28, %29, %30, %31}, "
        "%32, %33, p, 1, 1, 0, 0;\n}\n"
        : "+f"(d[0]), "+f"(d[1]), "+f"(d[2]), "+f"(d[3]), "+f"(d[4]), "+f"(d[5]), "+f"(d[6]), "+f"(d[7]),
          "+f"(d[8]), "+f"(d[9]), "+f"(d[10]), "+f"(d[11]), "+f"(d[12]), "+f"(d[13]), "+f"(d[14]), "+f"(d[15]),
          "+f"(d[16]), "+f"(d[17]), "+f"(d[18]), "+f"(d[19]), "+f"(d[20]), "+f"(d[21]), "+f"(d[22]), "+f"(d[23]),
          "+f"(d[24]), "+f"(d[25]), "+f"(d[26]), "+f"(d[27]), "+f"(d[28]), "+f"(d[29]), "+f"(d[30]), "+f"(d[31])
        : "l"(descA), "l"(descB), "r"(scaleD));
}

__device__ __forceinline__ void wgmma_n64_ss_z(float (&d)[32], uint64_t descA, uint64_t descB) {
    asm volatile("{\n.reg .pred p;\nsetp.ne.b32 p, 0, 0;\n"
        "wgmma.mma_async.sync.aligned.m64n64k16.f32.bf16.bf16 {"
        "%0, %1, %2, %3, %4, %5, %6, %7, %8, %9, %10, %11, %12, %13, %14, %15, "
        "%16, %17, %18, %19, %20, %21, %22, %23, %24, %25, %26, %27, %28, %29, %30, %31}, "
        "%32, %33, p, 1, 1, 0, 0;\n}\n"
        : "=f"(d[0]), "=f"(d[1]), "=f"(d[2]), "=f"(d[3]), "=f"(d[4]), "=f"(d[5]), "=f"(d[6]), "=f"(d[7]),
          "=f"(d[8]), "=f"(d[9]), "=f"(d[10]), "=f"(d[11]), "=f"(d[12]), "=f"(d[13]), "=f"(d[14]), "=f"(d[15]),
          "=f"(d[16]), "=f"(d[17]), "=f"(d[18]), "=f"(d[19]), "=f"(d[20]), "=f"(d[21]), "=f"(d[22]), "=f"(d[23]),
          "=f"(d[24]), "=f"(d[25]), "=f"(d[26]), "=f"(d[27]), "=f"(d[28]), "=f"(d[29]), "=f"(d[30]), "=f"(d[31])
        : "l"(descA), "l"(descB));
}

__device__ __forceinline__ void wgmma_n24_rs_tb(float (&d)[12], uint32_t a0, uint32_t a1, uint32_t a2, uint32_t a3, uint64_t descB, int scaleD) {
    asm volatile("{\n.reg .pred p;\nsetp.ne.b32 p, %17, 0;\n"
        "wgmma.mma_async.sync.aligned.m64n24k16.f32.bf16.bf16 {"
        "%0, %1, %2, %3, %4, %5, %6, %7, %8, %9, %10, %11}, "
        "{%12, %13, %14, %15}, %16, p, 1, 1, 1;\n}\n"
        : "+f"(d[0]), "+f"(d[1]), "+f"(d[2]), "+f"(d[3]), "+f"(d[4]), "+f"(d[5]), "+f"(d[6]), "+f"(d[7]),
          "+f"(d[8]), "+f"(d[9]), "+f"(d[10]), "+f"(d[11])
        : "r"(a0), "r"(a1), "r"(a2), "r"(a3), "l"(descB), "r"(scaleD));
}

__device__ __forceinline__ void cnt_signal(int idx) {
    asm volatile("fence.acq_rel.gpu;\nred.relaxed.gpu.global.add.u32 [%0], 1;"
                 ::"l"(g_cnt + idx * 32) : "memory");
}
__device__ __forceinline__ void cnt_wait(int idx, uint32_t target) {
    const uint32_t* p = g_cnt + idx * 32;
#pragma unroll 1
    for (uint32_t i = 0; i < (1u << 22); i++) {
        uint32_t v;
        asm volatile("ld.acquire.gpu.global.u32 %0, [%1];" : "=r"(v) : "l"(p) : "memory");
        if ((int32_t)(v - target) >= 0) break;
    }
    asm volatile("fence.proxy.async.global;" ::: "memory");
}
__device__ __forceinline__ void cluster_arrive() { asm volatile("barrier.cluster.arrive.release.aligned;" ::: "memory"); }
__device__ __forceinline__ void cluster_arrive_relaxed() { asm volatile("barrier.cluster.arrive.relaxed.aligned;" ::: "memory"); }
__device__ __forceinline__ void cluster_wait() { asm volatile("barrier.cluster.wait.acquire.aligned;" ::: "memory"); }
__device__ __forceinline__ void bulk_wait_read() { asm volatile("cp.async.bulk.wait_group.read 0;" ::: "memory"); }

__device__ __forceinline__ float gelu_half(float hx) {
    const float u = hx * fmaf(hx * hx, 8.f * 0.035677408136300125f, 2.f * 0.7978845608028654f);
    float t;
    asm("tanh.approx.f32 %0, %1;" : "=f"(t) : "f"(u));
    return fmaf(hx, t, hx);
}
__device__ __forceinline__ void release_stage(uint32_t bar, uint32_t peer, int lane) {
    if (lane == 0) { mbar_arrive(bar); mbar_arrive_cluster(bar, peer); }
}

constexpr int SM_RING = 163840;
constexpr int SM_Q = 0, SM_ZERO = 24576, SM_K = SM_ZERO + 3072, SM_V = SM_K + IMG_BYTES;
constexpr int G2_STAGE = 8192 + 20480;
constexpr int SM_MISC = 229376;
constexpr int SM_BIAS = SM_MISC, SM_RED = SM_BIAS + 384, SM_BAR = SM_RED + 128;
constexpr int B_A = 0, B_F1 = 10, B_E1 = 14, B_F2 = 18, B_E2 = 23, B_KV = 28, B_Q = 45, B_F3 = 47, B_E3 = 55, B_ST = 63, B_STAT = 65, B_AUX = 66, B_AUX2 = 67, B_DEAD = 68, B_HRD = 70, B_COUNT = 71;
constexpr int SM_EPOCH = SM_BAR + 568, SM_SAFE = SM_EPOCH + 4;
constexpr int SM_CS = SM_EPOCH + 8;
constexpr int SM_TOTAL = SM_CS + 1728;
static_assert(SM_TOTAL <= 232448, "shared memory budget");

struct Maps { CUtensorMap x, wqkv, w1, h, o, wo, w2; };

__device__ __forceinline__ uint32_t bf2_fma(uint32_t a, uint32_t b, uint32_t c) {
    uint32_t r;
    asm("fma.rn.bf16x2 %0, %1, %2, %3;" : "=r"(r) : "r"(a), "r"(b), "r"(c));
    return r;
}
__device__ __forceinline__ uint32_t lop_and_or(uint32_t a, uint32_t m, uint32_t o) {
    uint32_t r;
    asm("lop3.b32 %0, %1, %2, %3, 0xEA;" : "=r"(r) : "r"(a), "r"(m), "r"(o));
    return r;
}
struct ExpConst { uint32_t mask, slope; };
__device__ __forceinline__ ExpConst make_exp_const() {
    ExpConst k;
    asm volatile("mov.b32 %0, 0x007F007F;" : "=r"(k.mask));
    asm volatile("mov.b32 %0, 0x3EF83EF8;" : "=r"(k.slope));
    return k;
}
__device__ __forceinline__ uint32_t exp2_pair_fma(float t0, float t1, const ExpConst& k) {
    const uint32_t L = __byte_perm(__float_as_uint(t0), __float_as_uint(t1), 0x6521);
    const uint32_t g = lop_and_or(L, k.mask, 0x3F803F80u);
    const uint32_t u = bf2_fma(g, k.slope, 0xBF37BF37u);
    const uint32_t e = bf2_fma(u, u, 0xBD71BD71u);
    return bf2_fma(L, e, L);
}
template <int SHIFT>
__device__ __forceinline__ void exp_tile(const float (&s)[32], uint32_t (&p)[16], const ExpConst& k) {
#pragma unroll
    for (int b = 0; b < 8; b++) {
        if ((EMU_MASK >> (b + SHIFT)) & 1) {
            p[2 * b] = exp2_pair_fma(s[4 * b], s[4 * b + 1], k);
            p[2 * b + 1] = exp2_pair_fma(s[4 * b + 2], s[4 * b + 3], k);
        } else {
            p[2 * b] = pack_bf16(ex2(s[4 * b]), ex2(s[4 * b + 1]));
            p[2 * b + 1] = pack_bf16(ex2(s[4 * b + 2]), ex2(s[4 * b + 3]));
        }
    }
}

__device__ __forceinline__ void qk_tile(float (&s)[32], uint64_t dQ, uint64_t dQ2, uint64_t dK) {
    wg_fence();
    wgmma_n64_ss_z(s, dQ, dK);
    wgmma_n64_ss(s, dQ2, dK + 16, 1);
    wg_commit();
}
__device__ __forceinline__ void pv_tile(float (&o)[12], const uint32_t (&p)[16], uint64_t dV) {
    wg_fence();
#pragma unroll
    for (int ks = 0; ks < 4; ks++)
        wgmma_n24_rs_tb(o, p[4 * ks], p[4 * ks + 1], p[4 * ks + 2], p[4 * ks + 3], dV + ks * 48, 1);
    wg_commit();
}
__device__ __forceinline__ void store_o(const float (&o)[12], int h, int rbase, int lane) {
    const int g = lane >> 2, c = lane & 3;
    const bool odd = h & 1;
    const int lsrc = (lane & ~3) | (odd ? 0 : 2);
    const float i0 = 1.f / __shfl_sync(~0u, o[8], lsrc), i1 = 1.f / __shfl_sync(~0u, o[10], lsrc);
    __nv_bfloat16* dst = g_o + (size_t)(rbase + g) * DM + h * 20;
    const int d0 = (odd ? 4 : 0) + 2 * c, d1 = d0 + 8, d2 = odd ? 2 * c - 4 : 16 + 2 * c;
    *(uint32_t*)(dst + d0) = pack_bf16(o[0] * i0, o[1] * i0);
    *(uint32_t*)(dst + d1) = pack_bf16(o[4] * i0, o[5] * i0);
    *(uint32_t*)(dst + 8 * DM + d0) = pack_bf16(o[2] * i1, o[3] * i1);
    *(uint32_t*)(dst + 8 * DM + d1) = pack_bf16(o[6] * i1, o[7] * i1);
    if (odd ? (c >= 2) : (c < 2)) {
        *(uint32_t*)(dst + d2) = pack_bf16(o[8] * i0, o[9] * i0);
        *(uint32_t*)(dst + 8 * DM + d2) = pack_bf16(o[10] * i1, o[11] * i1);
    }
}

__device__ __forceinline__ void attn_rows_maxshift(uint32_t sK, uint32_t barKV, uint64_t dQ, uint64_t dQ2, int h, int rbase) {
    const int lane = threadIdx.x & 31;
    const uint64_t dK0 = make_desc(sK, 128, 384, 0), dV0 = make_desc(sK + IMG_BYTES, 384, 128, 0);
    float o[12], s[32];
    uint32_t p[16];
#pragma unroll
    for (int i = 0; i < 12; i++) o[i] = 0.f;
    float m0 = -3.0e38f, m1 = -3.0e38f;
    mbar_wait(barKV + 128, 0);
#pragma unroll 1
    for (int t = 0; t < 32; t++) {
        mbar_wait(barKV + (t >> 1) * 8, 0);
        qk_tile(s, dQ, dQ2, dK0 + t * 192);
        wg_wait<0>();
        fence_regs(s);
        const uint32_t mask = EMU_MASK >> ((t & 1) * 8);
        float n0 = m0, n1 = m1;
#pragma unroll
        for (int b = 0; b < 8; b++) {
            const bool emu = (mask >> b) & 1;
            const float f = emu ? 0.5f : 1.f, off = emu ? -383.00390625f : 0.f;
#pragma unroll
            for (int i = 0; i < 4; i++) s[4 * b + i] = fmaf(s[4 * b + i], f, off);
            n0 = fmaxf(n0, fmaxf(s[4 * b], s[4 * b + 1]));
            n1 = fmaxf(n1, fmaxf(s[4 * b + 2], s[4 * b + 3]));
        }
        n0 = fmaxf(n0, __shfl_xor_sync(~0u, n0, 1)); n0 = fmaxf(n0, __shfl_xor_sync(~0u, n0, 2));
        n1 = fmaxf(n1, __shfl_xor_sync(~0u, n1, 1)); n1 = fmaxf(n1, __shfl_xor_sync(~0u, n1, 2));
        const float c0 = ex2(m0 - n0), c1 = ex2(m1 - n1);
        m0 = n0; m1 = n1;
#pragma unroll
        for (int b = 0; b < 3; b++) { o[4 * b] *= c0; o[4 * b + 1] *= c0; o[4 * b + 2] *= c1; o[4 * b + 3] *= c1; }
#pragma unroll
        for (int b = 0; b < 8; b++) {
            p[2 * b] = pack_bf16(ex2(s[4 * b] - m0), ex2(s[4 * b + 1] - m0));
            p[2 * b + 1] = pack_bf16(ex2(s[4 * b + 2] - m1), ex2(s[4 * b + 3] - m1));
        }
        pv_tile(o, p, dV0 + (((t >> 1) + 7) & 15) * 384 + (t & 1) * 192);
        wg_wait<0>();
        fence_regs(o);
    }
    store_o(o, h, rbase, lane);
}

__global__ void __launch_bounds__(512, 1) __cluster_dims__(2, 1, 1)
k_fused(const __grid_constant__ Maps tm, const __nv_bfloat16* __restrict__ x, const uint8_t* __restrict__ wqkv,
        const uint8_t* __restrict__ w1, const uint8_t* __restrict__ w2, const uint8_t* __restrict__ wo,
        const __nv_bfloat16* __restrict__ b1, const __nv_bfloat16* __restrict__ b2, __nv_bfloat16* __restrict__ out) {
    extern __shared__ __align__(1024) uint8_t smem[];
    const uint32_t sb = smem_u32(smem);
    const uint32_t bar = sb + SM_BAR;
    const int warp = __shfl_sync(~0u, threadIdx.x >> 5, 0), lane = threadIdx.x & 31;
    const int wgi = warp >> 2, w4 = warp & 3, g = lane >> 2, c = lane & 3;
    const uint32_t rank = blockIdx.x & 1, peer = rank ^ 1;
    const int cl = blockIdx.x >> 1;
    const int cg = cl >> 3, rb = (cl & 7) * 2 + rank;

    if (threadIdx.x == 0) TL(0, 0);
    if (warp == 15 && lane < 4) prefetch_map(lane == 0 ? &tm.x : lane == 1 ? &tm.wqkv : lane == 2 ? &tm.w1 : &tm.h);
    if (elect_one()) {
#pragma unroll
        for (int j = 0; j < 5; j++) {
            const int i = warp * 5 + j;
            const int cnt = (i >= B_E1 && i < B_F2) || (i >= B_E2 && i < B_KV) ? 16
                          : (i >= B_E3 && i <= B_ST) || i == B_STAT || i == B_DEAD || i == B_DEAD + 1 ? 8 : i == B_ST + 1 || i == B_HRD ? 2 : i == B_AUX ? 4 : i == B_AUX2 ? 3 : 1;
            if (i < B_COUNT) mbar_init(bar + i * 8, cnt);
        }
        fence_barrier_init();
    }
    __syncthreads();
    if (threadIdx.x == 0) TL(0, 1);
    cluster_arrive_relaxed();
    cluster_wait();
    if (threadIdx.x == 0) TL(0, 3);

    {
        const uint32_t sB = sb + SM_RING;
        if (threadIdx.x == 0) TL(1, 0);
        if (wgi < 2) {
            reg_dealloc<56>();
            if (warp == 0) {
#pragma unroll 1
                for (int it = 0; it < 20; it++) {
                    const int s = it & 3;
                    const int kb = it < 2 ? it : (it & 1) ? (it + 1) >> 1 : 10;
                    if (it >= 4) mbar_wait(bar + (B_E1 + s) * 8, ((it >> 2) - 1) & 1);
                    else if (it > 0) __nanosleep(PACE_NS);
                    if (elect_one()) {
                        if (kb < 10) {
                            mbar_expect_tx(bar + (B_A + kb) * 8, 16384);
                            tma_load(sb + kb * 16384, &tm.x, kb * 64, rb * 128, bar + (B_A + kb) * 8);
                        }
                        const uint32_t dst = sB + s * 16384 + rank * 8192, fb = bar + (B_F1 + s) * 8;
                        const int c0 = cg * 240 + rank * 128;
                        mbar_expect_tx(fb, 16384);
                        tma_load_mc(dst, &tm.wqkv, c0, it * 32, fb, 3);
                        tma_load_mc(dst + 4096, &tm.wqkv, c0 + 64, it * 32, fb, 3);
                    }
                    __syncwarp();
                }
#pragma unroll 1
                for (int it = 0; it < 20; it++) {
                    const int s = it % 5;
                    if (it < 5) { if (it != 3) mbar_wait(bar + (B_E1 + (it == 4 ? 3 : it)) * 8, 0); }
                    else mbar_wait(bar + (B_E2 + s) * 8, ((it / 5) - 1) & 1);
                    if (elect_one()) {
                        const uint32_t dst = sB + s * 12288, fb = bar + (B_F2 + s) * 8;
                        mbar_expect_tx(fb, 12288);
                        if ((it & 1) == (int)rank) {
                            tma_load_mc(dst, &tm.w1, cg * 192, it * 32, fb, 3);
                            tma_load_mc(dst + 4096, &tm.w1, cg * 192 + 64, it * 32, fb, 3);
                        } else {
                            tma_load_mc(dst + 8192, &tm.w1, cg * 192 + 128, it * 32, fb, 3);
                        }
                    }
                    __syncwarp();
                }
            } else {
                const int ht = threadIdx.x - 32;
                if (ht == 160) *reinterpret_cast<volatile uint32_t*>(smem + SM_EPOCH) = *(volatile uint32_t*)&g_epoch;
                auto slab_sum = [&](const uint32_t* src, int pitch) {
                    float s0 = 0.f, s1 = 0.f;
                    uint32_t v[40];
#pragma unroll
                    for (int k = 0; k < 40; k++) v[k] = __ldg(src + k * pitch);
#pragma unroll
                    for (int k = 0; k < 40; k++) { s0 += bf_lo(v[k]); s1 += bf_hi(v[k]); }
                    return make_float2(s0, s1);
                };
                auto gather = [&](int idx) {
                    float s0 = 0.f, s1 = 0.f;
#pragma unroll
                    for (int r = 0; r < 16; r++) {
                        const float2 v = __ldcg(g_csp + r * 1728 + cg * 216 + idx);
                        s0 += v.x; s1 += v.y;
                    }
                    reinterpret_cast<float2*>(smem + SM_CS)[idx] = make_float2(s0, s1);
                };
                if (warp == 7) {
                    mbar_wait(bar + B_STAT * 8, 0);
                    if (elect_one()) cnt_signal(CNT_ST + rb);
                    __syncwarp();
                }
                if (ht < 120)
                    g_csp[rb * 1728 + cg * 216 + ht] = slab_sum(reinterpret_cast<const uint32_t*>(wqkv) + rb * 40 * 960 + cg * 120 + ht, 960);
                if (threadIdx.x == 64) IT(3, 0);
                if (threadIdx.x == 192) IT(3, 1);
                if (warp != 7) asm volatile("bar.sync 8, 192;" ::: "memory");
                const uint32_t epoch = *reinterpret_cast<volatile uint32_t*>(smem + SM_EPOCH);
                if (warp == 6) { if (elect_one()) cnt_signal(CNT_CS + cg); __syncwarp(); }

                if (threadIdx.x == 64) IT(3, 2);
                if (warp <= 4) {
                    if (lane == 0) { cnt_wait(CNT_CS + cg, (epoch + 1) * 16); cnt_wait(CNT_ST + rb, (epoch + 1) * 8); }
                    __syncwarp();
                    if (threadIdx.x == 64) IT(3, 4);
                    if (ht < 120) gather(ht);
                    __syncwarp();
                    if (threadIdx.x == 64) IT(3, 5);
                    if (lane == 0) mbar_arrive(bar + B_AUX * 8);
                }
                if (ht >= 128) {
                    g_csp[rb * 1728 + cg * 216 + 120 + (ht - 128)] = slab_sum(reinterpret_cast<const uint32_t*>(w1) + rb * 40 * 768 + cg * 96 + (ht - 128), 768);
                    reinterpret_cast<uint32_t*>(smem + SM_BIAS)[ht - 128] =
                        bf2_fma(__ldg(reinterpret_cast<const uint32_t*>(b1 + cg * 192) + (ht - 128)), 0x3F003F00u, 0x80008000u);
                    asm volatile("bar.sync 9, 96;" ::: "memory");
                    const uint32_t epoch2 = *reinterpret_cast<volatile uint32_t*>(smem + SM_EPOCH);
                    if (warp == 5) { if (elect_one()) cnt_signal(CNT_CS2 + cg); __syncwarp(); }
                    if (warp == 6 && elect_one()) {
                        prefetch_l2(w2 + blockIdx.x * 15360, 15360);
                        prefetch_l2(wo + blockIdx.x * 6400, 6400);
                    }
                    if (lane == 0) cnt_wait(CNT_CS2 + cg, (epoch2 + 1) * 16);
                    __syncwarp();
                    gather(120 + (ht - 128));
                    __syncwarp();
                    if (lane == 0) mbar_arrive(bar + B_AUX2 * 8);
                }
                if (warp == 4) {
                    mbar_wait(bar + B_ST * 8, 0);
                    if (elect_one()) cnt_signal(CNT_QKV + cg);
                    __syncwarp();
                }
                const int h = blockIdx.x >> 2, qb = blockIdx.x & 3;
                asm volatile("bar.sync 8, 224;" ::: "memory");
                const uint32_t ep = *reinterpret_cast<volatile uint32_t*>(smem + SM_EPOCH);
                if (lane == 0) {
                    cnt_wait(CNT_QKV + h / 12, (ep + 1) * 16);
                    cnt_wait(CNT_QKV + (32 + h) / 12, (ep + 1) * 16);
                    cnt_wait(CNT_QKV + (64 + h) / 12, (ep + 1) * 16);
                }
                __syncwarp();
                if (threadIdx.x == 64) TL(5, 0);
                {
                    float kmax = 0.f, qmax = 0.f;
#pragma unroll
                    for (int i = 0; i < 10; i++) if (ht + i * 224 < 2048) kmax = fmaxf(kmax, __ldcg(g_nrm + (32 + h) * SEQ + ht + i * 224));
#pragma unroll
                    for (int i = 0; i < 3; i++) if (ht + i * 224 < 512) qmax = fmaxf(qmax, __ldcg(g_nrm + h * SEQ + qb * 512 + ht + i * 224));
#pragma unroll
                    for (int o = 16; o; o >>= 1) {
                        kmax = fmaxf(kmax, __shfl_xor_sync(~0u, kmax, o));
                        qmax = fmaxf(qmax, __shfl_xor_sync(~0u, qmax, o));
                    }
                    float* red = reinterpret_cast<float*>(smem + SM_RED);
                    if (lane == 0) { red[warp] = kmax; red[8 + warp] = qmax; }
                    asm volatile("bar.sync 8, 224;" ::: "memory");
                    if (ht == 0) {
                        for (int w = 2; w < 8; w++) { kmax = fmaxf(kmax, red[w]); qmax = fmaxf(qmax, red[8 + w]); }
                        *reinterpret_cast<volatile uint32_t*>(smem + SM_SAFE) = kmax * qmax * 1.1f <= SAFE_BOUND * SAFE_BOUND;
                    }
                }
                const uint32_t barKV = bar + B_KV * 8;
                const uint8_t* gK = g_img + (size_t)(32 + h) * IMG_BYTES;
                const uint8_t* gV = g_img + (size_t)(64 + h) * IMG_BYTES;
                if (warp == 2) {
                    if (lane == 0) TL(5, 1);
                    mbar_wait(bar + B_DEAD * 8, 0);
                    if (lane == 0) TL(5, 2);
                    for (int i = lane; i < 192; i += 32) *reinterpret_cast<uint4*>(smem + SM_ZERO + i * 16) = make_uint4(0, 0, 0, 0);
                    fence_proxy_async();
                    __syncwarp();
                    if (elect_one()) {
                        asm volatile("fence.proxy.async.global;" ::: "memory");
                        const uint8_t* gQ = g_img + (size_t)h * IMG_BYTES + qb * 64 * 384;
                        mbar_expect_tx(barKV + 128, 6144);
                        bulk_load(sb + SM_K, gK, 6144, barKV + 128);
                        for (int p = 0; p < 2; p++) {
                            mbar_expect_tx(bar + (B_Q + p) * 8, 12288);
                            bulk_load(sb + SM_Q + p * 12288, gQ + p * 12288, 12288, bar + (B_Q + p) * 8);
                        }
                        for (int i = 0; i < 13; i++) {
                            mbar_expect_tx(barKV + i * 8, 12288);
                            bulk_load(sb + SM_K + (i + 1) * 6144, gK + (i + 1) * 6144, 6144, barKV + i * 8);
                        }
                    }
                    __syncwarp();
                    if (lane == 0) TL(5, 3);
                } else if (warp == 3) {
                    mbar_wait(bar + (B_DEAD + 1) * 8, 0);
                    if (elect_one()) {
                        asm volatile("fence.proxy.async.global;" ::: "memory");
                        for (int i = 0; i < 9; i++) bulk_load(sb + SM_V + (i + 7) * 6144, gV + i * 6144, 6144, barKV + i * 8);
                    }
                    __syncwarp();
                    if (lane == 0) TL(5, 4);
                }
            }
            asm volatile("bar.sync %0, 128;" ::"r"(wgi + 3) : "memory");
            reg_alloc<128>();
        } else {
            reg_alloc<200>();
            const int wi = wgi - 2;
            const int row0 = rb * 128 + wi * 64 + w4 * 16 + g;
            const uint32_t sAw = sb + wi * 8192;
            const int rbk = row0 >> 3, hs0 = cg * 12;
            {
                const int srow = rb * 128 + cg * 16 + (warp - 8) * 2 + (lane >> 4);
                uint4 xv[5];
#pragma unroll
                for (int i = 0; i < 5; i++) xv[i] = __ldg(reinterpret_cast<const uint4*>(x + (size_t)srow * DM) + (lane & 15) + 16 * i);
                float sm = 0.f;
#pragma unroll
                for (int i = 0; i < 5; i++)
                    sm += ((bf_lo(xv[i].x) + bf_hi(xv[i].x)) + (bf_lo(xv[i].y) + bf_hi(xv[i].y))) +
                          ((bf_lo(xv[i].z) + bf_hi(xv[i].z)) + (bf_lo(xv[i].w) + bf_hi(xv[i].w)));
#pragma unroll
                for (int o = 8; o; o >>= 1) sm += __shfl_xor_sync(~0u, sm, o);
                const float mu = sm * (1.f / DM);
                float q0 = 0.f, q1 = 0.f;
#pragma unroll
                for (int i = 0; i < 5; i++) {
                    const uint32_t w[4] = {xv[i].x, xv[i].y, xv[i].z, xv[i].w};
#pragma unroll
                    for (int j = 0; j < 4; j++) {
                        const float d0 = bf_lo(w[j]) - mu, d1 = bf_hi(w[j]) - mu;
                        q0 = fmaf(d0, d0, q0); q1 = fmaf(d1, d1, q1);
                    }
                }
                float q = q0 + q1;
#pragma unroll
                for (int o = 8; o; o >>= 1) q += __shfl_xor_sync(~0u, q, o);
                const float var = q * (1.f / DM);
                const float r1 = rsqrtf(var + LN_EPS);
                const float r2 = rsqrtf(var * r1 * r1 + LN_EPS);
                if ((lane & 15) == 0) g_stat[srow] = make_float4(mu, r1, r1 * r2, 0.f);
                __syncwarp();
                if (lane == 0) mbar_arrive(bar + B_STAT * 8);
            }
            float accA[100], accB[20];
            const uint64_t dA0 = make_desc(sAw, 16, 1024, 1), dB0 = make_desc(sB, 4096, 1024, 1);
#pragma unroll 2
            for (int it = 0; it < 20; it++) {
                const int s = it & 3;
                if (!(it & 1)) mbar_wait(bar + (B_A + (it >> 1)) * 8, 0);
                if (threadIdx.x == 256 && it == 0) TL(0, 2);
                if (threadIdx.x == 256) IT(0, it);
                mbar_wait(bar + (B_F1 + s) * 8, (it >> 2) & 1);
                if (threadIdx.x == 256) IT(1, it);
                const uint64_t dA = dA0 + (it >> 1) * 1024 + (it & 1) * 4, dB = dB0 + s * 1024;
                wg_fence();
                wgmma_n40_ss_tb(accB, dA, dB + 769, it > 0);
                wgmma_n40_ss_tb(accB, dA + 2, dB + 769 + 128, 1);
                wgmma_n200_ss_tb(accA, dA, dB, it > 0);
                wgmma_n200_ss_tb(accA, dA + 2, dB + 128, 1);
                wg_commit();
                if (it > 0) { wg_wait<1>(); release_stage(bar + (B_E1 + ((it - 1) & 3)) * 8, peer, lane); }
            }
            if (threadIdx.x == 256) IT(2, 0);
            mbar_wait(bar + B_AUX * 8, 0);
            if (threadIdx.x == 256) IT(2, 1);
            const float4 st0 = __ldcg(g_stat + row0), st1 = __ldcg(g_stat + row0 + 8);
            wg_wait<0>();
            release_stage(bar + (B_E1 + 3) * 8, peer, lane);
            fence_regs(accA);
            fence_regs(accB);
            if (threadIdx.x == 256) TL(1, 1);
            const float2* cs = reinterpret_cast<const float2*>(smem + SM_CS) + c;
            uint8_t* img = g_img + (size_t)hs0 * IMG_BYTES + rbk * 384 + g * 16 + c * 4;
            const bool emu0 = (EMU_MASK >> (rbk & 15)) & 1, emu1 = (EMU_MASK >> ((rbk + 1) & 15)) & 1;
            const bool low = c < 2;
            uint32_t pk[60];
#pragma unroll
            for (int m = 0; m < 6; m++) {
                const int which = (hs0 + 2 * m) >> 5;
                const float m0 = st0.y * (which == 0 ? QSCALE : (which == 1 && emu0) ? 2.f : 1.f);
                const float m1 = st1.y * (which == 0 ? QSCALE : (which == 1 && emu1) ? 2.f : 1.f);
                const float d0 = -st0.x * m0, d1 = -st1.x * m1;
                const float* a = m < 5 ? &accA[20 * m] : accB;
#pragma unroll
                for (int b = 0; b < 5; b++) {
                    const float2 cv = cs[(5 * m + b) * 4];
                    pk[10 * m + 2 * b] = pack_bf16(fmaf(a[4 * b], m0, d0 * cv.x), fmaf(a[4 * b + 1], m0, d0 * cv.y));
                    pk[10 * m + 2 * b + 1] = pack_bf16(fmaf(a[4 * b + 2], m1, d1 * cv.x), fmaf(a[4 * b + 3], m1, d1 * cv.y));
                }
            }
            const float r20 = 0.5f * st0.z, r21 = 0.5f * st1.z, e20 = -st0.x * r20, e21 = -st1.x * r21;
            if (threadIdx.x == 256) IT(2, 2);
            float acc2[96];
#pragma unroll
            for (int it = 0; it < 20; it++) {
                const int s = it % 5;
                if (threadIdx.x == 256) IT(0, 20 + it);
                mbar_wait(bar + (B_F2 + s) * 8, (it / 5) & 1);
                if (threadIdx.x == 256) IT(1, 20 + it);
                wg_fence();
                const uint64_t dA = make_desc(sAw + (it >> 1) * 16384 + (it & 1) * 64, 16, 1024, 1);
                const uint64_t dB = make_desc(sB + s * 12288, 4096, 1024, 1);
                if (it == 0) wgmma_n192_ss_tb_z(acc2, dA, dB); else wgmma_n192_ss_tb(acc2, dA, dB, 1);
                wgmma_n192_ss_tb(acc2, dA + 2, dB + 128, 1);
                wg_commit();
                if (it > 0) {
                    wg_wait<1>();
                    if (it <= 15) release_stage(bar + (B_E2 + (it - 1) % 5) * 8, peer, lane);
                    if (it == 14 && lane == 0) mbar_arrive(bar + B_DEAD * 8);
                }
                if (it < 12) {
                    const int m = it / 2, part = it % 2;
                    const int hs = hs0 + 2 * m, which = hs >> 5;
                    const uint32_t* a = pk + 10 * m;
                    uint8_t* pe = img + (2 * m) * IMG_BYTES;
                    uint8_t* po = pe + IMG_BYTES;
                    if (part == 0) {
                        const uint32_t padv = which == 0 ? 0x3F803F80u : which == 1 ? 0xBFFF4440u : 0x00003F80u;
                        const uint32_t p0 = ((c & 1) || (which == 1 && !emu0)) ? 0u : padv;
                        const uint32_t p1 = ((c & 1) || (which == 1 && !emu1)) ? 0u : padv;
                        *(uint32_t*)(pe) = a[0];
                        *(uint32_t*)(pe + 128) = a[2];
                        *(uint32_t*)(pe + 256) = low ? a[4] : p0;
                        *(uint32_t*)(pe + 384) = a[1];
                        *(uint32_t*)(pe + 512) = a[3];
                        *(uint32_t*)(pe + 640) = low ? a[5] : p1;
                        *(uint32_t*)(po + 256) = low ? p0 : a[4];
                        *(uint32_t*)(po + 640) = low ? p1 : a[5];
                    } else {
                        *(uint32_t*)(po) = a[6];
                        *(uint32_t*)(po + 128) = a[8];
                        *(uint32_t*)(po + 384) = a[7];
                        *(uint32_t*)(po + 512) = a[9];
                        if (which < 2) {
                            const uint32_t u0 = bf2_fma(a[4], a[4], 0u), u1 = bf2_fma(a[5], a[5], 0u);
                            const uint32_t pe0 = bf2_fma(a[0], a[0], bf2_fma(a[2], a[2], low ? u0 : 0u));
                            const uint32_t pe1 = bf2_fma(a[1], a[1], bf2_fma(a[3], a[3], low ? u1 : 0u));
                            const uint32_t po0 = bf2_fma(a[6], a[6], bf2_fma(a[8], a[8], low ? 0u : u0));
                            const uint32_t po1 = bf2_fma(a[7], a[7], bf2_fma(a[9], a[9], low ? 0u : u1));
                            const float e0 = bf_lo(pe0) + bf_hi(pe0), e1 = bf_lo(pe1) + bf_hi(pe1);
                            const float o0 = bf_lo(po0) + bf_hi(po0), o1 = bf_lo(po1) + bf_hi(po1);
                            const bool b0 = c & 1, b1_ = c & 2;
                            const float x0 = (b0 ? e1 : e0) + __shfl_xor_sync(~0u, b0 ? e0 : e1, 1);
                            const float x1 = (b0 ? o1 : o0) + __shfl_xor_sync(~0u, b0 ? o0 : o1, 1);
                            float y = (b1_ ? x1 : x0) + __shfl_xor_sync(~0u, b1_ ? x0 : x1, 2);
                            if (which == 1 && (b0 ? emu1 : emu0)) y *= 0.25f;
                            g_nrm[(hs + (c >> 1)) * SEQ + row0 + (c & 1) * 8] = y;
                        }
                    }
                    if (it == 11) { __syncwarp(); if (lane == 0) mbar_arrive(bar + B_ST * 8); }
                }
            }
            wg_wait<0>();
            fence_regs(acc2);
            if (lane == 0) mbar_arrive(bar + (B_DEAD + 1) * 8);
            if (threadIdx.x == 256) TL(1, 2);
            mbar_wait(bar + B_AUX2 * 8, 0);
            if (threadIdx.x == 256) TL(4, 0);
            const uint32_t* bias = reinterpret_cast<const uint32_t*>(smem + SM_BIAS) + c;
            const int mrow = w4 * 16 + (lane & 15);
            const uint32_t stage = sAw + 7 * 16384;
            const uint32_t st_row = stage + mrow * 128;
#pragma unroll
            for (int j = 0; j < 24; j += 2) {
                const uint32_t bA = bias[j * 4], bB = bias[j * 4 + 4];
                const float2 cA = cs[(30 + j) * 4], cB = cs[(31 + j) * 4];
                const float* a = acc2 + j * 4;
                const uint32_t r00 = pack_bf16(gelu_half(fmaf(a[0], r20, fmaf(e20, cA.x, bf_lo(bA)))), gelu_half(fmaf(a[1], r20, fmaf(e20, cA.y, bf_hi(bA)))));
                const uint32_t r10 = pack_bf16(gelu_half(fmaf(a[2], r21, fmaf(e21, cA.x, bf_lo(bA)))), gelu_half(fmaf(a[3], r21, fmaf(e21, cA.y, bf_hi(bA)))));
                const uint32_t r01 = pack_bf16(gelu_half(fmaf(a[4], r20, fmaf(e20, cB.x, bf_lo(bB)))), gelu_half(fmaf(a[5], r20, fmaf(e20, cB.y, bf_hi(bB)))));
                const uint32_t r11 = pack_bf16(gelu_half(fmaf(a[6], r21, fmaf(e21, cB.x, bf_lo(bB)))), gelu_half(fmaf(a[7], r21, fmaf(e21, cB.y, bf_hi(bB)))));
                const int chunk = (j & 7) + (lane >> 4);
                stmatrix_x4(st_row + (j >> 3) * 16384 + ((chunk ^ (mrow & 7)) << 4), r00, r10, r01, r11);
            }
            if (threadIdx.x == 256) TL(4, 1);
            fence_proxy_async();
            asm volatile("bar.sync %0, 128;" ::"r"(wgi + 3) : "memory");
            if (w4 == 0 && lane == 0) {
#pragma unroll
                for (int b = 0; b < 3; b++) tma_store(&tm.h, stage + b * 16384, cg * 192 + b * 64, rb * 128 + wi * 64);
                bulk_commit();
                if (threadIdx.x == 256) TL(4, 2);
            }
            __syncwarp();
            reg_dealloc<128>();
        }
        __syncthreads();
        if (threadIdx.x == 0) TL(1, 3);
    }

    {
        const int h = blockIdx.x >> 2, qb = blockIdx.x & 3;
        const uint32_t sK = sb + SM_K, sV = sb + SM_V, barKV = bar + B_KV * 8;
        if (threadIdx.x == 0) TL(2, 0);
        auto late_tiles = [&](int step) {
            if (step == 0) {
                if ((warp == 8 || warp == 12) && lane == 0) { bulk_wait_read(); mbar_arrive(bar + B_HRD * 8); }
            } else if (warp == 5) {
                mbar_wait(bar + B_HRD * 8, 0);
                if (elect_one()) {
                    asm volatile("fence.proxy.async.global;" ::: "memory");
                    const uint8_t* gK = g_img + (size_t)(32 + h) * IMG_BYTES;
                    const uint8_t* gV = g_img + (size_t)(64 + h) * IMG_BYTES;
                    for (int i = 9; i < 16; i++) {
                        if (i >= 13) mbar_expect_tx(barKV + i * 8, i < 15 ? 12288 : 6144);
                        bulk_load(sV + ((i + 7) & 15) * 6144, gV + i * 6144, 6144, barKV + i * 8);
                        if (i >= 13 && i < 15) bulk_load(sK + (i + 1) * 6144, gK + (i + 1) * 6144, 6144, barKV + i * 8);
                    }
                }
            }
            __syncwarp();
        };
        const bool safe = __all_sync(~0u, *reinterpret_cast<volatile uint32_t*>(smem + SM_SAFE) != 0);
        if (threadIdx.x == 0) TL(2, 1);
        const uint64_t dK0 = make_desc(sK, 128, 384, 0), dV0 = make_desc(sV, 384, 128, 0);
        auto publish_h = [&]() {
            if (warp == 8 || warp == 12) {
                if (lane == 0) { bulk_wait_all(); cnt_signal(CNT_H + rb); }
                __syncwarp();
            }
        };
        if (!safe) {
            late_tiles(0);
            late_tiles(1);
#pragma unroll 1
            for (int pass = 0; pass < 2; pass++) {
                const uint32_t sQ = sb + SM_Q + pass * 12288 + wgi * 3072;
                mbar_wait(bar + (B_Q + pass) * 8, 0);
                attn_rows_maxshift(sK, barKV, make_desc(sQ, 128, 384, 0), make_desc(sQ + 256, sb + SM_ZERO - (sQ + 256), 384, 0), h,
                                   qb * 512 + pass * 256 + wgi * 64 + w4 * 16);
                if (pass == 0) publish_h();
            }
        } else {
            const ExpConst kc = make_exp_const();
#pragma unroll 1
            for (int pass = 0; pass < 2; pass++) {
                const int rbase = qb * 512 + pass * 256 + wgi * 64 + w4 * 16;
                const uint32_t sQ = sb + SM_Q + pass * 12288 + wgi * 3072;
                const uint64_t dQ = make_desc(sQ, 128, 384, 0), dQ2 = make_desc(sQ + 256, sb + SM_ZERO - (sQ + 256), 384, 0);
                float o[12], sa[32], sc[32];
                uint32_t p[16];
#pragma unroll
                for (int i = 0; i < 12; i++) o[i] = 0.f;
                fence_regs(o);
                mbar_wait(bar + (B_Q + pass) * 8, 0);
                mbar_wait(barKV + 128, 0);
                qk_tile(sa, dQ, dQ2, dK0);
                wg_wait<0>();
                fence_regs(sa);
                uint64_t dK = dK0, dV = dV0 + 7 * 384;
                uint32_t bj = barKV;
#pragma unroll 1
                for (int j = 0; j < 16; j++) {
                    mbar_wait(bj, 0);
                    if (pass == 0 && (j == 1 || j == 3)) late_tiles(j >> 1);
                    qk_tile(sc, dQ, dQ2, dK + 192);
                    wg_wait<1>();
                    exp_tile<0>(sa, p, kc);
                    pv_tile(o, p, dV);
                    wg_wait<1>();
                    fence_regs(sc);
                    mbar_wait(bj, 0);
                    qk_tile(sa, dQ, dQ2, dK + 384);
                    wg_wait<1>();
                    exp_tile<8>(sc, p, kc);
                    pv_tile(o, p, dV + 192);
                    wg_wait<1>();
                    fence_regs(sa);
                    dK += 384; dV = j == 8 ? dV0 : dV + 384; bj += 8;
                }
                wg_wait<0>();
                fence_regs(o);
                store_o(o, h, rbase, lane);
                if (threadIdx.x == 0) TL(2, 2 + pass);
                if (pass == 0) publish_h();
            }
        }
        __syncthreads();
        if (threadIdx.x == 64) cnt_signal(CNT_O + qb);
        cluster_arrive_relaxed();
    }

    {
        const uint32_t epoch = *reinterpret_cast<volatile uint32_t*>(smem + SM_EPOCH);
        const int ct = cl & 3, rt = (cl >> 2) * 2 + rank;
        if (threadIdx.x == 0) TL(3, 0);
        const int orow = threadIdx.x >> 3, oseg = threadIdx.x & 7;
        const size_t ooff = (size_t)(rt * 64 + orow) * DM + ct * 160 + oseg * 20;
        uint2 xr[5], br[5];
#pragma unroll
        for (int i = 0; i < 5; i++) {
            xr[i] = __ldg(reinterpret_cast<const uint2*>(x + ooff) + i);
            br[i] = __ldg(reinterpret_cast<const uint2*>(b2 + ct * 160 + oseg * 20) + i);
        }
        cluster_wait();
        float* stg = reinterpret_cast<float*>(smem);
        if (warp == 4) {
            if (elect_one()) { prefetch_map(&tm.h); prefetch_map(&tm.o); prefetch_map(&tm.w2); prefetch_map(&tm.wo); cnt_wait(CNT_H + (rt >> 1), (epoch + 1) * 16); }
            __syncwarp();
#pragma unroll 1
            for (int kb = 0; kb < 34; kb++) {
                const int s = kb & 7;
                if (kb >= 8) mbar_wait(bar + (B_E3 + s) * 8, ((kb >> 3) - 1) & 1);
                if (elect_one()) {
                    if (kb == 24) { cnt_wait(CNT_O + (rt >> 3), (epoch + 1) * 32); TL(3, 1); }
                    const uint32_t dst = sb + s * G2_STAGE, fb = bar + (B_F3 + s) * 8;
                    const CUtensorMap* mA = kb < 24 ? &tm.h : &tm.o;
                    const CUtensorMap* mB = kb < 24 ? &tm.w2 : &tm.wo;
                    const int k0 = (kb < 24 ? kb : kb - 24) * 64;
                    mbar_expect_tx(fb, G2_STAGE);
                    tma_load(dst, mA, k0, rt * 64, fb);
                    const int first = ((kb & 1) == (int)rank) ? 0 : 3, last = ((kb & 1) == (int)rank) ? 3 : 5;
                    for (int b = first; b < last; b++) tma_load_mc(dst + 8192 + b * 4096, mB, ct * 160 + b * 32, k0, fb, 3);
                }
                __syncwarp();
            }
        } else if (wgi == 0) {
            float acc[80];
#pragma unroll 1
            for (int kb = 0; kb < 34; kb++) {
                const int s = kb & 7;
                mbar_wait(bar + (B_F3 + s) * 8, (kb >> 3) & 1);
                wg_fence();
                const uint64_t dA = make_desc(sb + s * G2_STAGE, 16, 1024, 1);
                const uint64_t dB = make_desc(sb + s * G2_STAGE + 8192, 4096, 512, 2);
#pragma unroll
                for (int kk = 0; kk < 4; kk++) wgmma_n160_ss_tb(acc, dA + kk * 2, dB + kk * 64, (kb | kk) != 0);
                wg_commit();
                if (kb > 0) {
                    wg_wait<1>();
                    if (kb <= 26) release_stage(bar + (B_E3 + ((kb - 1) & 7)) * 8, peer, lane);
                }
            }
            wg_wait<0>();
            fence_regs(acc);
            if (threadIdx.x == 0) TL(3, 2);
            const int r = w4 * 16 + g;
#pragma unroll
            for (int j = 0; j < 20; j++) {
                *reinterpret_cast<float2*>(stg + r * 168 + j * 8 + 2 * c) = make_float2(acc[4 * j], acc[4 * j + 1]);
                *reinterpret_cast<float2*>(stg + (r + 8) * 168 + j * 8 + 2 * c) = make_float2(acc[4 * j + 2], acc[4 * j + 3]);
            }
        }
        __syncthreads();
        const float4* sp = reinterpret_cast<const float4*>(stg + orow * 168 + oseg * 20);
#pragma unroll
        for (int i = 0; i < 5; i++) {
            const float4 a = sp[i];
            uint2 w;
            w.x = pack_bf16(a.x + bf_lo(br[i].x) + bf_lo(xr[i].x), a.y + bf_hi(br[i].x) + bf_hi(xr[i].x));
            w.y = pack_bf16(a.z + bf_lo(br[i].y) + bf_lo(xr[i].y), a.w + bf_hi(br[i].y) + bf_hi(xr[i].y));
            reinterpret_cast<uint2*>(out + ooff)[i] = w;
        }
        if (blockIdx.x == 0 && threadIdx.x == 0) g_epoch = epoch + 1;
        if (threadIdx.x == 0) TL(3, 3);
    }
    cluster_arrive_relaxed();
    cluster_wait();
}

typedef CUresult (*EncodeTiledFn)(CUtensorMap*, CUtensorMapDataType, cuuint32_t, void*, const cuuint64_t*,
                                  const cuuint64_t*, const cuuint32_t*, const cuuint32_t*, CUtensorMapInterleave,
                                  CUtensorMapSwizzle, CUtensorMapL2promotion, CUtensorMapFloatOOBfill);

CUtensorMap make_map(EncodeTiledFn enc, const void* ptr, int rows, int cols, int box_rows, int box_cols,
                     CUtensorMapSwizzle swz) {
    CUtensorMap m;
    cuuint64_t gd[2] = {(cuuint64_t)cols, (cuuint64_t)rows};
    cuuint64_t gs[1] = {(cuuint64_t)cols * 2};
    cuuint32_t bd[2] = {(cuuint32_t)box_cols, (cuuint32_t)box_rows};
    cuuint32_t es[2] = {1, 1};
    enc(&m, CU_TENSOR_MAP_DATA_TYPE_BFLOAT16, 2, const_cast<void*>(ptr), gd, gs, bd, es, CU_TENSOR_MAP_INTERLEAVE_NONE,
        swz, CU_TENSOR_MAP_L2_PROMOTION_L2_128B, CU_TENSOR_MAP_FLOAT_OOB_FILL_NONE);
    return m;
}

}

extern "C" void kernel_launch(void* const* d_in, const int* in_sizes, int n_in, void* d_out, int out_size) {
    (void)in_sizes; (void)n_in; (void)out_size;
    const __nv_bfloat16* x = (const __nv_bfloat16*)d_in[0];
    const __nv_bfloat16* wqkv = (const __nv_bfloat16*)d_in[1];
    const __nv_bfloat16* wo = (const __nv_bfloat16*)d_in[2];
    const __nv_bfloat16* w1 = (const __nv_bfloat16*)d_in[4];
    const __nv_bfloat16* b1 = (const __nv_bfloat16*)d_in[5];
    const __nv_bfloat16* w2 = (const __nv_bfloat16*)d_in[6];
    const __nv_bfloat16* b2 = (const __nv_bfloat16*)d_in[7];
    __nv_bfloat16* out = (__nv_bfloat16*)d_out;

    static EncodeTiledFn enc = nullptr;
    static void *p_h, *p_o;
    if (!enc) {
        cudaDriverEntryPointQueryResult qr;
        cudaGetDriverEntryPoint("cuTensorMapEncodeTiled", (void**)&enc, cudaEnableDefault, &qr);
        cudaGetSymbolAddress(&p_h, g_h);
        cudaGetSymbolAddress(&p_o, g_o);
        cudaFuncSetAttribute(k_fused, cudaFuncAttributeMaxDynamicSharedMemorySize, SM_TOTAL);
    }
    Maps tm;
    tm.x = make_map(enc, x, SEQ, DM, 128, 64, CU_TENSOR_MAP_SWIZZLE_128B);
    tm.wqkv = make_map(enc, wqkv, DM, 3 * DM, 32, 64, CU_TENSOR_MAP_SWIZZLE_128B);
    tm.w1 = make_map(enc, w1, DM, FF, 32, 64, CU_TENSOR_MAP_SWIZZLE_128B);
    tm.h = make_map(enc, p_h, SEQ, FF, 64, 64, CU_TENSOR_MAP_SWIZZLE_128B);
    tm.o = make_map(enc, p_o, SEQ, DM, 64, 64, CU_TENSOR_MAP_SWIZZLE_128B);
    tm.wo = make_map(enc, wo, DM, DM, 64, 32, CU_TENSOR_MAP_SWIZZLE_64B);
    tm.w2 = make_map(enc, w2, FF, DM, 64, 32, CU_TENSOR_MAP_SWIZZLE_64B);
    k_fused<<<128, 512, SM_TOTAL, cudaStreamPerThread>>>(tm, x, (const uint8_t*)wqkv, (const uint8_t*)w1, (const uint8_t*)w2,
                                                         (const uint8_t*)wo, b1, b2, out);
}
```

```cpp
#include <cuda_runtime.h>
#include <cuda_bf16.h>
#include <cuda.h>
#include <stdint.h>

namespace {

constexpr int SEQ = 2048, DM = 640, FF = 1536;
constexpr float LN_EPS = 1e-5f;

constexpr int IMG_BYTES = 256 * 384;
constexpr uint32_t EMU_MASK = 0xD5D5u;
constexpr float SAFE_BOUND = 80.0f;
#define XV_IT 1
#define PACE_NS 200
constexpr float QSCALE = 0.22360679774997896f * 1.4426950408889634f;

__device__ float4 g_stat[SEQ];
__device__ float2 g_csp[16 * 1728];
__device__ __align__(1024) uint8_t g_img[96 * IMG_BYTES + 1024];
__device__ float g_nrm[64 * SEQ];
__device__ __align__(1024) __nv_bfloat16 g_h[SEQ * FF];
__device__ __align__(1024) __nv_bfloat16 g_o[SEQ * DM];
constexpr int CNT_ST = 0, CNT_QKV = 16, CNT_H = 24, CNT_O = 40, CNT_CS = 44, CNT_CS2 = 52;
__device__ uint32_t g_cnt[60 * 32];
__device__ uint32_t g_epoch;

#define TL(kern, slot) do { } while (0)
#define IT(row, i) do { } while (0)

__device__ __forceinline__ uint32_t smem_u32(const void* p) { return (uint32_t)__cvta_generic_to_shared(p); }
__device__ __forceinline__ void mbar_init(uint32_t bar, int cnt) {
    asm volatile("mbarrier.init.shared::cta.b64 [%0], %1;" ::"r"(bar), "r"(cnt));
}
__device__ __forceinline__ void mbar_expect_tx(uint32_t bar, uint32_t bytes) {
    asm volatile("mbarrier.arrive.expect_tx.shared::cta.b64 _, [%0], %1;" ::"r"(bar), "r"(bytes) : "memory");
}
__device__ __forceinline__ void mbar_wait(uint32_t bar, uint32_t parity) {
    asm volatile("{\n.reg .pred p;\n.reg .u32 n;\nmov.u32 n, 0;\n"
                 "WAIT_LOOP:\nmbarrier.try_wait.parity.shared::cta.b64 p, [%0], %1;\n@p bra WAIT_DONE;\n"
                 "add.u32 n, n, 1;\nsetp.lt.u32 p, n, 4194304;\n@p bra WAIT_LOOP;\nWAIT_DONE:\n}"
                 ::"r"(bar), "r"(parity) : "memory");
}
__device__ __forceinline__ void mbar_arrive(uint32_t bar) {
    asm volatile("mbarrier.arrive.shared::cta.b64 _, [%0];" ::"r"(bar) : "memory");
}
__device__ __forceinline__ void mbar_arrive_cluster(uint32_t bar, uint32_t cta) {
    asm volatile("{\n.reg .b32 ra;\nmapa.shared::cluster.u32 ra, %0, %1;\n"
                 "mbarrier.arrive.shared::cluster.b64 _, [ra];\n}" ::"r"(bar), "r"(cta) : "memory");
}
__device__ __forceinline__ void fence_barrier_init() { asm volatile("fence.mbarrier_init.release.cluster;" ::: "memory"); }
__device__ __forceinline__ void fence_proxy_async() { asm volatile("fence.proxy.async.shared::cta;" ::: "memory"); }
__device__ __forceinline__ void cluster_sync() {
    asm volatile("barrier.cluster.arrive.release.aligned;\nbarrier.cluster.wait.acquire.aligned;" ::: "memory");
}
__device__ __forceinline__ bool elect_one() {
    uint32_t pred;
    asm volatile("{\n.reg .pred p;\nelect.sync _|p, 0xFFFFFFFF;\nselp.b32 %0, 1, 0, p;\n}" : "=r"(pred));
    return pred != 0;
}
__device__ __forceinline__ void pdl_launch() { asm volatile("griddepcontrol.launch_dependents;" ::: "memory"); }
__device__ __forceinline__ void pdl_wait() { asm volatile("griddepcontrol.wait;" ::: "memory"); }
__device__ __forceinline__ void prefetch_map(const CUtensorMap* m) {
    asm volatile("prefetch.tensormap [%0];" ::"l"(m) : "memory");
}
__device__ __forceinline__ void tma_load(uint32_t dst, const CUtensorMap* m, int c0, int c1, uint32_t bar) {
    asm volatile("cp.async.bulk.tensor.2d.shared::cluster.global.mbarrier::complete_tx::bytes [%0], [%1, {%3, %4}], [%2];"
                 ::"r"(dst), "l"(m), "r"(bar), "r"(c0), "r"(c1) : "memory");
}
__device__ __forceinline__ void tma_load_mc(uint32_t dst, const CUtensorMap* m, int c0, int c1, uint32_t bar, uint16_t mask) {
    asm volatile("cp.async.bulk.tensor.2d.shared::cluster.global.mbarrier::complete_tx::bytes.multicast::cluster"
                 " [%0], [%1, {%3, %4}], [%2], %5;"
                 ::"r"(dst), "l"(m), "r"(bar), "r"(c0), "r"(c1), "h"(mask) : "memory");
}
__device__ __forceinline__ void tma_store(const CUtensorMap* m, uint32_t src, int c0, int c1) {
    asm volatile("cp.async.bulk.tensor.2d.global.shared::cta.bulk_group [%0, {%2, %3}], [%1];"
                 ::"l"(m), "r"(src), "r"(c0), "r"(c1) : "memory");
}
__device__ __forceinline__ void bulk_commit() { asm volatile("cp.async.bulk.commit_group;" ::: "memory"); }
__device__ __forceinline__ void bulk_wait_all() { asm volatile("cp.async.bulk.wait_group 0;" ::: "memory"); }
__device__ __forceinline__ void bulk_load(uint32_t dst, const void* src, uint32_t bytes, uint32_t bar) {
    asm volatile("cp.async.bulk.shared::cluster.global.mbarrier::complete_tx::bytes [%0], [%1], %2, [%3];"
                 ::"r"(dst), "l"(src), "r"(bytes), "r"(bar) : "memory");
}
__device__ __forceinline__ void prefetch_l2(const void* p, uint32_t bytes) {
    asm volatile("cp.async.bulk.prefetch.L2.global [%0], %1;" ::"l"(p), "r"(bytes) : "memory");
}
__device__ __forceinline__ void tma_prefetch_l2(const CUtensorMap* m, int c0, int c1) {
    asm volatile("cp.async.bulk.prefetch.tensor.2d.L2.global.tile [%0, {%1, %2}];" ::"l"(m), "r"(c0), "r"(c1) : "memory");
}
__device__ __forceinline__ void wg_fence() { asm volatile("wgmma.fence.sync.aligned;" ::: "memory"); }
__device__ __forceinline__ void wg_commit() { asm volatile("wgmma.commit_group.sync.aligned;" ::: "memory"); }
template <int N> __device__ __forceinline__ void wg_wait() {
    asm volatile("wgmma.wait_group.sync.aligned %0;" ::"n"(N) : "memory");
}
template <int N> __device__ __forceinline__ void reg_alloc() { asm volatile("setmaxnreg.inc.sync.aligned.u32 %0;" ::"n"(N)); }
template <int N> __device__ __forceinline__ void reg_dealloc() { asm volatile("setmaxnreg.dec.sync.aligned.u32 %0;" ::"n"(N)); }
template <int N> __device__ __forceinline__ void fence_regs(float (&d)[N]) {
#pragma unroll
    for (int i = 0; i < N; i++) asm volatile("" : "+f"(d[i])::"memory");
}
__device__ __forceinline__ uint64_t make_desc(uint32_t addr, uint32_t lbo, uint32_t sbo, uint32_t swz) {
    return (uint64_t)((addr & 0x3FFFF) >> 4) | ((uint64_t)(lbo >> 4) << 16) | ((uint64_t)(sbo >> 4) << 32) |
           ((uint64_t)swz << 62);
}
__device__ __forceinline__ uint32_t pack_bf16(float lo, float hi) {
    uint32_t r;
    asm("cvt.rn.bf16x2.f32 %0, %1, %2;" : "=r"(r) : "f"(hi), "f"(lo));
    return r;
}
__device__ __forceinline__ float ex2(float x) {
    float r;
    asm("ex2.approx.ftz.f32 %0, %1;" : "=f"(r) : "f"(x));
    return r;
}
__device__ __forceinline__ float bf_lo(uint32_t v) { return __uint_as_float(v << 16); }
__device__ __forceinline__ float bf_hi(uint32_t v) { return __uint_as_float(v & 0xFFFF0000u); }
__device__ __forceinline__ void stmatrix_x4(uint32_t addr, uint32_t r0, uint32_t r1, uint32_t r2, uint32_t r3) {
    asm volatile("stmatrix.sync.aligned.m8n8.x4.shared.b16 [%0], {%1, %2, %3, %4};"
                 ::"r"(addr), "r"(r0), "r"(r1), "r"(r2), "r"(r3) : "memory");
}

__device__ __forceinline__ void wgmma_n200_ss_tb(float (&d)[100], uint64_t descA, uint64_t descB, int scaleD) {
    asm volatile("{\n.reg .pred p;\nsetp.ne.b32 p, %102, 0;\n"
        "wgmma.mma_async.sync.aligned.m64n200k16.f32.bf16.bf16 {"
        "%0, %1, %2, %3, %4, %5, %6, %7, %8, %9, %10, %11, %12, %13, %14, %15, "
        "%16, %17, %18, %19, %20, %21, %22, %23, %24, %25, %26, %27, %28, %29, %30, %31, "
        "%32, %33, %34, %35, %36, %37, %38, %39, %40, %41, %42, %43, %44, %45, %46, %47, "
        "%48, %49, %50, %51, %52, %53, %54, %55, %56, %57, %58, %59, %60, %61, %62, %63, "
        "%64, %65, %66, %67, %68, %69, %70, %71, %72, %73, %74, %75, %76, %77, %78, %79, "
        "%80, %81, %82, %83, %84, %85, %86, %87, %88, %89, %90, %91, %92, %93, %94, %95, "
        "%96, %97, %98, %99}, "
        "%100, %101, p, 1, 1, 0, 1;\n}\n"
        : "+f"(d[0]), "+f"(d[1]), "+f"(d[2]), "+f"(d[3]), "+f"(d[4]), "+f"(d[5]), "+f"(d[6]), "+f"(d[7]),
          "+f"(d[8]), "+f"(d[9]), "+f"(d[10]), "+f"(d[11]), "+f"(d[12]), "+f"(d[13]), "+f"(d[14]), "+f"(d[15]),
          "+f"(d[16]), "+f"(d[17]), "+f"(d[18]), "+f"(d[19]), "+f"(d[20]), "+f"(d[21]), "+f"(d[22]), "+f"(d[23]),
          "+f"(d[24]), "+f"(d[25]), "+f"(d[26]), "+f"(d[27]), "+f"(d[28]), "+f"(d[29]), "+f"(d[30]), "+f"(d[31]),
          "+f"(d[32]), "+f"(d[33]), "+f"(d[34]), "+f"(d[35]), "+f"(d[36]), "+f"(d[37]), "+f"(d[38]), "+f"(d[39]),
          "+f"(d[40]), "+f"(d[41]), "+f"(d[42]), "+f"(d[43]), "+f"(d[44]), "+f"(d[45]), "+f"(d[46]), "+f"(d[47]),
          "+f"(d[48]), "+f"(d[49]), "+f"(d[50]), "+f"(d[51]), "+f"(d[52]), "+f"(d[53]), "+f"(d[54]), "+f"(d[55]),
          "+f"(d[56]), "+f"(d[57]), "+f"(d[58]), "+f"(d[59]), "+f"(d[60]), "+f"(d[61]), "+f"(d[62]), "+f"(d[63]),
          "+f"(d[64]), "+f"(d[65]), "+f"(d[66]), "+f"(d[67]), "+f"(d[68]), "+f"(d[69]), "+f"(d[70]), "+f"(d[71]),
          "+f"(d[72]), "+f"(d[73]), "+f"(d[74]), "+f"(d[75]), "+f"(d[76]), "+f"(d[77]), "+f"(d[78]), "+f"(d[79]),
          "+f"(d[80]), "+f"(d[81]), "+f"(d[82]), "+f"(d[83]), "+f"(d[84]), "+f"(d[85]), "+f"(d[86]), "+f"(d[87]),
          "+f"(d[88]), "+f"(d[89]), "+f"(d[90]), "+f"(d[91]), "+f"(d[92]), "+f"(d[93]), "+f"(d[94]), "+f"(d[95]),
          "+f"(d[96]), "+f"(d[97]), "+f"(d[98]), "+f"(d[99])
        : "l"(descA), "l"(descB), "r"(scaleD));
}

__device__ __forceinline__ void wgmma_n40_ss_tb(float (&d)[20], uint64_t descA, uint64_t descB, int scaleD) {
    asm volatile("{\n.reg .pred p;\nsetp.ne.b32 p, %22, 0;\n"
        "wgmma.mma_async.sync.aligned.m64n40k16.f32.bf16.bf16 {"
        "%0, %1, %2, %3, %4, %5, %6, %7, %8, %9, %10, %11, %12, %13, %14, %15, "
        "%16, %17, %18, %19}, "
        "%20, %21, p, 1, 1, 0, 1;\n}\n"
        : "+f"(d[0]), "+f"(d[1]), "+f"(d[2]), "+f"(d[3]), "+f"(d[4]), "+f"(d[5]), "+f"(d[6]), "+f"(d[7]),
          "+f"(d[8]), "+f"(d[9]), "+f"(d[10]), "+f"(d[11]), "+f"(d[12]), "+f"(d[13]), "+f"(d[14]), "+f"(d[15]),
          "+f"(d[16]), "+f"(d[17]), "+f"(d[18]), "+f"(d[19])
        : "l"(descA), "l"(descB), "r"(scaleD));
}

__device__ __forceinline__ void wgmma_n192_ss_tb(float (&d)[96], uint64_t descA, uint64_t descB, int scaleD) {
    asm volatile("{\n.reg .pred p;\nsetp.ne.b32 p, %98, 0;\n"
        "wgmma.mma_async.sync.aligned.m64n192k16.f32.bf16.bf16 {"
        "%0, %1, %2, %3, %4, %5, %6, %7, %8, %9, %10, %11, %12, %13, %14, %15, "
        "%16, %17, %18, %19, %20, %21, %22, %23, %24, %25, %26, %27, %28, %29, %30, %31, "
        "%32, %33, %34, %35, %36, %37, %38, %39, %40, %41, %42, %43, %44, %45, %46, %47, "
        "%48, %49, %50, %51, %52, %53, %54, %55, %56, %57, %58, %59, %60, %61, %62, %63, "
        "%64, %65, %66, %67, %68, %69, %70, %71, %72, %73, %74, %75, %76, %77, %78, %79, "
        "%80, %81, %82, %83, %84, %85, %86, %87, %88, %89, %90, %91, %92, %93, %94, %95}, "
        "%96, %97, p, 1, 1, 0, 1;\n}\n"
        : "+f"(d[0]), "+f"(d[1]), "+f"(d[2]), "+f"(d[3]), "+f"(d[4]), "+f"(d[5]), "+f"(d[6]), "+f"(d[7]),
          "+f"(d[8]), "+f"(d[9]), "+f"(d[10]), "+f"(d[11]), "+f"(d[12]), "+f"(d[13]), "+f"(d[14]), "+f"(d[15]),
          "+f"(d[16]), "+f"(d[17]), "+f"(d[18]), "+f"(d[19]), "+f"(d[20]), "+f"(d[21]), "+f"(d[22]), "+f"(d[23]),
          "+f"(d[24]), "+f"(d[25]), "+f"(d[26]), "+f"(d[27]), "+f"(d[28]), "+f"(d[29]), "+f"(d[30]), "+f"(d[31]),
          "+f"(d[32]), "+f"(d[33]), "+f"(d[34]), "+f"(d[35]), "+f"(d[36]), "+f"(d[37]), "+f"(d[38]), "+f"(d[39]),
          "+f"(d[40]), "+f"(d[41]), "+f"(d[42]), "+f"(d[43]), "+f"(d[44]), "+f"(d[45]), "+f"(d[46]), "+f"(d[47]),
          "+f"(d[48]), "+f"(d[49]), "+f"(d[50]), "+f"(d[51]), "+f"(d[52]), "+f"(d[53]), "+f"(d[54]), "+f"(d[55]),
          "+f"(d[56]), "+f"(d[57]), "+f"(d[58]), "+f"(d[59]), "+f"(d[60]), "+f"(d[61]), "+f"(d[62]), "+f"(d[63]),
          "+f"(d[64]), "+f"(d[65]), "+f"(d[66]), "+f"(d[67]), "+f"(d[68]), "+f"(d[69]), "+f"(d[70]), "+f"(d[71]),
          "+f"(d[72]), "+f"(d[73]), "+f"(d[74]), "+f"(d[75]), "+f"(d[76]), "+f"(d[77]), "+f"(d[78]), "+f"(d[79]),
          "+f"(d[80]), "+f"(d[81]), "+f"(d[82]), "+f"(d[83]), "+f"(d[84]), "+f"(d[85]), "+f"(d[86]), "+f"(d[87]),
          "+f"(d[88]), "+f"(d[89]), "+f"(d[90]), "+f"(d[91]), "+f"(d[92]), "+f"(d[93]), "+f"(d[94]), "+f"(d[95])
        : "l"(descA), "l"(descB), "r"(scaleD));
}

__device__ __forceinline__ void wgmma_n192_ss_tb_z(float (&d)[96], uint64_t descA, uint64_t descB) {
    asm volatile("{\n.reg .pred p;\nsetp.ne.b32 p, 0, 0;\n"
        "wgmma.mma_async.sync.aligned.m64n192k16.f32.bf16.bf16 {"
        "%0, %1, %2, %3, %4, %5, %6, %7, %8, %9, %10, %11, %12, %13, %14, %15, "
        "%16, %17, %18, %19, %20, %21, %22, %23, %24, %25, %26, %27, %28, %29, %30, %31, "
        "%32, %33, %34, %35, %36, %37, %38, %39, %40, %41, %42, %43, %44, %45, %46, %47, "
        "%48, %49, %50, %51, %52, %53, %54, %55, %56, %57, %58, %59, %60, %61, %62, %63, "
        "%64, %65, %66, %67, %68, %69, %70, %71, %72, %73, %74, %75, %76, %77, %78, %79, "
        "%80, %81, %82, %83, %84, %85, %86, %87, %88, %89, %90, %91, %92, %93, %94, %95}, "
        "%96, %97, p, 1, 1, 0, 1;\n}\n"
        : "=f"(d[0]), "=f"(d[1]), "=f"(d[2]), "=f"(d[3]), "=f"(d[4]), "=f"(d[5]), "=f"(d[6]), "=f"(d[7]),
          "=f"(d[8]), "=f"(d[9]), "=f"(d[10]), "=f"(d[11]), "=f"(d[12]), "=f"(d[13]), "=f"(d[14]), "=f"(d[15]),
          "=f"(d[16]), "=f"(d[17]), "=f"(d[18]), "=f"(d[19]), "=f"(d[20]), "=f"(d[21]), "=f"(d[22]), "=f"(d[23]),
          "=f"(d[24]), "=f"(d[25]), "=f"(d[26]), "=f"(d[27]), "=f"(d[28]), "=f"(d[29]), "=f"(d[30]), "=f"(d[31]),
          "=f"(d[32]), "=f"(d[33]), "=f"(d[34]), "=f"(d[35]), "=f"(d[36]), "=f"(d[37]), "=f"(d[38]), "=f"(d[39]),
          "=f"(d[40]), "=f"(d[41]), "=f"(d[42]), "=f"(d[43]), "=f"(d[44]), "=f"(d[45]), "=f"(d[46]), "=f"(d[47]),
          "=f"(d[48]), "=f"(d[49]), "=f"(d[50]), "=f"(d[51]), "=f"(d[52]), "=f"(d[53]), "=f"(d[54]), "=f"(d[55]),
          "=f"(d[56]), "=f"(d[57]), "=f"(d[58]), "=f"(d[59]), "=f"(d[60]), "=f"(d[61]), "=f"(d[62]), "=f"(d[63]),
          "=f"(d[64]), "=f"(d[65]), "=f"(d[66]), "=f"(d[67]), "=f"(d[68]), "=f"(d[69]), "=f"(d[70]), "=f"(d[71]),
          "=f"(d[72]), "=f"(d[73]), "=f"(d[74]), "=f"(d[75]), "=f"(d[76]), "=f"(d[77]), "=f"(d[78]), "=f"(d[79]),
          "=f"(d[80]), "=f"(d[81]), "=f"(d[82]), "=f"(d[83]), "=f"(d[84]), "=f"(d[85]), "=f"(d[86]), "=f"(d[87]),
          "=f"(d[88]), "=f"(d[89]), "=f"(d[90]), "=f"(d[91]), "=f"(d[92]), "=f"(d[93]), "=f"(d[94]), "=f"(d[95])
        : "l"(descA), "l"(descB));
}

__device__ __forceinline__ void wgmma_n160_ss_tb(float (&d)[80], uint64_t descA, uint64_t descB, int scaleD) {
    asm volatile("{\n.reg .pred p;\nsetp.ne.b32 p, %82, 0;\n"
        "wgmma.mma_async.sync.aligned.m64n160k16.f32.bf16.bf16 {"
        "%0, %1, %2, %3, %4, %5, %6, %7, %8, %9, %10, %11, %12, %13, %14, %15, "
        "%16, %17, %18, %19, %20, %21, %22, %23, %24, %25, %26, %27, %28, %29, %30, %31, "
        "%32, %33, %34, %35, %36, %37, %38, %39, %40, %41, %42, %43, %44, %45, %46, %47, "
        "%48, %49, %50, %51, %52, %53, %54, %55, %56, %57, %58, %59, %60, %61, %62, %63, "
        "%64, %65, %66, %67, %68, %69, %70, %71, %72, %73, %74, %75, %76, %77, %78, %79}, "
        "%80, %81, p, 1, 1, 0, 1;\n}\n"
        : "+f"(d[0]), "+f"(d[1]), "+f"(d[2]), "+f"(d[3]), "+f"(d[4]), "+f"(d[5]), "+f"(d[6]), "+f"(d[7]),
          "+f"(d[8]), "+f"(d[9]), "+f"(d[10]), "+f"(d[11]), "+f"(d[12]), "+f"(d[13]), "+f"(d[14]), "+f"(d[15]),
          "+f"(d[16]), "+f"(d[17]), "+f"(d[18]), "+f"(d[19]), "+f"(d[20]), "+f"(d[21]), "+f"(d[22]), "+f"(d[23]),
          "+f"(d[24]), "+f"(d[25]), "+f"(d[26]), "+f"(d[27]), "+f"(d[28]), "+f"(d[29]), "+f"(d[30]), "+f"(d[31]),
          "+f"(d[32]), "+f"(d[33]), "+f"(d[34]), "+f"(d[35]), "+f"(d[36]), "+f"(d[37]), "+f"(d[38]), "+f"(d[39]),
          "+f"(d[40]), "+f"(d[41]), "+f"(d[42]), "+f"(d[43]), "+f"(d[44]), "+f"(d[45]), "+f"(d[46]), "+f"(d[47]),
          "+f"(d[48]), "+f"(d[49]), "+f"(d[50]), "+f"(d[51]), "+f"(d[52]), "+f"(d[53]), "+f"(d[54]), "+f"(d[55]),
          "+f"(d[56]), "+f"(d[57]), "+f"(d[58]), "+f"(d[59]), "+f"(d[60]), "+f"(d[61]), "+f"(d[62]), "+f"(d[63]),
          "+f"(d[64]), "+f"(d[65]), "+f"(d[66]), "+f"(d[67]), "+f"(d[68]), "+f"(d[69]), "+f"(d[70]), "+f"(d[71]),
          "+f"(d[72]), "+f"(d[73]), "+f"(d[74]), "+f"(d[75]), "+f"(d[76]), "+f"(d[77]), "+f"(d[78]), "+f"(d[79])
        : "l"(descA), "l"(descB), "r"(scaleD));
}

__device__ __forceinline__ void wgmma_n64_ss(float (&d)[32], uint64_t descA, uint64_t descB, int scaleD) {
    asm volatile("{\n.reg .pred p;\nsetp.ne.b32 p, %34, 0;\n"
        "wgmma.mma_async.sync.aligned.m64n64k16.f32.bf16.bf16 {"
        "%0, %1, %2, %3, %4, %5, %6, %7, %8, %9, %10, %11, %12, %13, %14, %15, "
        "%16, %17, %18, %19, %20, %21, %22, %23, %24, %25, %26, %27, %28, %29, %30, %31}, "
        "%32, %33, p, 1, 1, 0, 0;\n}\n"
        : "+f"(d[0]), "+f"(d[1]), "+f"(d[2]), "+f"(d[3]), "+f"(d[4]), "+f"(d[5]), "+f"(d[6]), "+f"(d[7]),
          "+f"(d[8]), "+f"(d[9]), "+f"(d[10]), "+f"(d[11]), "+f"(d[12]), "+f"(d[13]), "+f"(d[14]), "+f"(d[15]),
          "+f"(d[16]), "+f"(d[17]), "+f"(d[18]), "+f"(d[19]), "+f"(d[20]), "+f"(d[21]), "+f"(d[22]), "+f"(d[23]),
          "+f"(d[24]), "+f"(d[25]), "+f"(d[26]), "+f"(d[27]), "+f"(d[28]), "+f"(d[29]), "+f"(d[30]), "+f"(d[31])
        : "l"(descA), "l"(descB), "r"(scaleD));
}

__device__ __forceinline__ void wgmma_n64_ss_z(float (&d)[32], uint64_t descA, uint64_t descB) {
    asm volatile("{\n.reg .pred p;\nsetp.ne.b32 p, 0, 0;\n"
        "wgmma.mma_async.sync.aligned.m64n64k16.f32.bf16.bf16 {"
        "%0, %1, %2, %3, %4, %5, %6, %7, %8, %9, %10, %11, %12, %13, %14, %15, "
        "%16, %17, %18, %19, %20, %21, %22, %23, %24, %25, %26, %27, %28, %29, %30, %31}, "
        "%32, %33, p, 1, 1, 0, 0;\n}\n"
        : "=f"(d[0]), "=f"(d[1]), "=f"(d[2]), "=f"(d[3]), "=f"(d[4]), "=f"(d[5]), "=f"(d[6]), "=f"(d[7]),
          "=f"(d[8]), "=f"(d[9]), "=f"(d[10]), "=f"(d[11]), "=f"(d[12]), "=f"(d[13]), "=f"(d[14]), "=f"(d[15]),
          "=f"(d[16]), "=f"(d[17]), "=f"(d[18]), "=f"(d[19]), "=f"(d[20]), "=f"(d[21]), "=f"(d[22]), "=f"(d[23]),
          "=f"(d[24]), "=f"(d[25]), "=f"(d[26]), "=f"(d[27]), "=f"(d[28]), "=f"(d[29]), "=f"(d[30]), "=f"(d[31])
        : "l"(descA), "l"(descB));
}

__device__ __forceinline__ void wgmma_n24_rs_tb(float (&d)[12], uint32_t a0, uint32_t a1, uint32_t a2, uint32_t a3, uint64_t descB, int scaleD) {
    asm volatile("{\n.reg .pred p;\nsetp.ne.b32 p, %17, 0;\n"
        "wgmma.mma_async.sync.aligned.m64n24k16.f32.bf16.bf16 {"
        "%0, %1, %2, %3, %4, %5, %6, %7, %8, %9, %10, %11}, "
        "{%12, %13, %14, %15}, %16, p, 1, 1, 1;\n}\n"
        : "+f"(d[0]), "+f"(d[1]), "+f"(d[2]), "+f"(d[3]), "+f"(d[4]), "+f"(d[5]), "+f"(d[6]), "+f"(d[7]),
          "+f"(d[8]), "+f"(d[9]), "+f"(d[10]), "+f"(d[11])
        : "r"(a0), "r"(a1), "r"(a2), "r"(a3), "l"(descB), "r"(scaleD));
}

__device__ __forceinline__ void cnt_signal(int idx) {
    asm volatile("fence.acq_rel.gpu;\nred.relaxed.gpu.global.add.u32 [%0], 1;"
                 ::"l"(g_cnt + idx * 32) : "memory");
}
__device__ __forceinline__ void cnt_wait(int idx, uint32_t target) {
    const uint32_t* p = g_cnt + idx * 32;
#pragma unroll 1
    for (uint32_t i = 0; i < (1u << 22); i++) {
        uint32_t v;
        asm volatile("ld.acquire.gpu.global.u32 %0, [%1];" : "=r"(v) : "l"(p) : "memory");
        if ((int32_t)(v - target) >= 0) break;
    }
    asm volatile("fence.proxy.async.global;" ::: "memory");
}
__device__ __forceinline__ void cluster_arrive() { asm volatile("barrier.cluster.arrive.release.aligned;" ::: "memory"); }
__device__ __forceinline__ void cluster_arrive_relaxed() { asm volatile("barrier.cluster.arrive.relaxed.aligned;" ::: "memory"); }
__device__ __forceinline__ void cluster_wait() { asm volatile("barrier.cluster.wait.acquire.aligned;" ::: "memory"); }
__device__ __forceinline__ void bulk_wait_read() { asm volatile("cp.async.bulk.wait_group.read 0;" ::: "memory"); }

__device__ __forceinline__ float gelu_half(float hx) {
    const float u = hx * fmaf(hx * hx, 8.f * 0.035677408136300125f, 2.f * 0.7978845608028654f);
    float t;
    asm("tanh.approx.f32 %0, %1;" : "=f"(t) : "f"(u));
    return fmaf(hx, t, hx);
}
__device__ __forceinline__ void release_stage(uint32_t bar, uint32_t peer, int lane) {
    if (lane == 0) { mbar_arrive(bar); mbar_arrive_cluster(bar, peer); }
}

constexpr int SM_RING = 163840;
constexpr int SM_Q = 0, SM_ZERO = 24576, SM_K = SM_ZERO + 3072, SM_V = SM_K + IMG_BYTES;
constexpr int G2_STAGE = 8192 + 20480;
constexpr int SM_MISC = 229376;
constexpr int SM_BIAS = SM_MISC, SM_RED = SM_BIAS + 384, SM_BAR = SM_RED + 128;
constexpr int B_A = 0, B_F1 = 10, B_E1 = 14, B_F2 = 18, B_E2 = 23, B_KV = 28, B_Q = 45, B_F3 = 47, B_E3 = 55, B_ST = 63, B_STAT = 65, B_AUX = 66, B_AUX2 = 67, B_DEAD = 68, B_COUNT = 70;
constexpr int SM_EPOCH = SM_BAR + 568, SM_SAFE = SM_EPOCH + 4;
constexpr int SM_CS = SM_EPOCH + 8;
constexpr int SM_TOTAL = SM_CS + 1728;
static_assert(SM_TOTAL <= 232448, "shared memory budget");

struct Maps { CUtensorMap x, wqkv, w1, h, o, wo, w2; };

__device__ __forceinline__ uint32_t bf2_fma(uint32_t a, uint32_t b, uint32_t c) {
    uint32_t r;
    asm("fma.rn.bf16x2 %0, %1, %2, %3;" : "=r"(r) : "r"(a), "r"(b), "r"(c));
    return r;
}
__device__ __forceinline__ uint32_t lop_and_or(uint32_t a, uint32_t m, uint32_t o) {
    uint32_t r;
    asm("lop3.b32 %0, %1, %2, %3, 0xEA;" : "=r"(r) : "r"(a), "r"(m), "r"(o));
    return r;
}
struct ExpConst { uint32_t mask, slope; };
__device__ __forceinline__ ExpConst make_exp_const() {
    ExpConst k;
    asm volatile("mov.b32 %0, 0x007F007F;" : "=r"(k.mask));
    asm volatile("mov.b32 %0, 0x3EF83EF8;" : "=r"(k.slope));
    return k;
}
__device__ __forceinline__ uint32_t exp2_pair_fma(float t0, float t1, const ExpConst& k) {
    const uint32_t L = __byte_perm(__float_as_uint(t0), __float_as_uint(t1), 0x6521);
    const uint32_t g = lop_and_or(L, k.mask, 0x3F803F80u);
    const uint32_t u = bf2_fma(g, k.slope, 0xBF37BF37u);
    const uint32_t e = bf2_fma(u, u, 0xBD71BD71u);
    return bf2_fma(L, e, L);
}
template <int SHIFT>
__device__ __forceinline__ void exp_tile(const float (&s)[32], uint32_t (&p)[16], const ExpConst& k) {
#pragma unroll
    for (int b = 0; b < 8; b++) {
        if ((EMU_MASK >> (b + SHIFT)) & 1) {
            p[2 * b] = exp2_pair_fma(s[4 * b], s[4 * b + 1], k);
            p[2 * b + 1] = exp2_pair_fma(s[4 * b + 2], s[4 * b + 3], k);
        } else {
            p[2 * b] = pack_bf16(ex2(s[4 * b]), ex2(s[4 * b + 1]));
            p[2 * b + 1] = pack_bf16(ex2(s[4 * b + 2]), ex2(s[4 * b + 3]));
        }
    }
}

__device__ __forceinline__ void qk_tile(float (&s)[32], uint64_t dQ, uint64_t dQ2, uint64_t dK) {
    wg_fence();
    wgmma_n64_ss_z(s, dQ, dK);
    wgmma_n64_ss(s, dQ2, dK + 16, 1);
    wg_commit();
}
__device__ __forceinline__ void pv_tile(float (&o)[12], const uint32_t (&p)[16], uint64_t dV) {
    wg_fence();
#pragma unroll
    for (int ks = 0; ks < 4; ks++)
        wgmma_n24_rs_tb(o, p[4 * ks], p[4 * ks + 1], p[4 * ks + 2], p[4 * ks + 3], dV + ks * 48, 1);
    wg_commit();
}
__device__ __forceinline__ void store_o(const float (&o)[12], int h, int rbase, int lane) {
    const int g = lane >> 2, c = lane & 3;
    const bool odd = h & 1;
    const int lsrc = (lane & ~3) | (odd ? 0 : 2);
    const float i0 = 1.f / __shfl_sync(~0u, o[8], lsrc), i1 = 1.f / __shfl_sync(~0u, o[10], lsrc);
    __nv_bfloat16* dst = g_o + (size_t)(rbase + g) * DM + h * 20;
    const int d0 = (odd ? 4 : 0) + 2 * c, d1 = d0 + 8, d2 = odd ? 2 * c - 4 : 16 + 2 * c;
    *(uint32_t*)(dst + d0) = pack_bf16(o[0] * i0, o[1] * i0);
    *(uint32_t*)(dst + d1) = pack_bf16(o[4] * i0, o[5] * i0);
    *(uint32_t*)(dst + 8 * DM + d0) = pack_bf16(o[2] * i1, o[3] * i1);
    *(uint32_t*)(dst + 8 * DM + d1) = pack_bf16(o[6] * i1, o[7] * i1);
    if (odd ? (c >= 2) : (c < 2)) {
        *(uint32_t*)(dst + d2) = pack_bf16(o[8] * i0, o[9] * i0);
        *(uint32_t*)(dst + 8 * DM + d2) = pack_bf16(o[10] * i1, o[11] * i1);
    }
}

__device__ __forceinline__ void attn_rows_maxshift(uint32_t sK, uint32_t barKV, uint64_t dQ, uint64_t dQ2, int h, int rbase) {
    const int lane = threadIdx.x & 31;
    const uint64_t dK0 = make_desc(sK, 128, 384, 0), dV0 = make_desc(sK + IMG_BYTES, 384, 128, 0);
    float o[12], s[32];
    uint32_t p[16];
#pragma unroll
    for (int i = 0; i < 12; i++) o[i] = 0.f;
    float m0 = -3.0e38f, m1 = -3.0e38f;
    mbar_wait(barKV + 128, 0);
#pragma unroll 1
    for (int t = 0; t < 32; t++) {
        mbar_wait(barKV + (t >> 1) * 8, 0);
        qk_tile(s, dQ, dQ2, dK0 + t * 192);
        wg_wait<0>();
        fence_regs(s);
        const uint32_t mask = EMU_MASK >> ((t & 1) * 8);
        float n0 = m0, n1 = m1;
#pragma unroll
        for (int b = 0; b < 8; b++) {
            const bool emu = (mask >> b) & 1;
            const float f = emu ? 0.5f : 1.f, off = emu ? -383.00390625f : 0.f;
#pragma unroll
            for (int i = 0; i < 4; i++) s[4 * b + i] = fmaf(s[4 * b + i], f, off);
            n0 = fmaxf(n0, fmaxf(s[4 * b], s[4 * b + 1]));
            n1 = fmaxf(n1, fmaxf(s[4 * b + 2], s[4 * b + 3]));
        }
        n0 = fmaxf(n0, __shfl_xor_sync(~0u, n0, 1)); n0 = fmaxf(n0, __shfl_xor_sync(~0u, n0, 2));
        n1 = fmaxf(n1, __shfl_xor_sync(~0u, n1, 1)); n1 = fmaxf(n1, __shfl_xor_sync(~0u, n1, 2));
        const float c0 = ex2(m0 - n0), c1 = ex2(m1 - n1);
        m0 = n0; m1 = n1;
#pragma unroll
        for (int b = 0; b < 3; b++) { o[4 * b] *= c0; o[4 * b + 1] *= c0; o[4 * b + 2] *= c1; o[4 * b + 3] *= c1; }
#pragma unroll
        for (int b = 0; b < 8; b++) {
            p[2 * b] = pack_bf16(ex2(s[4 * b] - m0), ex2(s[4 * b + 1] - m0));
            p[2 * b + 1] = pack_bf16(ex2(s[4 * b + 2] - m1), ex2(s[4 * b + 3] - m1));
        }
        pv_tile(o, p, dV0 + (((t >> 1) + 7) & 15) * 384 + (t & 1) * 192);
        wg_wait<0>();
        fence_regs(o);
    }
    store_o(o, h, rbase, lane);
}

__global__ void __launch_bounds__(512, 1) __cluster_dims__(2, 1, 1)
k_fused(const __grid_constant__ Maps tm, const __nv_bfloat16* __restrict__ x, const uint8_t* __restrict__ wqkv,
        const uint8_t* __restrict__ w1, const uint8_t* __restrict__ w2, const uint8_t* __restrict__ wo,
        const __nv_bfloat16* __restrict__ b1, const __nv_bfloat16* __restrict__ b2, __nv_bfloat16* __restrict__ out) {
    extern __shared__ __align__(1024) uint8_t smem[];
    const uint32_t sb = smem_u32(smem);
    const uint32_t bar = sb + SM_BAR;
    const int warp = __shfl_sync(~0u, threadIdx.x >> 5, 0), lane = threadIdx.x & 31;
    const int wgi = warp >> 2, w4 = warp & 3, g = lane >> 2, c = lane & 3;
    const uint32_t rank = blockIdx.x & 1, peer = rank ^ 1;
    const int cl = blockIdx.x >> 1;
    const int cg = cl >> 3, rb = (cl & 7) * 2 + rank;

    if (threadIdx.x == 0) TL(0, 0);
    if (warp == 15 && lane < 4) prefetch_map(lane == 0 ? &tm.x : lane == 1 ? &tm.wqkv : lane == 2 ? &tm.w1 : &tm.h);
    if (elect_one()) {
#pragma unroll
        for (int j = 0; j < 5; j++) {
            const int i = warp * 5 + j;
            const int cnt = (i >= B_E1 && i < B_F2) || (i >= B_E2 && i < B_KV) ? 16
                          : (i >= B_E3 && i <= B_ST + 1) || i == B_STAT || i == B_DEAD || i == B_DEAD + 1 ? 8 : i == B_AUX ? 4 : i == B_AUX2 ? 3 : 1;
            if (i < B_COUNT) mbar_init(bar + i * 8, cnt);
        }
        fence_barrier_init();
    }
    __syncthreads();
    if (threadIdx.x == 0) TL(0, 1);
    cluster_arrive_relaxed();
    cluster_wait();
    if (threadIdx.x == 0) TL(0, 3);

    {
        const uint32_t sB = sb + SM_RING;
        if (threadIdx.x == 0) TL(1, 0);
        if (wgi < 2) {
            reg_dealloc<56>();
            if (warp == 0) {
#pragma unroll 1
                for (int it = 0; it < 20; it++) {
                    const int s = it & 3;
                    const int kb = it < 2 ? it : (it & 1) ? (it + 1) >> 1 : 10;
                    if (it >= 4) mbar_wait(bar + (B_E1 + s) * 8, ((it >> 2) - 1) & 1);
                    else if (it > 0) __nanosleep(PACE_NS);
                    if (elect_one()) {
                        if (kb < 10) {
                            mbar_expect_tx(bar + (B_A + kb) * 8, 16384);
                            tma_load(sb + kb * 16384, &tm.x, kb * 64, rb * 128, bar + (B_A + kb) * 8);
                        }
                        const uint32_t dst = sB + s * 16384 + rank * 8192, fb = bar + (B_F1 + s) * 8;
                        const int c0 = cg * 240 + rank * 128;
                        mbar_expect_tx(fb, 16384);
                        tma_load_mc(dst, &tm.wqkv, c0, it * 32, fb, 3);
                        tma_load_mc(dst + 4096, &tm.wqkv, c0 + 64, it * 32, fb, 3);
                    }
                    __syncwarp();
                }
#pragma unroll 1
                for (int it = 0; it < 20; it++) {
                    const int s = it % 5;
                    if (it < 5) { if (it != 3) mbar_wait(bar + (B_E1 + (it == 4 ? 3 : it)) * 8, 0); }
                    else mbar_wait(bar + (B_E2 + s) * 8, ((it / 5) - 1) & 1);
                    if (elect_one()) {
                        const uint32_t dst = sB + s * 12288, fb = bar + (B_F2 + s) * 8;
                        mbar_expect_tx(fb, 12288);
                        if ((it & 1) == (int)rank) {
                            tma_load_mc(dst, &tm.w1, cg * 192, it * 32, fb, 3);
                            tma_load_mc(dst + 4096, &tm.w1, cg * 192 + 64, it * 32, fb, 3);
                        } else {
                            tma_load_mc(dst + 8192, &tm.w1, cg * 192 + 128, it * 32, fb, 3);
                        }
                    }
                    __syncwarp();
                }
            } else {
                const int ht = threadIdx.x - 32;
                if (ht == 160) *reinterpret_cast<volatile uint32_t*>(smem + SM_EPOCH) = *(volatile uint32_t*)&g_epoch;
                auto slab_sum = [&](const uint32_t* src, int pitch) {
                    float s0 = 0.f, s1 = 0.f;
                    uint32_t v[40];
#pragma unroll
                    for (int k = 0; k < 40; k++) v[k] = __ldg(src + k * pitch);
#pragma unroll
                    for (int k = 0; k < 40; k++) { s0 += bf_lo(v[k]); s1 += bf_hi(v[k]); }
                    return make_float2(s0, s1);
                };
                auto gather = [&](int idx) {
                    float s0 = 0.f, s1 = 0.f;
#pragma unroll
                    for (int r = 0; r < 16; r++) {
                        const float2 v = __ldcg(g_csp + r * 1728 + cg * 216 + idx);
                        s0 += v.x; s1 += v.y;
                    }
                    reinterpret_cast<float2*>(smem + SM_CS)[idx] = make_float2(s0, s1);
                };
                if (warp == 7) {
                    mbar_wait(bar + B_STAT * 8, 0);
                    if (elect_one()) cnt_signal(CNT_ST + rb);
                    __syncwarp();
                }
                if (ht < 120)
                    g_csp[rb * 1728 + cg * 216 + ht] = slab_sum(reinterpret_cast<const uint32_t*>(wqkv) + rb * 40 * 960 + cg * 120 + ht, 960);
                if (threadIdx.x == 64) IT(3, 0);
                if (threadIdx.x == 192) IT(3, 1);
                if (warp != 7) asm volatile("bar.sync 8, 192;" ::: "memory");
                const uint32_t epoch = *reinterpret_cast<volatile uint32_t*>(smem + SM_EPOCH);
                if (warp == 6) { if (elect_one()) cnt_signal(CNT_CS + cg); __syncwarp(); }

                if (threadIdx.x == 64) IT(3, 2);
                if (warp <= 4) {
                    if (lane == 0) { cnt_wait(CNT_CS + cg, (epoch + 1) * 16); cnt_wait(CNT_ST + rb, (epoch + 1) * 8); }
                    __syncwarp();
                    if (threadIdx.x == 64) IT(3, 4);
                    if (ht < 120) gather(ht);
                    __syncwarp();
                    if (threadIdx.x == 64) IT(3, 5);
                    if (lane == 0) mbar_arrive(bar + B_AUX * 8);
                }
                if (ht >= 128) {
                    g_csp[rb * 1728 + cg * 216 + 120 + (ht - 128)] = slab_sum(reinterpret_cast<const uint32_t*>(w1) + rb * 40 * 768 + cg * 96 + (ht - 128), 768);
                    reinterpret_cast<uint32_t*>(smem + SM_BIAS)[ht - 128] =
                        bf2_fma(__ldg(reinterpret_cast<const uint32_t*>(b1 + cg * 192) + (ht - 128)), 0x3F003F00u, 0x80008000u);
                    asm volatile("bar.sync 9, 96;" ::: "memory");
                    const uint32_t epoch2 = *reinterpret_cast<volatile uint32_t*>(smem + SM_EPOCH);
                    if (warp == 5) { if (elect_one()) cnt_signal(CNT_CS2 + cg); __syncwarp(); }
                    if (warp == 6 && elect_one()) {
                        prefetch_l2(w2 + blockIdx.x * 15360, 15360);
                        prefetch_l2(wo + blockIdx.x * 6400, 6400);
                    }
                    if (lane == 0) cnt_wait(CNT_CS2 + cg, (epoch2 + 1) * 16);
                    __syncwarp();
                    gather(120 + (ht - 128));
                    __syncwarp();
                    if (lane == 0) mbar_arrive(bar + B_AUX2 * 8);
                }
                if (warp == 4) {
                    mbar_wait(bar + B_ST * 8, 0);
                    if (elect_one()) cnt_signal(CNT_QKV + cg);
                    __syncwarp();
                }
                const int h = blockIdx.x >> 2, qb = blockIdx.x & 3;
                asm volatile("bar.sync 8, 224;" ::: "memory");
                const uint32_t ep = *reinterpret_cast<volatile uint32_t*>(smem + SM_EPOCH);
                if (lane == 0) {
                    cnt_wait(CNT_QKV + h / 12, (ep + 1) * 16);
                    cnt_wait(CNT_QKV + (32 + h) / 12, (ep + 1) * 16);
                    cnt_wait(CNT_QKV + (64 + h) / 12, (ep + 1) * 16);
                }
                __syncwarp();
                if (threadIdx.x == 64) TL(5, 0);
                {
                    float kmax = 0.f, qmax = 0.f;
#pragma unroll
                    for (int i = 0; i < 10; i++) if (ht + i * 224 < 2048) kmax = fmaxf(kmax, __ldcg(g_nrm + (32 + h) * SEQ + ht + i * 224));
#pragma unroll
                    for (int i = 0; i < 3; i++) if (ht + i * 224 < 512) qmax = fmaxf(qmax, __ldcg(g_nrm + h * SEQ + qb * 512 + ht + i * 224));
#pragma unroll
                    for (int o = 16; o; o >>= 1) {
                        kmax = fmaxf(kmax, __shfl_xor_sync(~0u, kmax, o));
                        qmax = fmaxf(qmax, __shfl_xor_sync(~0u, qmax, o));
                    }
                    float* red = reinterpret_cast<float*>(smem + SM_RED);
                    if (lane == 0) { red[warp] = kmax; red[8 + warp] = qmax; }
                    asm volatile("bar.sync 8, 224;" ::: "memory");
                    if (ht == 0) {
                        for (int w = 2; w < 8; w++) { kmax = fmaxf(kmax, red[w]); qmax = fmaxf(qmax, red[8 + w]); }
                        *reinterpret_cast<volatile uint32_t*>(smem + SM_SAFE) = kmax * qmax * 1.1f <= SAFE_BOUND * SAFE_BOUND;
                    }
                }
                const uint32_t barKV = bar + B_KV * 8;
                const uint8_t* gK = g_img + (size_t)(32 + h) * IMG_BYTES;
                const uint8_t* gV = g_img + (size_t)(64 + h) * IMG_BYTES;
                if (warp == 2) {
                    if (lane == 0) TL(5, 1);
                    mbar_wait(bar + B_DEAD * 8, 0);
                    if (lane == 0) TL(5, 2);
                    for (int i = lane; i < 192; i += 32) *reinterpret_cast<uint4*>(smem + SM_ZERO + i * 16) = make_uint4(0, 0, 0, 0);
                    fence_proxy_async();
                    __syncwarp();
                    if (elect_one()) {
                        asm volatile("fence.proxy.async.global;" ::: "memory");
                        const uint8_t* gQ = g_img + (size_t)h * IMG_BYTES + qb * 64 * 384;
                        mbar_expect_tx(barKV + 128, 6144);
                        bulk_load(sb + SM_K, gK, 6144, barKV + 128);
                        for (int p = 0; p < 2; p++) {
                            mbar_expect_tx(bar + (B_Q + p) * 8, 12288);
                            bulk_load(sb + SM_Q + p * 12288, gQ + p * 12288, 12288, bar + (B_Q + p) * 8);
                        }
                        for (int i = 0; i < 13; i++) {
                            mbar_expect_tx(barKV + i * 8, 12288);
                            bulk_load(sb + SM_K + (i + 1) * 6144, gK + (i + 1) * 6144, 6144, barKV + i * 8);
                        }
                    }
                    __syncwarp();
                    if (lane == 0) TL(5, 3);
                } else if (warp == 5) {
                    mbar_wait(bar + (B_ST + 1) * 8, 0);
                    if (lane == 0) {
                        for (int b = 0; b < 6; b++)
                            tma_store(&tm.h, sb + (7 + b % 3) * 16384 + (b / 3) * 8192, cg * 192 + (b % 3) * 64, rb * 128 + (b / 3) * 64);
                        bulk_commit();
                    }
                    __syncwarp();
                } else if (warp == 3) {
                    mbar_wait(bar + (B_DEAD + 1) * 8, 0);
                    if (elect_one()) {
                        asm volatile("fence.proxy.async.global;" ::: "memory");
                        for (int i = 0; i < 9; i++) bulk_load(sb + SM_V + (i + 7) * 6144, gV + i * 6144, 6144, barKV + i * 8);
                    }
                    __syncwarp();
                }
            }
            if (lane == 0) TL(6, warp);
            asm volatile("bar.sync %0, 128;" ::"r"(wgi + 3) : "memory");
            reg_alloc<128>();
        } else {
            reg_alloc<200>();
            const int wi = wgi - 2;
            const int row0 = rb * 128 + wi * 64 + w4 * 16 + g;
            const uint32_t sAw = sb + wi * 8192;
            const int rbk = row0 >> 3, hs0 = cg * 12;
            {
                const int srow = rb * 128 + cg * 16 + (warp - 8) * 2 + (lane >> 4);
                uint4 xv[5];
#pragma unroll
                for (int i = 0; i < 5; i++) xv[i] = __ldg(reinterpret_cast<const uint4*>(x + (size_t)srow * DM) + (lane & 15) + 16 * i);
                float sm = 0.f;
#pragma unroll
                for (int i = 0; i < 5; i++)
                    sm += ((bf_lo(xv[i].x) + bf_hi(xv[i].x)) + (bf_lo(xv[i].y) + bf_hi(xv[i].y))) +
                          ((bf_lo(xv[i].z) + bf_hi(xv[i].z)) + (bf_lo(xv[i].w) + bf_hi(xv[i].w)));
#pragma unroll
                for (int o = 8; o; o >>= 1) sm += __shfl_xor_sync(~0u, sm, o);
                const float mu = sm * (1.f / DM);
                float q0 = 0.f, q1 = 0.f;
#pragma unroll
                for (int i = 0; i < 5; i++) {
                    const uint32_t w[4] = {xv[i].x, xv[i].y, xv[i].z, xv[i].w};
#pragma unroll
                    for (int j = 0; j < 4; j++) {
                        const float d0 = bf_lo(w[j]) - mu, d1 = bf_hi(w[j]) - mu;
                        q0 = fmaf(d0, d0, q0); q1 = fmaf(d1, d1, q1);
                    }
                }
                float q = q0 + q1;
#pragma unroll
                for (int o = 8; o; o >>= 1) q += __shfl_xor_sync(~0u, q, o);
                const float var = q * (1.f / DM);
                const float r1 = rsqrtf(var + LN_EPS);
                const float r2 = rsqrtf(var * r1 * r1 + LN_EPS);
                if ((lane & 15) == 0) g_stat[srow] = make_float4(mu, r1, r1 * r2, 0.f);
                __syncwarp();
                if (lane == 0) mbar_arrive(bar + B_STAT * 8);
            }
            float accA[100], accB[20];
            const uint64_t dA0 = make_desc(sAw, 16, 1024, 1), dB0 = make_desc(sB, 4096, 1024, 1);
#pragma unroll 2
            for (int it = 0; it < 20; it++) {
                const int s = it & 3;
                if (!(it & 1)) mbar_wait(bar + (B_A + (it >> 1)) * 8, 0);
                if (threadIdx.x == 256 && it == 0) TL(0, 2);
                if (threadIdx.x == 256) IT(0, it);
                mbar_wait(bar + (B_F1 + s) * 8, (it >> 2) & 1);
                if (threadIdx.x == 256) IT(1, it);
                const uint64_t dA = dA0 + (it >> 1) * 1024 + (it & 1) * 4, dB = dB0 + s * 1024;
                wg_fence();
                wgmma_n40_ss_tb(accB, dA, dB + 769, it > 0);
                wgmma_n40_ss_tb(accB, dA + 2, dB + 769 + 128, 1);
                wgmma_n200_ss_tb(accA, dA, dB, it > 0);
                wgmma_n200_ss_tb(accA, dA + 2, dB + 128, 1);
                wg_commit();
                if (it > 0) { wg_wait<1>(); release_stage(bar + (B_E1 + ((it - 1) & 3)) * 8, peer, lane); }
            }
            if (threadIdx.x == 256) IT(2, 0);
            mbar_wait(bar + B_AUX * 8, 0);
            if (threadIdx.x == 256) IT(2, 1);
            const float4 st0 = __ldcg(g_stat + row0), st1 = __ldcg(g_stat + row0 + 8);
            wg_wait<0>();
            release_stage(bar + (B_E1 + 3) * 8, peer, lane);
            fence_regs(accA);
            fence_regs(accB);
            if (threadIdx.x == 256) TL(1, 1);
            const float2* cs = reinterpret_cast<const float2*>(smem + SM_CS) + c;
            uint8_t* img = g_img + (size_t)hs0 * IMG_BYTES + rbk * 384 + g * 16 + c * 4;
            const bool emu0 = (EMU_MASK >> (rbk & 15)) & 1, emu1 = (EMU_MASK >> ((rbk + 1) & 15)) & 1;
            const bool low = c < 2;
            uint32_t pk[60];
#pragma unroll
            for (int m = 0; m < 6; m++) {
                const int which = (hs0 + 2 * m) >> 5;
                const float m0 = st0.y * (which == 0 ? QSCALE : (which == 1 && emu0) ? 2.f : 1.f);
                const float m1 = st1.y * (which == 0 ? QSCALE : (which == 1 && emu1) ? 2.f : 1.f);
                const float d0 = -st0.x * m0, d1 = -st1.x * m1;
                const float* a = m < 5 ? &accA[20 * m] : accB;
#pragma unroll
                for (int b = 0; b < 5; b++) {
                    const float2 cv = cs[(5 * m + b) * 4];
                    pk[10 * m + 2 * b] = pack_bf16(fmaf(a[4 * b], m0, d0 * cv.x), fmaf(a[4 * b + 1], m0, d0 * cv.y));
                    pk[10 * m + 2 * b + 1] = pack_bf16(fmaf(a[4 * b + 2], m1, d1 * cv.x), fmaf(a[4 * b + 3], m1, d1 * cv.y));
                }
            }
            const float r20 = 0.5f * st0.z, r21 = 0.5f * st1.z, e20 = -st0.x * r20, e21 = -st1.x * r21;
            if (threadIdx.x == 256) IT(2, 2);
            float acc2[96];
#pragma unroll
            for (int it = 0; it < 20; it++) {
                const int s = it % 5;
                if (threadIdx.x == 256) IT(0, 20 + it);
                mbar_wait(bar + (B_F2 + s) * 8, (it / 5) & 1);
                if (threadIdx.x == 256) IT(1, 20 + it);
                wg_fence();
                const uint64_t dA = make_desc(sAw + (it >> 1) * 16384 + (it & 1) * 64, 16, 1024, 1);
                const uint64_t dB = make_desc(sB + s * 12288, 4096, 1024, 1);
                if (it == 0) wgmma_n192_ss_tb_z(acc2, dA, dB); else wgmma_n192_ss_tb(acc2, dA, dB, 1);
                wgmma_n192_ss_tb(acc2, dA + 2, dB + 128, 1);
                wg_commit();
                if (it > 0) {
                    wg_wait<1>();
                    if (it <= 15) release_stage(bar + (B_E2 + (it - 1) % 5) * 8, peer, lane);
                    if (it == 14 && lane == 0) mbar_arrive(bar + B_DEAD * 8);
                }
                if (it < 12) {
                    const int m = it / 2, part = it % 2;
                    const int hs = hs0 + 2 * m, which = hs >> 5;
                    const uint32_t* a = pk + 10 * m;
                    uint8_t* pe = img + (2 * m) * IMG_BYTES;
                    uint8_t* po = pe + IMG_BYTES;
                    if (part == 0) {
                        const uint32_t padv = which == 0 ? 0x3F803F80u : which == 1 ? 0xBFFF4440u : 0x00003F80u;
                        const uint32_t p0 = ((c & 1) || (which == 1 && !emu0)) ? 0u : padv;
                        const uint32_t p1 = ((c & 1) || (which == 1 && !emu1)) ? 0u : padv;
                        *(uint32_t*)(pe) = a[0];
                        *(uint32_t*)(pe + 128) = a[2];
                        *(uint32_t*)(pe + 256) = low ? a[4] : p0;
                        *(uint32_t*)(pe + 384) = a[1];
                        *(uint32_t*)(pe + 512) = a[3];
                        *(uint32_t*)(pe + 640) = low ? a[5] : p1;
                        *(uint32_t*)(po + 256) = low ? p0 : a[4];
                        *(uint32_t*)(po + 640) = low ? p1 : a[5];
                    } else {
                        *(uint32_t*)(po) = a[6];
                        *(uint32_t*)(po + 128) = a[8];
                        *(uint32_t*)(po + 384) = a[7];
                        *(uint32_t*)(po + 512) = a[9];
                        if (which < 2) {
                            const uint32_t u0 = bf2_fma(a[4], a[4], 0u), u1 = bf2_fma(a[5], a[5], 0u);
                            const uint32_t pe0 = bf2_fma(a[0], a[0], bf2_fma(a[2], a[2], low ? u0 : 0u));
                            const uint32_t pe1 = bf2_fma(a[1], a[1], bf2_fma(a[3], a[3], low ? u1 : 0u));
                            const uint32_t po0 = bf2_fma(a[6], a[6], bf2_fma(a[8], a[8], low ? 0u : u0));
                            const uint32_t po1 = bf2_fma(a[7], a[7], bf2_fma(a[9], a[9], low ? 0u : u1));
                            const float e0 = bf_lo(pe0) + bf_hi(pe0), e1 = bf_lo(pe1) + bf_hi(pe1);
                            const float o0 = bf_lo(po0) + bf_hi(po0), o1 = bf_lo(po1) + bf_hi(po1);
                            const bool b0 = c & 1, b1_ = c & 2;
                            const float x0 = (b0 ? e1 : e0) + __shfl_xor_sync(~0u, b0 ? e0 : e1, 1);
                            const float x1 = (b0 ? o1 : o0) + __shfl_xor_sync(~0u, b0 ? o0 : o1, 1);
                            float y = (b1_ ? x1 : x0) + __shfl_xor_sync(~0u, b1_ ? x0 : x1, 2);
                            if (which == 1 && (b0 ? emu1 : emu0)) y *= 0.25f;
                            g_nrm[(hs + (c >> 1)) * SEQ + row0 + (c & 1) * 8] = y;
                        }
                    }
                    if (it == 11) { __syncwarp(); if (lane == 0) mbar_arrive(bar + B_ST * 8); }
                }
            }
            wg_wait<0>();
            fence_regs(acc2);
            if (lane == 0) mbar_arrive(bar + (B_DEAD + 1) * 8);
            if (threadIdx.x == 256) TL(1, 2);
            mbar_wait(bar + B_AUX2 * 8, 0);
            if (threadIdx.x == 256) TL(4, 0);
            const uint32_t* bias = reinterpret_cast<const uint32_t*>(smem + SM_BIAS) + c;
            const int mrow = w4 * 16 + (lane & 15);
            const uint32_t stage = sAw + 7 * 16384;
            const uint32_t st_row = stage + mrow * 128;
#pragma unroll
            for (int j = 0; j < 24; j += 2) {
                const uint32_t bA = bias[j * 4], bB = bias[j * 4 + 4];
                const float2 cA = cs[(30 + j) * 4], cB = cs[(31 + j) * 4];
                const float* a = acc2 + j * 4;
                const uint32_t r00 = pack_bf16(gelu_half(fmaf(a[0], r20, fmaf(e20, cA.x, bf_lo(bA)))), gelu_half(fmaf(a[1], r20, fmaf(e20, cA.y, bf_hi(bA)))));
                const uint32_t r10 = pack_bf16(gelu_half(fmaf(a[2], r21, fmaf(e21, cA.x, bf_lo(bA)))), gelu_half(fmaf(a[3], r21, fmaf(e21, cA.y, bf_hi(bA)))));
                const uint32_t r01 = pack_bf16(gelu_half(fmaf(a[4], r20, fmaf(e20, cB.x, bf_lo(bB)))), gelu_half(fmaf(a[5], r20, fmaf(e20, cB.y, bf_hi(bB)))));
                const uint32_t r11 = pack_bf16(gelu_half(fmaf(a[6], r21, fmaf(e21, cB.x, bf_lo(bB)))), gelu_half(fmaf(a[7], r21, fmaf(e21, cB.y, bf_hi(bB)))));
                const int chunk = (j & 7) + (lane >> 4);
                stmatrix_x4(st_row + (j >> 3) * 16384 + ((chunk ^ (mrow & 7)) << 4), r00, r10, r01, r11);
            }
            if (threadIdx.x == 256) TL(4, 1);
            fence_proxy_async();
            __syncwarp();
            if (lane == 0) mbar_arrive(bar + (B_ST + 1) * 8);
            asm volatile("bar.sync %0, 128;" ::"r"(wgi + 3) : "memory");
            reg_dealloc<128>();
            if (threadIdx.x == 256) TL(4, 3);
        }
        __syncthreads();
        if (threadIdx.x == 0) TL(1, 3);
    }

    {
        const int h = blockIdx.x >> 2, qb = blockIdx.x & 3;
        const uint32_t sK = sb + SM_K, sV = sb + SM_V, barKV = bar + B_KV * 8;
        if (threadIdx.x == 0) TL(2, 0);
        auto late_tiles = [&]() {
            if (warp == 5 && lane == 0) {
                bulk_wait_read();
                asm volatile("fence.proxy.async.global;" ::: "memory");
                const uint8_t* gK = g_img + (size_t)(32 + h) * IMG_BYTES;
                const uint8_t* gV = g_img + (size_t)(64 + h) * IMG_BYTES;
                for (int i = 9; i < 16; i++) {
                    if (i >= 13) mbar_expect_tx(barKV + i * 8, i < 15 ? 12288 : 6144);
                    bulk_load(sV + ((i + 7) & 15) * 6144, gV + i * 6144, 6144, barKV + i * 8);
                    if (i >= 13 && i < 15) bulk_load(sK + (i + 1) * 6144, gK + (i + 1) * 6144, 6144, barKV + i * 8);
                }
            }
            __syncwarp();
        };
        const bool safe = __all_sync(~0u, *reinterpret_cast<volatile uint32_t*>(smem + SM_SAFE) != 0);
        if (threadIdx.x == 0) TL(2, 1);
        const uint64_t dK0 = make_desc(sK, 128, 384, 0), dV0 = make_desc(sV, 384, 128, 0);
        auto publish_h = [&]() {
            if (warp == 5) {
                if (lane == 0) { bulk_wait_all(); cnt_signal(CNT_H + rb); }
                __syncwarp();
            }
        };
        if (!safe) {
            late_tiles();
#pragma unroll 1
            for (int pass = 0; pass < 2; pass++) {
                const uint32_t sQ = sb + SM_Q + pass * 12288 + wgi * 3072;
                mbar_wait(bar + (B_Q + pass) * 8, 0);
                attn_rows_maxshift(sK, barKV, make_desc(sQ, 128, 384, 0), make_desc(sQ + 256, sb + SM_ZERO - (sQ + 256), 384, 0), h,
                                   qb * 512 + pass * 256 + wgi * 64 + w4 * 16);
                if (pass == 0) publish_h();
            }
        } else {
            const ExpConst kc = make_exp_const();
#pragma unroll 1
            for (int pass = 0; pass < 2; pass++) {
                const int rbase = qb * 512 + pass * 256 + wgi * 64 + w4 * 16;
                const uint32_t sQ = sb + SM_Q + pass * 12288 + wgi * 3072;
                const uint64_t dQ = make_desc(sQ, 128, 384, 0), dQ2 = make_desc(sQ + 256, sb + SM_ZERO - (sQ + 256), 384, 0);
                float o[12], sa[32], sc[32];
                uint32_t p[16];
#pragma unroll
                for (int i = 0; i < 12; i++) o[i] = 0.f;
                fence_regs(o);
                mbar_wait(bar + (B_Q + pass) * 8, 0);
                mbar_wait(barKV + 128, 0);
                qk_tile(sa, dQ, dQ2, dK0);
                wg_wait<0>();
                fence_regs(sa);
                uint64_t dK = dK0, dV = dV0 + 7 * 384;
                uint32_t bj = barKV;
#pragma unroll 1
                for (int j = 0; j < 16; j++) {
                    mbar_wait(bj, 0);
                    if (pass == 0 && j == 2) late_tiles();
                    qk_tile(sc, dQ, dQ2, dK + 192);
                    wg_wait<1>();
                    exp_tile<0>(sa, p, kc);
                    pv_tile(o, p, dV);
                    wg_wait<1>();
                    fence_regs(sc);
                    mbar_wait(bj, 0);
                    qk_tile(sa, dQ, dQ2, dK + 384);
                    wg_wait<1>();
                    exp_tile<8>(sc, p, kc);
                    pv_tile(o, p, dV + 192);
                    wg_wait<1>();
                    fence_regs(sa);
                    dK += 384; dV = j == 8 ? dV0 : dV + 384; bj += 8;
                }
                wg_wait<0>();
                fence_regs(o);
                store_o(o, h, rbase, lane);
                if (threadIdx.x == 0) TL(2, 2 + pass);
                if (pass == 0) publish_h();
            }
        }
        __syncthreads();
        if (threadIdx.x == 64) cnt_signal(CNT_O + qb);
        cluster_arrive_relaxed();
    }

    {
        const uint32_t epoch = *reinterpret_cast<volatile uint32_t*>(smem + SM_EPOCH);
        const int ct = cl & 3, rt = (cl >> 2) * 2 + rank;
        if (threadIdx.x == 0) TL(3, 0);
        const int orow = threadIdx.x >> 3, oseg = threadIdx.x & 7;
        const size_t ooff = (size_t)(rt * 64 + orow) * DM + ct * 160 + oseg * 20;
        uint2 xr[5], br[5];
#pragma unroll
        for (int i = 0; i < 5; i++) {
            xr[i] = __ldg(reinterpret_cast<const uint2*>(x + ooff) + i);
            br[i] = __ldg(reinterpret_cast<const uint2*>(b2 + ct * 160 + oseg * 20) + i);
        }
        cluster_wait();
        float* stg = reinterpret_cast<float*>(smem);
        if (warp == 4) {
            if (elect_one()) { prefetch_map(&tm.h); prefetch_map(&tm.o); prefetch_map(&tm.w2); prefetch_map(&tm.wo); cnt_wait(CNT_H + (rt >> 1), (epoch + 1) * 8); }
            __syncwarp();
#pragma unroll 1
            for (int kb = 0; kb < 34; kb++) {
                const int s = kb & 7;
                if (kb >= 8) mbar_wait(bar + (B_E3 + s) * 8, ((kb >> 3) - 1) & 1);
                if (elect_one()) {
                    if (kb == 24) { cnt_wait(CNT_O + (rt >> 3), (epoch + 1) * 32); TL(3, 1); }
                    const uint32_t dst = sb + s * G2_STAGE, fb = bar + (B_F3 + s) * 8;
                    const CUtensorMap* mA = kb < 24 ? &tm.h : &tm.o;
                    const CUtensorMap* mB = kb < 24 ? &tm.w2 : &tm.wo;
                    const int k0 = (kb < 24 ? kb : kb - 24) * 64;
                    mbar_expect_tx(fb, G2_STAGE);
                    tma_load(dst, mA, k0, rt * 64, fb);
                    const int first = ((kb & 1) == (int)rank) ? 0 : 3, last = ((kb & 1) == (int)rank) ? 3 : 5;
                    for (int b = first; b < last; b++) tma_load_mc(dst + 8192 + b * 4096, mB, ct * 160 + b * 32, k0, fb, 3);
                }
                __syncwarp();
            }
        } else if (wgi == 0) {
            float acc[80];
#pragma unroll 1
            for (int kb = 0; kb < 34; kb++) {
                const int s = kb & 7;
                mbar_wait(bar + (B_F3 + s) * 8, (kb >> 3) & 1);
                wg_fence();
                const uint64_t dA = make_desc(sb + s * G2_STAGE, 16, 1024, 1);
                const uint64_t dB = make_desc(sb + s * G2_STAGE + 8192, 4096, 512, 2);
#pragma unroll
                for (int kk = 0; kk < 4; kk++) wgmma_n160_ss_tb(acc, dA + kk * 2, dB + kk * 64, (kb | kk) != 0);
                wg_commit();
                if (kb > 0) {
                    wg_wait<1>();
                    if (kb <= 26) release_stage(bar + (B_E3 + ((kb - 1) & 7)) * 8, peer, lane);
                }
            }
            wg_wait<0>();
            fence_regs(acc);
            if (threadIdx.x == 0) TL(3, 2);
            const int r = w4 * 16 + g;
#pragma unroll
            for (int j = 0; j < 20; j++) {
                *reinterpret_cast<float2*>(stg + r * 168 + j * 8 + 2 * c) = make_float2(acc[4 * j], acc[4 * j + 1]);
                *reinterpret_cast<float2*>(stg + (r + 8) * 168 + j * 8 + 2 * c) = make_float2(acc[4 * j + 2], acc[4 * j + 3]);
            }
        }
        __syncthreads();
        const float4* sp = reinterpret_cast<const float4*>(stg + orow * 168 + oseg * 20);
#pragma unroll
        for (int i = 0; i < 5; i++) {
            const float4 a = sp[i];
            uint2 w;
            w.x = pack_bf16(a.x + bf_lo(br[i].x) + bf_lo(xr[i].x), a.y + bf_hi(br[i].x) + bf_hi(xr[i].x));
            w.y = pack_bf16(a.z + bf_lo(br[i].y) + bf_lo(xr[i].y), a.w + bf_hi(br[i].y) + bf_hi(xr[i].y));
            reinterpret_cast<uint2*>(out + ooff)[i] = w;
        }
        if (blockIdx.x == 0 && threadIdx.x == 0) g_epoch = epoch + 1;
        if (threadIdx.x == 0) TL(3, 3);
    }
    cluster_arrive_relaxed();
    cluster_wait();
}

typedef CUresult (*EncodeTiledFn)(CUtensorMap*, CUtensorMapDataType, cuuint32_t, void*, const cuuint64_t*,
                                  const cuuint64_t*, const cuuint32_t*, const cuuint32_t*, CUtensorMapInterleave,
                                  CUtensorMapSwizzle, CUtensorMapL2promotion, CUtensorMapFloatOOBfill);

CUtensorMap make_map(EncodeTiledFn enc, const void* ptr, int rows, int cols, int box_rows, int box_cols,
                     CUtensorMapSwizzle swz) {
    CUtensorMap m;
    cuuint64_t gd[2] = {(cuuint64_t)cols, (cuuint64_t)rows};
    cuuint64_t gs[1] = {(cuuint64_t)cols * 2};
    cuuint32_t bd[2] = {(cuuint32_t)box_cols, (cuuint32_t)box_rows};
    cuuint32_t es[2] = {1, 1};
    enc(&m, CU_TENSOR_MAP_DATA_TYPE_BFLOAT16, 2, const_cast<void*>(ptr), gd, gs, bd, es, CU_TENSOR_MAP_INTERLEAVE_NONE,
        swz, CU_TENSOR_MAP_L2_PROMOTION_L2_128B, CU_TENSOR_MAP_FLOAT_OOB_FILL_NONE);
    return m;
}

}

extern "C" void kernel_launch(void* const* d_in, const int* in_sizes, int n_in, void* d_out, int out_size) {
    (void)in_sizes; (void)n_in; (void)out_size;
    const __nv_bfloat16* x = (const __nv_bfloat16*)d_in[0];
    const __nv_bfloat16* wqkv = (const __nv_bfloat16*)d_in[1];
    const __nv_bfloat16* wo = (const __nv_bfloat16*)d_in[2];
    const __nv_bfloat16* w1 = (const __nv_bfloat16*)d_in[4];
    const __nv_bfloat16* b1 = (const __nv_bfloat16*)d_in[5];
    const __nv_bfloat16* w2 = (const __nv_bfloat16*)d_in[6];
    const __nv_bfloat16* b2 = (const __nv_bfloat16*)d_in[7];
    __nv_bfloat16* out = (__nv_bfloat16*)d_out;

    static EncodeTiledFn enc = nullptr;
    static void *p_h, *p_o;
    if (!enc) {
        cudaDriverEntryPointQueryResult qr;
        cudaGetDriverEntryPoint("cuTensorMapEncodeTiled", (void**)&enc, cudaEnableDefault, &qr);
        cudaGetSymbolAddress(&p_h, g_h);
        cudaGetSymbolAddress(&p_o, g_o);
        cudaFuncSetAttribute(k_fused, cudaFuncAttributeMaxDynamicSharedMemorySize, SM_TOTAL);
    }
    Maps tm;
    tm.x = make_map(enc, x, SEQ, DM, 128, 64, CU_TENSOR_MAP_SWIZZLE_128B);
    tm.wqkv = make_map(enc, wqkv, DM, 3 * DM, 32, 64, CU_TENSOR_MAP_SWIZZLE_128B);
    tm.w1 = make_map(enc, w1, DM, FF, 32, 64, CU_TENSOR_MAP_SWIZZLE_128B);
    tm.h = make_map(enc, p_h, SEQ, FF, 64, 64, CU_TENSOR_MAP_SWIZZLE_128B);
    tm.o = make_map(enc, p_o, SEQ, DM, 64, 64, CU_TENSOR_MAP_SWIZZLE_128B);
    tm.wo = make_map(enc, wo, DM, DM, 64, 32, CU_TENSOR_MAP_SWIZZLE_64B);
    tm.w2 = make_map(enc, w2, FF, DM, 64, 32, CU_TENSOR_MAP_SWIZZLE_64B);
    k_fused<<<128, 512, SM_TOTAL, cudaStreamPerThread>>>(tm, x, (const uint8_t*)wqkv, (const uint8_t*)w1, (const uint8_t*)w2,
                                                         (const uint8_t*)wo, b1, b2, out);
}
```

```cpp
#include <cuda_runtime.h>
#include <cuda_bf16.h>
#include <cuda.h>
#include <stdint.h>

namespace {

constexpr int SEQ = 2048, DM = 640, FF = 1536;
constexpr float LN_EPS = 1e-5f;

constexpr int IMG_BYTES = 256 * 384;
constexpr uint32_t EMU_MASK = 0xD5D5u;
constexpr float SAFE_BOUND = 80.0f;
#define XV_IT 1
#define PACE_NS 200
constexpr float QSCALE = 0.22360679774997896f * 1.4426950408889634f;

__device__ float4 g_stat[SEQ];
__device__ float2 g_csp[16 * 1728];
__device__ __align__(1024) uint8_t g_img[96 * IMG_BYTES + 1024];
__device__ float g_nrm[64 * SEQ];
__device__ __align__(1024) __nv_bfloat16 g_h[SEQ * FF];
__device__ __align__(1024) __nv_bfloat16 g_o[SEQ * DM];
constexpr int CNT_ST = 0, CNT_QKV = 16, CNT_H = 24, CNT_O = 40, CNT_CS = 44, CNT_CS2 = 52;
__device__ uint32_t g_cnt[60 * 32];
__device__ uint32_t g_epoch;

#define TL(kern, slot) do { } while (0)
#define IT(row, i) do { } while (0)

__device__ __forceinline__ uint32_t smem_u32(const void* p) { return (uint32_t)__cvta_generic_to_shared(p); }
__device__ __forceinline__ void mbar_init(uint32_t bar, int cnt) {
    asm volatile("mbarrier.init.shared::cta.b64 [%0], %1;" ::"r"(bar), "r"(cnt));
}
__device__ __forceinline__ void mbar_expect_tx(uint32_t bar, uint32_t bytes) {
    asm volatile("mbarrier.arrive.expect_tx.shared::cta.b64 _, [%0], %1;" ::"r"(bar), "r"(bytes) : "memory");
}
__device__ __forceinline__ void mbar_wait(uint32_t bar, uint32_t parity) {
    asm volatile("{\n.reg .pred p;\n.reg .u32 n;\nmov.u32 n, 0;\n"
                 "WAIT_LOOP:\nmbarrier.try_wait.parity.shared::cta.b64 p, [%0], %1;\n@p bra WAIT_DONE;\n"
                 "add.u32 n, n, 1;\nsetp.lt.u32 p, n, 4194304;\n@p bra WAIT_LOOP;\nWAIT_DONE:\n}"
                 ::"r"(bar), "r"(parity) : "memory");
}
__device__ __forceinline__ void mbar_arrive(uint32_t bar) {
    asm volatile("mbarrier.arrive.shared::cta.b64 _, [%0];" ::"r"(bar) : "memory");
}
__device__ __forceinline__ void mbar_arrive_cluster(uint32_t bar, uint32_t cta) {
    asm volatile("{\n.reg .b32 ra;\nmapa.shared::cluster.u32 ra, %0, %1;\n"
                 "mbarrier.arrive.shared::cluster.b64 _, [ra];\n}" ::"r"(bar), "r"(cta) : "memory");
}
__device__ __forceinline__ void fence_barrier_init() { asm volatile("fence.mbarrier_init.release.cluster;" ::: "memory"); }
__device__ __forceinline__ void fence_proxy_async() { asm volatile("fence.proxy.async.shared::cta;" ::: "memory"); }
__device__ __forceinline__ void cluster_sync() {
    asm volatile("barrier.cluster.arrive.release.aligned;\nbarrier.cluster.wait.acquire.aligned;" ::: "memory");
}
__device__ __forceinline__ bool elect_one() {
    uint32_t pred;
    asm volatile("{\n.reg .pred p;\nelect.sync _|p, 0xFFFFFFFF;\nselp.b32 %0, 1, 0, p;\n}" : "=r"(pred));
    return pred != 0;
}
__device__ __forceinline__ void pdl_launch() { asm volatile("griddepcontrol.launch_dependents;" ::: "memory"); }
__device__ __forceinline__ void pdl_wait() { asm volatile("griddepcontrol.wait;" ::: "memory"); }
__device__ __forceinline__ void prefetch_map(const CUtensorMap* m) {
    asm volatile("prefetch.tensormap [%0];" ::"l"(m) : "memory");
}
__device__ __forceinline__ void tma_load(uint32_t dst, const CUtensorMap* m, int c0, int c1, uint32_t bar) {
    asm volatile("cp.async.bulk.tensor.2d.shared::cluster.global.mbarrier::complete_tx::bytes [%0], [%1, {%3, %4}], [%2];"
                 ::"r"(dst), "l"(m), "r"(bar), "r"(c0), "r"(c1) : "memory");
}
__device__ __forceinline__ void tma_load_mc(uint32_t dst, const CUtensorMap* m, int c0, int c1, uint32_t bar, uint16_t mask) {
    asm volatile("cp.async.bulk.tensor.2d.shared::cluster.global.mbarrier::complete_tx::bytes.multicast::cluster"
                 " [%0], [%1, {%3, %4}], [%2], %5;"
                 ::"r"(dst), "l"(m), "r"(bar), "r"(c0), "r"(c1), "h"(mask) : "memory");
}
__device__ __forceinline__ void tma_store(const CUtensorMap* m, uint32_t src, int c0, int c1) {
    asm volatile("cp.async.bulk.tensor.2d.global.shared::cta.bulk_group [%0, {%2, %3}], [%1];"
                 ::"l"(m), "r"(src), "r"(c0), "r"(c1) : "memory");
}
__device__ __forceinline__ void bulk_commit() { asm volatile("cp.async.bulk.commit_group;" ::: "memory"); }
__device__ __forceinline__ void bulk_wait_all() { asm volatile("cp.async.bulk.wait_group 0;" ::: "memory"); }
__device__ __forceinline__ void bulk_load(uint32_t dst, const void* src, uint32_t bytes, uint32_t bar) {
    asm volatile("cp.async.bulk.shared::cluster.global.mbarrier::complete_tx::bytes [%0], [%1], %2, [%3];"
                 ::"r"(dst), "l"(src), "r"(bytes), "r"(bar) : "memory");
}
__device__ __forceinline__ void prefetch_l2(const void* p, uint32_t bytes) {
    asm volatile("cp.async.bulk.prefetch.L2.global [%0], %1;" ::"l"(p), "r"(bytes) : "memory");
}
__device__ __forceinline__ void tma_prefetch_l2(const CUtensorMap* m, int c0, int c1) {
    asm volatile("cp.async.bulk.prefetch.tensor.2d.L2.global.tile [%0, {%1, %2}];" ::"l"(m), "r"(c0), "r"(c1) : "memory");
}
__device__ __forceinline__ void wg_fence() { asm volatile("wgmma.fence.sync.aligned;" ::: "memory"); }
__device__ __forceinline__ void wg_commit() { asm volatile("wgmma.commit_group.sync.aligned;" ::: "memory"); }
template <int N> __device__ __forceinline__ void wg_wait() {
    asm volatile("wgmma.wait_group.sync.aligned %0;" ::"n"(N) : "memory");
}
template <int N> __device__ __forceinline__ void reg_alloc() { asm volatile("setmaxnreg.inc.sync.aligned.u32 %0;" ::"n"(N)); }
template <int N> __device__ __forceinline__ void reg_dealloc() { asm volatile("setmaxnreg.dec.sync.aligned.u32 %0;" ::"n"(N)); }
template <int N> __device__ __forceinline__ void fence_regs(float (&d)[N]) {
#pragma unroll
    for (int i = 0; i < N; i++) asm volatile("" : "+f"(d[i])::"memory");
}
__device__ __forceinline__ uint64_t make_desc(uint32_t addr, uint32_t lbo, uint32_t sbo, uint32_t swz) {
    return (uint64_t)((addr & 0x3FFFF) >> 4) | ((uint64_t)(lbo >> 4) << 16) | ((uint64_t)(sbo >> 4) << 32) |
           ((uint64_t)swz << 62);
}
__device__ __forceinline__ uint32_t pack_bf16(float lo, float hi) {
    uint32_t r;
    asm("cvt.rn.bf16x2.f32 %0, %1, %2;" : "=r"(r) : "f"(hi), "f"(lo));
    return r;
}
__device__ __forceinline__ float ex2(float x) {
    float r;
    asm("ex2.approx.ftz.f32 %0, %1;" : "=f"(r) : "f"(x));
    return r;
}
__device__ __forceinline__ float bf_lo(uint32_t v) { return __uint_as_float(v << 16); }
__device__ __forceinline__ float bf_hi(uint32_t v) { return __uint_as_float(v & 0xFFFF0000u); }
__device__ __forceinline__ void stmatrix_x4(uint32_t addr, uint32_t r0, uint32_t r1, uint32_t r2, uint32_t r3) {
    asm volatile("stmatrix.sync.aligned.m8n8.x4.shared.b16 [%0], {%1, %2, %3, %4};"
                 ::"r"(addr), "r"(r0), "r"(r1), "r"(r2), "r"(r3) : "memory");
}

__device__ __forceinline__ void wgmma_n200_ss_tb(float (&d)[100], uint64_t descA, uint64_t descB, int scaleD) {
    asm volatile("{\n.reg .pred p;\nsetp.ne.b32 p, %102, 0;\n"
        "wgmma.mma_async.sync.aligned.m64n200k16.f32.bf16.bf16 {"
        "%0, %1, %2, %3, %4, %5, %6, %7, %8, %9, %10, %11, %12, %13, %14, %15, "
        "%16, %17, %18, %19, %20, %21, %22, %23, %24, %25, %26, %27, %28, %29, %30, %31, "
        "%32, %33, %34, %35, %36, %37, %38, %39, %40, %41, %42, %43, %44, %45, %46, %47, "
        "%48, %49, %50, %51, %52, %53, %54, %55, %56, %57, %58, %59, %60, %61, %62, %63, "
        "%64, %65, %66, %67, %68, %69, %70, %71, %72, %73, %74, %75, %76, %77, %78, %79, "
        "%80, %81, %82, %83, %84, %85, %86, %87, %88, %89, %90, %91, %92, %93, %94, %95, "
        "%96, %97, %98, %99}, "
        "%100, %101, p, 1, 1, 0, 1;\n}\n"
        : "+f"(d[0]), "+f"(d[1]), "+f"(d[2]), "+f"(d[3]), "+f"(d[4]), "+f"(d[5]), "+f"(d[6]), "+f"(d[7]),
          "+f"(d[8]), "+f"(d[9]), "+f"(d[10]), "+f"(d[11]), "+f"(d[12]), "+f"(d[13]), "+f"(d[14]), "+f"(d[15]),
          "+f"(d[16]), "+f"(d[17]), "+f"(d[18]), "+f"(d[19]), "+f"(d[20]), "+f"(d[21]), "+f"(d[22]), "+f"(d[23]),
          "+f"(d[24]), "+f"(d[25]), "+f"(d[26]), "+f"(d[27]), "+f"(d[28]), "+f"(d[29]), "+f"(d[30]), "+f"(d[31]),
          "+f"(d[32]), "+f"(d[33]), "+f"(d[34]), "+f"(d[35]), "+f"(d[36]), "+f"(d[37]), "+f"(d[38]), "+f"(d[39]),
          "+f"(d[40]), "+f"(d[41]), "+f"(d[42]), "+f"(d[43]), "+f"(d[44]), "+f"(d[45]), "+f"(d[46]), "+f"(d[47]),
          "+f"(d[48]), "+f"(d[49]), "+f"(d[50]), "+f"(d[51]), "+f"(d[52]), "+f"(d[53]), "+f"(d[54]), "+f"(d[55]),
          "+f"(d[56]), "+f"(d[57]), "+f"(d[58]), "+f"(d[59]), "+f"(d[60]), "+f"(d[61]), "+f"(d[62]), "+f"(d[63]),
          "+f"(d[64]), "+f"(d[65]), "+f"(d[66]), "+f"(d[67]), "+f"(d[68]), "+f"(d[69]), "+f"(d[70]), "+f"(d[71]),
          "+f"(d[72]), "+f"(d[73]), "+f"(d[74]), "+f"(d[75]), "+f"(d[76]), "+f"(d[77]), "+f"(d[78]), "+f"(d[79]),
          "+f"(d[80]), "+f"(d[81]), "+f"(d[82]), "+f"(d[83]), "+f"(d[84]), "+f"(d[85]), "+f"(d[86]), "+f"(d[87]),
          "+f"(d[88]), "+f"(d[89]), "+f"(d[90]), "+f"(d[91]), "+f"(d[92]), "+f"(d[93]), "+f"(d[94]), "+f"(d[95]),
          "+f"(d[96]), "+f"(d[97]), "+f"(d[98]), "+f"(d[99])
        : "l"(descA), "l"(descB), "r"(scaleD));
}

__device__ __forceinline__ void wgmma_n40_ss_tb(float (&d)[20], uint64_t descA, uint64_t descB, int scaleD) {
    asm volatile("{\n.reg .pred p;\nsetp.ne.b32 p, %22, 0;\n"
        "wgmma.mma_async.sync.aligned.m64n40k16.f32.bf16.bf16 {"
        "%0, %1, %2, %3, %4, %5, %6, %7, %8, %9, %10, %11, %12, %13, %14, %15, "
        "%16, %17, %18, %19}, "
        "%20, %21, p, 1, 1, 0, 1;\n}\n"
        : "+f"(d[0]), "+f"(d[1]), "+f"(d[2]), "+f"(d[3]), "+f"(d[4]), "+f"(d[5]), "+f"(d[6]), "+f"(d[7]),
          "+f"(d[8]), "+f"(d[9]), "+f"(d[10]), "+f"(d[11]), "+f"(d[12]), "+f"(d[13]), "+f"(d[14]), "+f"(d[15]),
          "+f"(d[16]), "+f"(d[17]), "+f"(d[18]), "+f"(d[19])
        : "l"(descA), "l"(descB), "r"(scaleD));
}

__device__ __forceinline__ void wgmma_n192_ss_tb(float (&d)[96], uint64_t descA, uint64_t descB, int scaleD) {
    asm volatile("{\n.reg .pred p;\nsetp.ne.b32 p, %98, 0;\n"
        "wgmma.mma_async.sync.aligned.m64n192k16.f32.bf16.bf16 {"
        "%0, %1, %2, %3, %4, %5, %6, %7, %8, %9, %10, %11, %12, %13, %14, %15, "
        "%16, %17, %18, %19, %20, %21, %22, %23, %24, %25, %26, %27, %28, %29, %30, %31, "
        "%32, %33, %34, %35, %36, %37, %38, %39, %40, %41, %42, %43, %44, %45, %46, %47, "
        "%48, %49, %50, %51, %52, %53, %54, %55, %56, %57, %58, %59, %60, %61, %62, %63, "
        "%64, %65, %66, %67, %68, %69, %70, %71, %72, %73, %74, %75, %76, %77, %78, %79, "
        "%80, %81, %82, %83, %84, %85, %86, %87, %88, %89, %90, %91, %92, %93, %94, %95}, "
        "%96, %97, p, 1, 1, 0, 1;\n}\n"
        : "+f"(d[0]), "+f"(d[1]), "+f"(d[2]), "+f"(d[3]), "+f"(d[4]), "+f"(d[5]), "+f"(d[6]), "+f"(d[7]),
          "+f"(d[8]), "+f"(d[9]), "+f"(d[10]), "+f"(d[11]), "+f"(d[12]), "+f"(d[13]), "+f"(d[14]), "+f"(d[15]),
          "+f"(d[16]), "+f"(d[17]), "+f"(d[18]), "+f"(d[19]), "+f"(d[20]), "+f"(d[21]), "+f"(d[22]), "+f"(d[23]),
          "+f"(d[24]), "+f"(d[25]), "+f"(d[26]), "+f"(d[27]), "+f"(d[28]), "+f"(d[29]), "+f"(d[30]), "+f"(d[31]),
          "+f"(d[32]), "+f"(d[33]), "+f"(d[34]), "+f"(d[35]), "+f"(d[36]), "+f"(d[37]), "+f"(d[38]), "+f"(d[39]),
          "+f"(d[40]), "+f"(d[41]), "+f"(d[42]), "+f"(d[43]), "+f"(d[44]), "+f"(d[45]), "+f"(d[46]), "+f"(d[47]),
          "+f"(d[48]), "+f"(d[49]), "+f"(d[50]), "+f"(d[51]), "+f"(d[52]), "+f"(d[53]), "+f"(d[54]), "+f"(d[55]),
          "+f"(d[56]), "+f"(d[57]), "+f"(d[58]), "+f"(d[59]), "+f"(d[60]), "+f"(d[61]), "+f"(d[62]), "+f"(d[63]),
          "+f"(d[64]), "+f"(d[65]), "+f"(d[66]), "+f"(d[67]), "+f"(d[68]), "+f"(d[69]), "+f"(d[70]), "+f"(d[71]),
          "+f"(d[72]), "+f"(d[73]), "+f"(d[74]), "+f"(d[75]), "+f"(d[76]), "+f"(d[77]), "+f"(d[78]), "+f"(d[79]),
          "+f"(d[80]), "+f"(d[81]), "+f"(d[82]), "+f"(d[83]), "+f"(d[84]), "+f"(d[85]), "+f"(d[86]), "+f"(d[87]),
          "+f"(d[88]), "+f"(d[89]), "+f"(d[90]), "+f"(d[91]), "+f"(d[92]), "+f"(d[93]), "+f"(d[94]), "+f"(d[95])
        : "l"(descA), "l"(descB), "r"(scaleD));
}

__device__ __forceinline__ void wgmma_n192_ss_tb_z(float (&d)[96], uint64_t descA, uint64_t descB) {
    asm volatile("{\n.reg .pred p;\nsetp.ne.b32 p, 0, 0;\n"
        "wgmma.mma_async.sync.aligned.m64n192k16.f32.bf16.bf16 {"
        "%0, %1, %2, %3, %4, %5, %6, %7, %8, %9, %10, %11, %12, %13, %14, %15, "
        "%16, %17, %18, %19, %20, %21, %22, %23, %24, %25, %26, %27, %28, %29, %30, %31, "
        "%32, %33, %34, %35, %36, %37, %38, %39, %40, %41, %42, %43, %44, %45, %46, %47, "
        "%48, %49, %50, %51, %52, %53, %54, %55, %56, %57, %58, %59, %60, %61, %62, %63, "
        "%64, %65, %66, %67, %68, %69, %70, %71, %72, %73, %74, %75, %76, %77, %78, %79, "
        "%80, %81, %82, %83, %84, %85, %86, %87, %88, %89, %90, %91, %92, %93, %94, %95}, "
        "%96, %97, p, 1, 1, 0, 1;\n}\n"
        : "=f"(d[0]), "=f"(d[1]), "=f"(d[2]), "=f"(d[3]), "=f"(d[4]), "=f"(d[5]), "=f"(d[6]), "=f"(d[7]),
          "=f"(d[8]), "=f"(d[9]), "=f"(d[10]), "=f"(d[11]), "=f"(d[12]), "=f"(d[13]), "=f"(d[14]), "=f"(d[15]),
          "=f"(d[16]), "=f"(d[17]), "=f"(d[18]), "=f"(d[19]), "=f"(d[20]), "=f"(d[21]), "=f"(d[22]), "=f"(d[23]),
          "=f"(d[24]), "=f"(d[25]), "=f"(d[26]), "=f"(d[27]), "=f"(d[28]), "=f"(d[29]), "=f"(d[30]), "=f"(d[31]),
          "=f"(d[32]), "=f"(d[33]), "=f"(d[34]), "=f"(d[35]), "=f"(d[36]), "=f"(d[37]), "=f"(d[38]), "=f"(d[39]),
          "=f"(d[40]), "=f"(d[41]), "=f"(d[42]), "=f"(d[43]), "=f"(d[44]), "=f"(d[45]), "=f"(d[46]), "=f"(d[47]),
          "=f"(d[48]), "=f"(d[49]), "=f"(d[50]), "=f"(d[51]), "=f"(d[52]), "=f"(d[53]), "=f"(d[54]), "=f"(d[55]),
          "=f"(d[56]), "=f"(d[57]), "=f"(d[58]), "=f"(d[59]), "=f"(d[60]), "=f"(d[61]), "=f"(d[62]), "=f"(d[63]),
          "=f"(d[64]), "=f"(d[65]), "=f"(d[66]), "=f"(d[67]), "=f"(d[68]), "=f"(d[69]), "=f"(d[70]), "=f"(d[71]),
          "=f"(d[72]), "=f"(d[73]), "=f"(d[74]), "=f"(d[75]), "=f"(d[76]), "=f"(d[77]), "=f"(d[78]), "=f"(d[79]),
          "=f"(d[80]), "=f"(d[81]), "=f"(d[82]), "=f"(d[83]), "=f"(d[84]), "=f"(d[85]), "=f"(d[86]), "=f"(d[87]),
          "=f"(d[88]), "=f"(d[89]), "=f"(d[90]), "=f"(d[91]), "=f"(d[92]), "=f"(d[93]), "=f"(d[94]), "=f"(d[95])
        : "l"(descA), "l"(descB));
}

__device__ __forceinline__ void wgmma_n160_ss_tb(float (&d)[80], uint64_t descA, uint64_t descB, int scaleD) {
    asm volatile("{\n.reg .pred p;\nsetp.ne.b32 p, %82, 0;\n"
        "wgmma.mma_async.sync.aligned.m64n160k16.f32.bf16.bf16 {"
        "%0, %1, %2, %3, %4, %5, %6, %7, %8, %9, %10, %11, %12, %13, %14, %15, "
        "%16, %17, %18, %19, %20, %21, %22, %23, %24, %25, %26, %27, %28, %29, %30, %31, "
        "%32, %33, %34, %35, %36, %37, %38, %39, %40, %41, %42, %43, %44, %45, %46, %47, "
        "%48, %49, %50, %51, %52, %53, %54, %55, %56, %57, %58, %59, %60, %61, %62, %63, "
        "%64, %65, %66, %67, %68, %69, %70, %71, %72, %73, %74, %75, %76, %77, %78, %79}, "
        "%80, %81, p, 1, 1, 0, 1;\n}\n"
        : "+f"(d[0]), "+f"(d[1]), "+f"(d[2]), "+f"(d[3]), "+f"(d[4]), "+f"(d[5]), "+f"(d[6]), "+f"(d[7]),
          "+f"(d[8]), "+f"(d[9]), "+f"(d[10]), "+f"(d[11]), "+f"(d[12]), "+f"(d[13]), "+f"(d[14]), "+f"(d[15]),
          "+f"(d[16]), "+f"(d[17]), "+f"(d[18]), "+f"(d[19]), "+f"(d[20]), "+f"(d[21]), "+f"(d[22]), "+f"(d[23]),
          "+f"(d[24]), "+f"(d[25]), "+f"(d[26]), "+f"(d[27]), "+f"(d[28]), "+f"(d[29]), "+f"(d[30]), "+f"(d[31]),
          "+f"(d[32]), "+f"(d[33]), "+f"(d[34]), "+f"(d[35]), "+f"(d[36]), "+f"(d[37]), "+f"(d[38]), "+f"(d[39]),
          "+f"(d[40]), "+f"(d[41]), "+f"(d[42]), "+f"(d[43]), "+f"(d[44]), "+f"(d[45]), "+f"(d[46]), "+f"(d[47]),
          "+f"(d[48]), "+f"(d[49]), "+f"(d[50]), "+f"(d[51]), "+f"(d[52]), "+f"(d[53]), "+f"(d[54]), "+f"(d[55]),
          "+f"(d[56]), "+f"(d[57]), "+f"(d[58]), "+f"(d[59]), "+f"(d[60]), "+f"(d[61]), "+f"(d[62]), "+f"(d[63]),
          "+f"(d[64]), "+f"(d[65]), "+f"(d[66]), "+f"(d[67]), "+f"(d[68]), "+f"(d[69]), "+f"(d[70]), "+f"(d[71]),
          "+f"(d[72]), "+f"(d[73]), "+f"(d[74]), "+f"(d[75]), "+f"(d[76]), "+f"(d[77]), "+f"(d[78]), "+f"(d[79])
        : "l"(descA), "l"(descB), "r"(scaleD));
}

__device__ __forceinline__ void wgmma_n64_ss(float (&d)[32], uint64_t descA, uint64_t descB, int scaleD) {
    asm volatile("{\n.reg .pred p;\nsetp.ne.b32 p, %34, 0;\n"
        "wgmma.mma_async.sync.aligned.m64n64k16.f32.bf16.bf16 {"
        "%0, %1, %2, %3, %4, %5, %6, %7, %8, %9, %10, %11, %12, %13, %14, %15, "
        "%16, %17, %18, %19, %20, %21, %22, %23, %24, %25, %26, %27, %28, %29, %30, %31}, "
        "%32, %33, p, 1, 1, 0, 0;\n}\n"
        : "+f"(d[0]), "+f"(d[1]), "+f"(d[2]), "+f"(d[3]), "+f"(d[4]), "+f"(d[5]), "+f"(d[6]), "+f"(d[7]),
          "+f"(d[8]), "+f"(d[9]), "+f"(d[10]), "+f"(d[11]), "+f"(d[12]), "+f"(d[13]), "+f"(d[14]), "+f"(d[15]),
          "+f"(d[16]), "+f"(d[17]), "+f"(d[18]), "+f"(d[19]), "+f"(d[20]), "+f"(d[21]), "+f"(d[22]), "+f"(d[23]),
          "+f"(d[24]), "+f"(d[25]), "+f"(d[26]), "+f"(d[27]), "+f"(d[28]), "+f"(d[29]), "+f"(d[30]), "+f"(d[31])
        : "l"(descA), "l"(descB), "r"(scaleD));
}

__device__ __forceinline__ void wgmma_n64_ss_z(float (&d)[32], uint64_t descA, uint64_t descB) {
    asm volatile("{\n.reg .pred p;\nsetp.ne.b32 p, 0, 0;\n"
        "wgmma.mma_async.sync.aligned.m64n64k16.f32.bf16.bf16 {"
        "%0, %1, %2, %3, %4, %5, %6, %7, %8, %9, %10, %11, %12, %13, %14, %15, "
        "%16, %17, %18, %19, %20, %21, %22, %23, %24, %25, %26, %27, %28, %29, %30, %31}, "
        "%32, %33, p, 1, 1, 0, 0;\n}\n"
        : "=f"(d[0]), "=f"(d[1]), "=f"(d[2]), "=f"(d[3]), "=f"(d[4]), "=f"(d[5]), "=f"(d[6]), "=f"(d[7]),
          "=f"(d[8]), "=f"(d[9]), "=f"(d[10]), "=f"(d[11]), "=f"(d[12]), "=f"(d[13]), "=f"(d[14]), "=f"(d[15]),
          "=f"(d[16]), "=f"(d[17]), "=f"(d[18]), "=f"(d[19]), "=f"(d[20]), "=f"(d[21]), "=f"(d[22]), "=f"(d[23]),
          "=f"(d[24]), "=f"(d[25]), "=f"(d[26]), "=f"(d[27]), "=f"(d[28]), "=f"(d[29]), "=f"(d[30]), "=f"(d[31])
        : "l"(descA), "l"(descB));
}

__device__ __forceinline__ void wgmma_n24_rs_tb(float (&d)[12], uint32_t a0, uint32_t a1, uint32_t a2, uint32_t a3, uint64_t descB, int scaleD) {
    asm volatile("{\n.reg .pred p;\nsetp.ne.b32 p, %17, 0;\n"
        "wgmma.mma_async.sync.aligned.m64n24k16.f32.bf16.bf16 {"
        "%0, %1, %2, %3, %4, %5, %6, %7, %8, %9, %10, %11}, "
        "{%12, %13, %14, %15}, %16, p, 1, 1, 1;\n}\n"
        : "+f"(d[0]), "+f"(d[1]), "+f"(d[2]), "+f"(d[3]), "+f"(d[4]), "+f"(d[5]), "+f"(d[6]), "+f"(d[7]),
          "+f"(d[8]), "+f"(d[9]), "+f"(d[10]), "+f"(d[11])
        : "r"(a0), "r"(a1), "r"(a2), "r"(a3), "l"(descB), "r"(scaleD));
}

__device__ __forceinline__ void cnt_signal(int idx) {
    asm volatile("fence.acq_rel.gpu;\nred.relaxed.gpu.global.add.u32 [%0], 1;"
                 ::"l"(g_cnt + idx * 32) : "memory");
}
__device__ __forceinline__ void cnt_wait(int idx, uint32_t target) {
    const uint32_t* p = g_cnt + idx * 32;
#pragma unroll 1
    for (uint32_t i = 0; i < (1u << 22); i++) {
        uint32_t v;
        asm volatile("ld.acquire.gpu.global.u32 %0, [%1];" : "=r"(v) : "l"(p) : "memory");
        if ((int32_t)(v - target) >= 0) break;
    }
    asm volatile("fence.proxy.async.global;" ::: "memory");
}
__device__ __forceinline__ void cluster_arrive() { asm volatile("barrier.cluster.arrive.release.aligned;" ::: "memory"); }
__device__ __forceinline__ void cluster_arrive_relaxed() { asm volatile("barrier.cluster.arrive.relaxed.aligned;" ::: "memory"); }
__device__ __forceinline__ void cluster_wait() { asm volatile("barrier.cluster.wait.acquire.aligned;" ::: "memory"); }
__device__ __forceinline__ void bulk_wait_read() { asm volatile("cp.async.bulk.wait_group.read 0;" ::: "memory"); }

__device__ __forceinline__ float gelu_half(float hx) {
    const float u = hx * fmaf(hx * hx, 8.f * 0.035677408136300125f, 2.f * 0.7978845608028654f);
    float t;
    asm("tanh.approx.f32 %0, %1;" : "=f"(t) : "f"(u));
    return fmaf(hx, t, hx);
}
__device__ __forceinline__ void release_stage(uint32_t bar, uint32_t peer, int lane) {
    if (lane == 0) { mbar_arrive(bar); mbar_arrive_cluster(bar, peer); }
}

constexpr int SM_RING = 163840;
constexpr int SM_Q = 0, SM_ZERO = 24576, SM_K = SM_ZERO + 3072, SM_V = SM_K + IMG_BYTES;
constexpr int G2_STAGE = 8192 + 20480;
constexpr int SM_MISC = 229376;
constexpr int SM_BIAS = SM_MISC, SM_RED = SM_BIAS + 384, SM_BAR = SM_RED + 128;
constexpr int B_A = 0, B_F1 = 10, B_E1 = 14, B_F2 = 18, B_E2 = 23, B_KV = 28, B_Q = 45, B_F3 = 47, B_E3 = 55, B_ST = 63, B_STAT = 65, B_AUX = 66, B_AUX2 = 67, B_DEAD = 68, B_COUNT = 70;
constexpr int SM_EPOCH = SM_BAR + 568, SM_SAFE = SM_EPOCH + 4;
constexpr int SM_CS = SM_EPOCH + 8;
constexpr int SM_TOTAL = SM_CS + 1728;
static_assert(SM_TOTAL <= 232448, "shared memory budget");

struct Maps { CUtensorMap x, wqkv, w1, h, o, wo, w2; };

__device__ __forceinline__ uint32_t bf2_fma(uint32_t a, uint32_t b, uint32_t c) {
    uint32_t r;
    asm("fma.rn.bf16x2 %0, %1, %2, %3;" : "=r"(r) : "r"(a), "r"(b), "r"(c));
    return r;
}
__device__ __forceinline__ uint32_t lop_and_or(uint32_t a, uint32_t m, uint32_t o) {
    uint32_t r;
    asm("lop3.b32 %0, %1, %2, %3, 0xEA;" : "=r"(r) : "r"(a), "r"(m), "r"(o));
    return r;
}
struct ExpConst { uint32_t mask, slope; };
__device__ __forceinline__ ExpConst make_exp_const() {
    ExpConst k;
    asm volatile("mov.b32 %0, 0x007F007F;" : "=r"(k.mask));
    asm volatile("mov.b32 %0, 0x3EF83EF8;" : "=r"(k.slope));
    return k;
}
__device__ __forceinline__ uint32_t exp2_pair_fma(float t0, float t1, const ExpConst& k) {
    const uint32_t L = __byte_perm(__float_as_uint(t0), __float_as_uint(t1), 0x6521);
    const uint32_t g = lop_and_or(L, k.mask, 0x3F803F80u);
    const uint32_t u = bf2_fma(g, k.slope, 0xBF37BF37u);
    const uint32_t e = bf2_fma(u, u, 0xBD71BD71u);
    return bf2_fma(L, e, L);
}
template <int SHIFT>
__device__ __forceinline__ void exp_tile(const float (&s)[32], uint32_t (&p)[16], const ExpConst& k) {
#pragma unroll
    for (int b = 0; b < 8; b++) {
        if ((EMU_MASK >> (b + SHIFT)) & 1) {
            p[2 * b] = exp2_pair_fma(s[4 * b], s[4 * b + 1], k);
            p[2 * b + 1] = exp2_pair_fma(s[4 * b + 2], s[4 * b + 3], k);
        } else {
            p[2 * b] = pack_bf16(ex2(s[4 * b]), ex2(s[4 * b + 1]));
            p[2 * b + 1] = pack_bf16(ex2(s[4 * b + 2]), ex2(s[4 * b + 3]));
        }
    }
}

__device__ __forceinline__ void qk_tile(float (&s)[32], uint64_t dQ, uint64_t dQ2, uint64_t dK) {
    wg_fence();
    wgmma_n64_ss_z(s, dQ, dK);
    wgmma_n64_ss(s, dQ2, dK + 16, 1);
    wg_commit();
}
__device__ __forceinline__ void pv_tile(float (&o)[12], const uint32_t (&p)[16], uint64_t dV) {
    wg_fence();
#pragma unroll
    for (int ks = 0; ks < 4; ks++)
        wgmma_n24_rs_tb(o, p[4 * ks], p[4 * ks + 1], p[4 * ks + 2], p[4 * ks + 3], dV + ks * 48, 1);
    wg_commit();
}
__device__ __forceinline__ void store_o(const float (&o)[12], int h, int rbase, int lane) {
    const int g = lane >> 2, c = lane & 3;
    const bool odd = h & 1;
    const int lsrc = (lane & ~3) | (odd ? 0 : 2);
    const float i0 = 1.f / __shfl_sync(~0u, o[8], lsrc), i1 = 1.f / __shfl_sync(~0u, o[10], lsrc);
    __nv_bfloat16* dst = g_o + (size_t)(rbase + g) * DM + h * 20;
    const int d0 = (odd ? 4 : 0) + 2 * c, d1 = d0 + 8, d2 = odd ? 2 * c - 4 : 16 + 2 * c;
    *(uint32_t*)(dst + d0) = pack_bf16(o[0] * i0, o[1] * i0);
    *(uint32_t*)(dst + d1) = pack_bf16(o[4] * i0, o[5] * i0);
    *(uint32_t*)(dst + 8 * DM + d0) = pack_bf16(o[2] * i1, o[3] * i1);
    *(uint32_t*)(dst + 8 * DM + d1) = pack_bf16(o[6] * i1, o[7] * i1);
    if (odd ? (c >= 2) : (c < 2)) {
        *(uint32_t*)(dst + d2) = pack_bf16(o[8] * i0, o[9] * i0);
        *(uint32_t*)(dst + 8 * DM + d2) = pack_bf16(o[10] * i1, o[11] * i1);
    }
}

__device__ __forceinline__ void attn_rows_maxshift(uint32_t sK, uint32_t barKV, uint64_t dQ, uint64_t dQ2, int h, int rbase) {
    const int lane = threadIdx.x & 31;
    const uint64_t dK0 = make_desc(sK, 128, 384, 0), dV0 = make_desc(sK + IMG_BYTES, 384, 128, 0);
    float o[12], s[32];
    uint32_t p[16];
#pragma unroll
    for (int i = 0; i < 12; i++) o[i] = 0.f;
    float m0 = -3.0e38f, m1 = -3.0e38f;
    mbar_wait(barKV + 128, 0);
#pragma unroll 1
    for (int t = 0; t < 32; t++) {
        mbar_wait(barKV + (t >> 1) * 8, 0);
        qk_tile(s, dQ, dQ2, dK0 + t * 192);
        wg_wait<0>();
        fence_regs(s);
        const uint32_t mask = EMU_MASK >> ((t & 1) * 8);
        float n0 = m0, n1 = m1;
#pragma unroll
        for (int b = 0; b < 8; b++) {
            const bool emu = (mask >> b) & 1;
            const float f = emu ? 0.5f : 1.f, off = emu ? -383.00390625f : 0.f;
#pragma unroll
            for (int i = 0; i < 4; i++) s[4 * b + i] = fmaf(s[4 * b + i], f, off);
            n0 = fmaxf(n0, fmaxf(s[4 * b], s[4 * b + 1]));
            n1 = fmaxf(n1, fmaxf(s[4 * b + 2], s[4 * b + 3]));
        }
        n0 = fmaxf(n0, __shfl_xor_sync(~0u, n0, 1)); n0 = fmaxf(n0, __shfl_xor_sync(~0u, n0, 2));
        n1 = fmaxf(n1, __shfl_xor_sync(~0u, n1, 1)); n1 = fmaxf(n1, __shfl_xor_sync(~0u, n1, 2));
        const float c0 = ex2(m0 - n0), c1 = ex2(m1 - n1);
        m0 = n0; m1 = n1;
#pragma unroll
        for (int b = 0; b < 3; b++) { o[4 * b] *= c0; o[4 * b + 1] *= c0; o[4 * b + 2] *= c1; o[4 * b + 3] *= c1; }
#pragma unroll
        for (int b = 0; b < 8; b++) {
            p[2 * b] = pack_bf16(ex2(s[4 * b] - m0), ex2(s[4 * b + 1] - m0));
            p[2 * b + 1] = pack_bf16(ex2(s[4 * b + 2] - m1), ex2(s[4 * b + 3] - m1));
        }
        pv_tile(o, p, dV0 + (((t >> 1) + 7) & 15) * 384 + (t & 1) * 192);
        wg_wait<0>();
        fence_regs(o);
    }
    store_o(o, h, rbase, lane);
}

__global__ void __launch_bounds__(512, 1) __cluster_dims__(2, 1, 1)
k_fused(const __grid_constant__ Maps tm, const __nv_bfloat16* __restrict__ x, const uint8_t* __restrict__ wqkv,
        const uint8_t* __restrict__ w1, const uint8_t* __restrict__ w2, const uint8_t* __restrict__ wo,
        const __nv_bfloat16* __restrict__ b1, const __nv_bfloat16* __restrict__ b2, __nv_bfloat16* __restrict__ out) {
    extern __shared__ __align__(1024) uint8_t smem[];
    const uint32_t sb = smem_u32(smem);
    const uint32_t bar = sb + SM_BAR;
    const int warp = __shfl_sync(~0u, threadIdx.x >> 5, 0), lane = threadIdx.x & 31;
    const int wgi = warp >> 2, w4 = warp & 3, g = lane >> 2, c = lane & 3;
    const uint32_t rank = blockIdx.x & 1, peer = rank ^ 1;
    const int cl = blockIdx.x >> 1;
    const int cg = cl >> 3, rb = (cl & 7) * 2 + rank;

    if (threadIdx.x == 0) TL(0, 0);
    if (warp == 15 && lane < 4) prefetch_map(lane == 0 ? &tm.x : lane == 1 ? &tm.wqkv : lane == 2 ? &tm.w1 : &tm.h);
    if (elect_one()) {
#pragma unroll
        for (int j = 0; j < 5; j++) {
            const int i = warp * 5 + j;
            const int cnt = (i >= B_E1 && i < B_F2) || (i >= B_E2 && i < B_KV) ? 16
                          : (i >= B_E3 && i <= B_ST + 1) || i == B_STAT || i == B_DEAD || i == B_DEAD + 1 ? 8 : i == B_AUX ? 4 : i == B_AUX2 ? 3 : 1;
            if (i < B_COUNT) mbar_init(bar + i * 8, cnt);
        }
        fence_barrier_init();
    }
    __syncthreads();
    if (threadIdx.x == 0) TL(0, 1);
    cluster_arrive_relaxed();
    cluster_wait();
    if (threadIdx.x == 0) TL(0, 3);

    {
        const uint32_t sB = sb + SM_RING;
        if (threadIdx.x == 0) TL(1, 0);
        if (wgi < 2) {
            reg_dealloc<56>();
            if (warp == 0) {
#pragma unroll 1
                for (int it = 0; it < 20; it++) {
                    const int s = it & 3;
                    const int kb = it < 2 ? it : (it & 1) ? (it + 1) >> 1 : 10;
                    if (it >= 4) mbar_wait(bar + (B_E1 + s) * 8, ((it >> 2) - 1) & 1);
                    else if (it > 0) __nanosleep(PACE_NS);
                    if (elect_one()) {
                        if (kb < 10) {
                            mbar_expect_tx(bar + (B_A + kb) * 8, 16384);
                            tma_load(sb + kb * 16384, &tm.x, kb * 64, rb * 128, bar + (B_A + kb) * 8);
                        }
                        const uint32_t dst = sB + s * 16384 + rank * 8192, fb = bar + (B_F1 + s) * 8;
                        const int c0 = cg * 240 + rank * 128;
                        mbar_expect_tx(fb, 16384);
                        tma_load_mc(dst, &tm.wqkv, c0, it * 32, fb, 3);
                        tma_load_mc(dst + 4096, &tm.wqkv, c0 + 64, it * 32, fb, 3);
                    }
                    __syncwarp();
                }
#pragma unroll 1
                for (int it = 0; it < 20; it++) {
                    const int s = it % 5;
                    if (it < 5) { if (it != 3) mbar_wait(bar + (B_E1 + (it == 4 ? 3 : it)) * 8, 0); }
                    else mbar_wait(bar + (B_E2 + s) * 8, ((it / 5) - 1) & 1);
                    if (elect_one()) {
                        const uint32_t dst = sB + s * 12288, fb = bar + (B_F2 + s) * 8;
                        mbar_expect_tx(fb, 12288);
                        if ((it & 1) == (int)rank) {
                            tma_load_mc(dst, &tm.w1, cg * 192, it * 32, fb, 3);
                            tma_load_mc(dst + 4096, &tm.w1, cg * 192 + 64, it * 32, fb, 3);
                        } else {
                            tma_load_mc(dst + 8192, &tm.w1, cg * 192 + 128, it * 32, fb, 3);
                        }
                    }
                    __syncwarp();
                }
            } else {
                const int ht = threadIdx.x - 32;
                if (ht == 160) *reinterpret_cast<volatile uint32_t*>(smem + SM_EPOCH) = *(volatile uint32_t*)&g_epoch;
                auto slab_sum = [&](const uint32_t* src, int pitch) {
                    float s0 = 0.f, s1 = 0.f;
                    uint32_t v[40];
#pragma unroll
                    for (int k = 0; k < 40; k++) v[k] = __ldg(src + k * pitch);
#pragma unroll
                    for (int k = 0; k < 40; k++) { s0 += bf_lo(v[k]); s1 += bf_hi(v[k]); }
                    return make_float2(s0, s1);
                };
                auto gather = [&](int idx) {
                    float s0 = 0.f, s1 = 0.f;
#pragma unroll
                    for (int r = 0; r < 16; r++) {
                        const float2 v = __ldcg(g_csp + r * 1728 + cg * 216 + idx);
                        s0 += v.x; s1 += v.y;
                    }
                    reinterpret_cast<float2*>(smem + SM_CS)[idx] = make_float2(s0, s1);
                };
                if (warp == 7) {
                    mbar_wait(bar + B_STAT * 8, 0);
                    if (elect_one()) cnt_signal(CNT_ST + rb);
                    __syncwarp();
                }
                if (ht < 120)
                    g_csp[rb * 1728 + cg * 216 + ht] = slab_sum(reinterpret_cast<const uint32_t*>(wqkv) + rb * 40 * 960 + cg * 120 + ht, 960);
                if (threadIdx.x == 64) IT(3, 0);
                if (threadIdx.x == 192) IT(3, 1);
                if (warp != 7) asm volatile("bar.sync 8, 192;" ::: "memory");
                const uint32_t epoch = *reinterpret_cast<volatile uint32_t*>(smem + SM_EPOCH);
                if (warp == 6) { if (elect_one()) cnt_signal(CNT_CS + cg); __syncwarp(); }

                if (threadIdx.x == 64) IT(3, 2);
                if (warp <= 4) {
                    if (lane == 0) { cnt_wait(CNT_CS + cg, (epoch + 1) * 16); cnt_wait(CNT_ST + rb, (epoch + 1) * 8); }
                    __syncwarp();
                    if (threadIdx.x == 64) IT(3, 4);
                    if (ht < 120) gather(ht);
                    __syncwarp();
                    if (threadIdx.x == 64) IT(3, 5);
                    if (lane == 0) mbar_arrive(bar + B_AUX * 8);
                }
                if (ht >= 128) {
                    g_csp[rb * 1728 + cg * 216 + 120 + (ht - 128)] = slab_sum(reinterpret_cast<const uint32_t*>(w1) + rb * 40 * 768 + cg * 96 + (ht - 128), 768);
                    reinterpret_cast<uint32_t*>(smem + SM_BIAS)[ht - 128] =
                        bf2_fma(__ldg(reinterpret_cast<const uint32_t*>(b1 + cg * 192) + (ht - 128)), 0x3F003F00u, 0x80008000u);
                    asm volatile("bar.sync 9, 96;" ::: "memory");
                    const uint32_t epoch2 = *reinterpret_cast<volatile uint32_t*>(smem + SM_EPOCH);
                    if (warp == 5) { if (elect_one()) cnt_signal(CNT_CS2 + cg); __syncwarp(); }
                    if (warp == 6 && elect_one()) {
                        prefetch_l2(w2 + blockIdx.x * 15360, 15360);
                        prefetch_l2(wo + blockIdx.x * 6400, 6400);
                    }
                    if (lane == 0) cnt_wait(CNT_CS2 + cg, (epoch2 + 1) * 16);
                    __syncwarp();
                    gather(120 + (ht - 128));
                    __syncwarp();
                    if (lane == 0) mbar_arrive(bar + B_AUX2 * 8);
                }
                if (warp == 4) {
                    mbar_wait(bar + B_ST * 8, 0);
                    if (elect_one()) cnt_signal(CNT_QKV + cg);
                    __syncwarp();
                }
                const int h = blockIdx.x >> 2, qb = blockIdx.x & 3;
                const uint32_t ep = *reinterpret_cast<volatile uint32_t*>(smem + SM_EPOCH);
                if (lane == 0 && warp != 5) {
                    cnt_wait(CNT_QKV + h / 12, (ep + 1) * 16);
                    cnt_wait(CNT_QKV + (32 + h) / 12, (ep + 1) * 16);
                    cnt_wait(CNT_QKV + (64 + h) / 12, (ep + 1) * 16);
                }
                __syncwarp();
                if (threadIdx.x == 64) TL(5, 0);
                if (warp == 1 || warp == 4 || warp >= 6) {
                    const int w = warp == 1 ? 0 : warp == 4 ? 1 : warp - 4, t = w * 32 + lane;
                    float kmax = 0.f, qmax = 0.f;
#pragma unroll
                    for (int i = 0; i < 4; i++) {
                        const float4 v = __ldcg(reinterpret_cast<const float4*>(g_nrm + (32 + h) * SEQ) + t + i * 128);
                        kmax = fmaxf(fmaxf(kmax, fmaxf(v.x, v.y)), fmaxf(v.z, v.w));
                    }
                    {
                        const float4 v = __ldcg(reinterpret_cast<const float4*>(g_nrm + h * SEQ + qb * 512) + t);
                        qmax = fmaxf(fmaxf(v.x, v.y), fmaxf(v.z, v.w));
                    }
#pragma unroll
                    for (int o = 16; o; o >>= 1) {
                        kmax = fmaxf(kmax, __shfl_xor_sync(~0u, kmax, o));
                        qmax = fmaxf(qmax, __shfl_xor_sync(~0u, qmax, o));
                    }
                    float* red = reinterpret_cast<float*>(smem + SM_RED);
                    if (lane == 0) { red[w] = kmax; red[8 + w] = qmax; }
                    asm volatile("bar.sync 8, 128;" ::: "memory");
                    if (warp == 1 && lane == 0) {
                        for (int u = 1; u < 4; u++) { kmax = fmaxf(kmax, red[u]); qmax = fmaxf(qmax, red[8 + u]); }
                        *reinterpret_cast<volatile uint32_t*>(smem + SM_SAFE) = kmax * qmax * 1.1f <= SAFE_BOUND * SAFE_BOUND;
                    }
                }
                const uint32_t barKV = bar + B_KV * 8;
                const uint8_t* gK = g_img + (size_t)(32 + h) * IMG_BYTES;
                const uint8_t* gV = g_img + (size_t)(64 + h) * IMG_BYTES;
                if (warp == 2) {
                    if (lane == 0) TL(5, 1);
                    mbar_wait(bar + B_DEAD * 8, 0);
                    if (lane == 0) TL(5, 2);
                    for (int i = lane; i < 192; i += 32) *reinterpret_cast<uint4*>(smem + SM_ZERO + i * 16) = make_uint4(0, 0, 0, 0);
                    fence_proxy_async();
                    __syncwarp();
                    if (elect_one()) {
                        asm volatile("fence.proxy.async.global;" ::: "memory");
                        const uint8_t* gQ = g_img + (size_t)h * IMG_BYTES + qb * 64 * 384;
                        mbar_expect_tx(barKV + 128, 6144);
                        bulk_load(sb + SM_K, gK, 6144, barKV + 128);
                        for (int p = 0; p < 2; p++) {
                            mbar_expect_tx(bar + (B_Q + p) * 8, 12288);
                            bulk_load(sb + SM_Q + p * 12288, gQ + p * 12288, 12288, bar + (B_Q + p) * 8);
                        }
                        for (int i = 0; i < 13; i++) {
                            mbar_expect_tx(barKV + i * 8, 12288);
                            bulk_load(sb + SM_K + (i + 1) * 6144, gK + (i + 1) * 6144, 6144, barKV + i * 8);
                        }
                    }
                    __syncwarp();
                    if (lane == 0) TL(5, 3);
                } else if (warp == 5) {
                    mbar_wait(bar + (B_ST + 1) * 8, 0);
                    if (lane == 0) {
                        for (int b = 0; b < 6; b++)
                            tma_store(&tm.h, sb + (7 + b % 3) * 16384 + (b / 3) * 8192, cg * 192 + (b % 3) * 64, rb * 128 + (b / 3) * 64);
                        bulk_commit();
                    }
                    __syncwarp();
                } else if (warp == 3) {
                    mbar_wait(bar + (B_DEAD + 1) * 8, 0);
                    if (elect_one()) {
                        asm volatile("fence.proxy.async.global;" ::: "memory");
                        for (int i = 0; i < 9; i++) bulk_load(sb + SM_V + (i + 7) * 6144, gV + i * 6144, 6144, barKV + i * 8);
                    }
                    __syncwarp();
                }
            }
            if (lane == 0) TL(6, warp);
            asm volatile("bar.sync %0, 128;" ::"r"(wgi + 3) : "memory");
            reg_alloc<128>();
        } else {
            reg_alloc<200>();
            const int wi = wgi - 2;
            const int row0 = rb * 128 + wi * 64 + w4 * 16 + g;
            const uint32_t sAw = sb + wi * 8192;
            const int rbk = row0 >> 3, hs0 = cg * 12;
            {
                const int srow = rb * 128 + cg * 16 + (warp - 8) * 2 + (lane >> 4);
                uint4 xv[5];
#pragma unroll
                for (int i = 0; i < 5; i++) xv[i] = __ldg(reinterpret_cast<const uint4*>(x + (size_t)srow * DM) + (lane & 15) + 16 * i);
                float sm = 0.f;
#pragma unroll
                for (int i = 0; i < 5; i++)
                    sm += ((bf_lo(xv[i].x) + bf_hi(xv[i].x)) + (bf_lo(xv[i].y) + bf_hi(xv[i].y))) +
                          ((bf_lo(xv[i].z) + bf_hi(xv[i].z)) + (bf_lo(xv[i].w) + bf_hi(xv[i].w)));
#pragma unroll
                for (int o = 8; o; o >>= 1) sm += __shfl_xor_sync(~0u, sm, o);
                const float mu = sm * (1.f / DM);
                float q0 = 0.f, q1 = 0.f;
#pragma unroll
                for (int i = 0; i < 5; i++) {
                    const uint32_t w[4] = {xv[i].x, xv[i].y, xv[i].z, xv[i].w};
#pragma unroll
                    for (int j = 0; j < 4; j++) {
                        const float d0 = bf_lo(w[j]) - mu, d1 = bf_hi(w[j]) - mu;
                        q0 = fmaf(d0, d0, q0); q1 = fmaf(d1, d1, q1);
                    }
                }
                float q = q0 + q1;
#pragma unroll
                for (int o = 8; o; o >>= 1) q += __shfl_xor_sync(~0u, q, o);
                const float var = q * (1.f / DM);
                const float r1 = rsqrtf(var + LN_EPS);
                const float r2 = rsqrtf(var * r1 * r1 + LN_EPS);
                if ((lane & 15) == 0) g_stat[srow] = make_float4(mu, r1, r1 * r2, 0.f);
                __syncwarp();
                if (lane == 0) mbar_arrive(bar + B_STAT * 8);
            }
            float accA[100], accB[20];
            const uint64_t dA0 = make_desc(sAw, 16, 1024, 1), dB0 = make_desc(sB, 4096, 1024, 1);
#pragma unroll 2
            for (int it = 0; it < 20; it++) {
                const int s = it & 3;
                if (!(it & 1)) mbar_wait(bar + (B_A + (it >> 1)) * 8, 0);
                if (threadIdx.x == 256 && it == 0) TL(0, 2);
                if (threadIdx.x == 256) IT(0, it);
                mbar_wait(bar + (B_F1 + s) * 8, (it >> 2) & 1);
                if (threadIdx.x == 256) IT(1, it);
                const uint64_t dA = dA0 + (it >> 1) * 1024 + (it & 1) * 4, dB = dB0 + s * 1024;
                wg_fence();
                wgmma_n40_ss_tb(accB, dA, dB + 769, it > 0);
                wgmma_n40_ss_tb(accB, dA + 2, dB + 769 + 128, 1);
                wgmma_n200_ss_tb(accA, dA, dB, it > 0);
                wgmma_n200_ss_tb(accA, dA + 2, dB + 128, 1);
                wg_commit();
                if (it > 0) { wg_wait<1>(); release_stage(bar + (B_E1 + ((it - 1) & 3)) * 8, peer, lane); }
            }
            if (threadIdx.x == 256) IT(2, 0);
            mbar_wait(bar + B_AUX * 8, 0);
            if (threadIdx.x == 256) IT(2, 1);
            const float4 st0 = __ldcg(g_stat + row0), st1 = __ldcg(g_stat + row0 + 8);
            wg_wait<0>();
            release_stage(bar + (B_E1 + 3) * 8, peer, lane);
            fence_regs(accA);
            fence_regs(accB);
            if (threadIdx.x == 256) TL(1, 1);
            const float2* cs = reinterpret_cast<const float2*>(smem + SM_CS) + c;
            uint8_t* img = g_img + (size_t)hs0 * IMG_BYTES + rbk * 384 + g * 16 + c * 4;
            const bool emu0 = (EMU_MASK >> (rbk & 15)) & 1, emu1 = (EMU_MASK >> ((rbk + 1) & 15)) & 1;
            const bool low = c < 2;
            uint32_t pk[60];
#pragma unroll
            for (int m = 0; m < 6; m++) {
                const int which = (hs0 + 2 * m) >> 5;
                const float m0 = st0.y * (which == 0 ? QSCALE : (which == 1 && emu0) ? 2.f : 1.f);
                const float m1 = st1.y * (which == 0 ? QSCALE : (which == 1 && emu1) ? 2.f : 1.f);
                const float d0 = -st0.x * m0, d1 = -st1.x * m1;
                const float* a = m < 5 ? &accA[20 * m] : accB;
#pragma unroll
                for (int b = 0; b < 5; b++) {
                    const float2 cv = cs[(5 * m + b) * 4];
                    pk[10 * m + 2 * b] = pack_bf16(fmaf(a[4 * b], m0, d0 * cv.x), fmaf(a[4 * b + 1], m0, d0 * cv.y));
                    pk[10 * m + 2 * b + 1] = pack_bf16(fmaf(a[4 * b + 2], m1, d1 * cv.x), fmaf(a[4 * b + 3], m1, d1 * cv.y));
                }
            }
            const float r20 = 0.5f * st0.z, r21 = 0.5f * st1.z, e20 = -st0.x * r20, e21 = -st1.x * r21;
            if (threadIdx.x == 256) IT(2, 2);
            float acc2[96];
#pragma unroll
            for (int it = 0; it < 20; it++) {
                const int s = it % 5;
                if (threadIdx.x == 256) IT(0, 20 + it);
                mbar_wait(bar + (B_F2 + s) * 8, (it / 5) & 1);
                if (threadIdx.x == 256) IT(1, 20 + it);
                wg_fence();
                const uint64_t dA = make_desc(sAw + (it >> 1) * 16384 + (it & 1) * 64, 16, 1024, 1);
                const uint64_t dB = make_desc(sB + s * 12288, 4096, 1024, 1);
                if (it == 0) wgmma_n192_ss_tb_z(acc2, dA, dB); else wgmma_n192_ss_tb(acc2, dA, dB, 1);
                wgmma_n192_ss_tb(acc2, dA + 2, dB + 128, 1);
                wg_commit();
                if (it > 0) {
                    wg_wait<1>();
                    if (it <= 15) release_stage(bar + (B_E2 + (it - 1) % 5) * 8, peer, lane);
                    if (it == 14 && lane == 0) mbar_arrive(bar + B_DEAD * 8);
                }
                if (it < 6) {
                    const int m = it;
                    const int hs = hs0 + 2 * m, which = hs >> 5;
                    const uint32_t* a = pk + 10 * m;
                    uint8_t* pe = img + (2 * m) * IMG_BYTES;
                    uint8_t* po = pe + IMG_BYTES;
                    const uint32_t padv = which == 0 ? 0x3F803F80u : which == 1 ? 0xBFFF4440u : 0x00003F80u;
                    const uint32_t p0 = ((c & 1) || (which == 1 && !emu0)) ? 0u : padv;
                    const uint32_t p1 = ((c & 1) || (which == 1 && !emu1)) ? 0u : padv;
                    *(uint32_t*)(pe) = a[0];
                    *(uint32_t*)(pe + 128) = a[2];
                    *(uint32_t*)(pe + 256) = low ? a[4] : p0;
                    *(uint32_t*)(pe + 384) = a[1];
                    *(uint32_t*)(pe + 512) = a[3];
                    *(uint32_t*)(pe + 640) = low ? a[5] : p1;
                    *(uint32_t*)(po) = a[6];
                    *(uint32_t*)(po + 128) = a[8];
                    *(uint32_t*)(po + 256) = low ? p0 : a[4];
                    *(uint32_t*)(po + 384) = a[7];
                    *(uint32_t*)(po + 512) = a[9];
                    *(uint32_t*)(po + 640) = low ? p1 : a[5];
                    if (which < 2) {
                        const uint32_t u0 = bf2_fma(a[4], a[4], 0u), u1 = bf2_fma(a[5], a[5], 0u);
                        const uint32_t pe0 = bf2_fma(a[0], a[0], bf2_fma(a[2], a[2], low ? u0 : 0u));
                        const uint32_t pe1 = bf2_fma(a[1], a[1], bf2_fma(a[3], a[3], low ? u1 : 0u));
                        const uint32_t po0 = bf2_fma(a[6], a[6], bf2_fma(a[8], a[8], low ? 0u : u0));
                        const uint32_t po1 = bf2_fma(a[7], a[7], bf2_fma(a[9], a[9], low ? 0u : u1));
                        const float e0 = bf_lo(pe0) + bf_hi(pe0), e1 = bf_lo(pe1) + bf_hi(pe1);
                        const float o0 = bf_lo(po0) + bf_hi(po0), o1 = bf_lo(po1) + bf_hi(po1);
                        const bool b0 = c & 1, b1_ = c & 2;
                        const float x0 = (b0 ? e1 : e0) + __shfl_xor_sync(~0u, b0 ? e0 : e1, 1);
                        const float x1 = (b0 ? o1 : o0) + __shfl_xor_sync(~0u, b0 ? o0 : o1, 1);
                        float y = (b1_ ? x1 : x0) + __shfl_xor_sync(~0u, b1_ ? x0 : x1, 2);
                        if (which == 1 && (b0 ? emu1 : emu0)) y *= 0.25f;
                        g_nrm[(hs + (c >> 1)) * SEQ + row0 + (c & 1) * 8] = y;
                    }
                    if (it == 5) { __syncwarp(); if (lane == 0) mbar_arrive(bar + B_ST * 8); }
                }
            }
            wg_wait<0>();
            fence_regs(acc2);
            if (lane == 0) mbar_arrive(bar + (B_DEAD + 1) * 8);
            if (threadIdx.x == 256) TL(1, 2);
            mbar_wait(bar + B_AUX2 * 8, 0);
            if (threadIdx.x == 256) TL(4, 0);
            const uint32_t* bias = reinterpret_cast<const uint32_t*>(smem + SM_BIAS) + c;
            const int mrow = w4 * 16 + (lane & 15);
            const uint32_t stage = sAw + 7 * 16384;
            const uint32_t st_row = stage + mrow * 128;
#pragma unroll
            for (int j = 0; j < 24; j += 2) {
                const uint32_t bA = bias[j * 4], bB = bias[j * 4 + 4];
                const float2 cA = cs[(30 + j) * 4], cB = cs[(31 + j) * 4];
                const float* a = acc2 + j * 4;
                const uint32_t r00 = pack_bf16(gelu_half(fmaf(a[0], r20, fmaf(e20, cA.x, bf_lo(bA)))), gelu_half(fmaf(a[1], r20, fmaf(e20, cA.y, bf_hi(bA)))));
                const uint32_t r10 = pack_bf16(gelu_half(fmaf(a[2], r21, fmaf(e21, cA.x, bf_lo(bA)))), gelu_half(fmaf(a[3], r21, fmaf(e21, cA.y, bf_hi(bA)))));
                const uint32_t r01 = pack_bf16(gelu_half(fmaf(a[4], r20, fmaf(e20, cB.x, bf_lo(bB)))), gelu_half(fmaf(a[5], r20, fmaf(e20, cB.y, bf_hi(bB)))));
                const uint32_t r11 = pack_bf16(gelu_half(fmaf(a[6], r21, fmaf(e21, cB.x, bf_lo(bB)))), gelu_half(fmaf(a[7], r21, fmaf(e21, cB.y, bf_hi(bB)))));
                const int chunk = (j & 7) + (lane >> 4);
                stmatrix_x4(st_row + (j >> 3) * 16384 + ((chunk ^ (mrow & 7)) << 4), r00, r10, r01, r11);
            }
            if (threadIdx.x == 256) TL(4, 1);
            fence_proxy_async();
            __syncwarp();
            if (lane == 0) mbar_arrive(bar + (B_ST + 1) * 8);
            asm volatile("bar.sync %0, 128;" ::"r"(wgi + 3) : "memory");
            reg_dealloc<128>();
            if (threadIdx.x == 256) TL(4, 3);
        }
        __syncthreads();
        if (threadIdx.x == 0) TL(1, 3);
    }

    {
        const int h = blockIdx.x >> 2, qb = blockIdx.x & 3;
        const uint32_t sK = sb + SM_K, sV = sb + SM_V, barKV = bar + B_KV * 8;
        if (threadIdx.x == 0) TL(2, 0);
        auto late_tiles = [&]() {
            if (warp == 5 && lane == 0) {
                bulk_wait_read();
                asm volatile("fence.proxy.async.global;" ::: "memory");
                const uint8_t* gK = g_img + (size_t)(32 + h) * IMG_BYTES;
                const uint8_t* gV = g_img + (size_t)(64 + h) * IMG_BYTES;
                for (int i = 9; i < 16; i++) {
                    if (i >= 13) mbar_expect_tx(barKV + i * 8, i < 15 ? 12288 : 6144);
                    bulk_load(sV + ((i + 7) & 15) * 6144, gV + i * 6144, 6144, barKV + i * 8);
                    if (i >= 13 && i < 15) bulk_load(sK + (i + 1) * 6144, gK + (i + 1) * 6144, 6144, barKV + i * 8);
                }
            }
            __syncwarp();
        };
        const bool safe = __all_sync(~0u, *reinterpret_cast<volatile uint32_t*>(smem + SM_SAFE) != 0);
        if (threadIdx.x == 0) TL(2, 1);
        const uint64_t dK0 = make_desc(sK, 128, 384, 0), dV0 = make_desc(sV, 384, 128, 0);
        auto publish_h = [&]() {
            if (warp == 5) {
                if (lane == 0) { bulk_wait_all(); cnt_signal(CNT_H + rb); }
                __syncwarp();
            }
        };
        if (!safe) {
            late_tiles();
#pragma unroll 1
            for (int pass = 0; pass < 2; pass++) {
                const uint32_t sQ = sb + SM_Q + pass * 12288 + wgi * 3072;
                mbar_wait(bar + (B_Q + pass) * 8, 0);
                attn_rows_maxshift(sK, barKV, make_desc(sQ, 128, 384, 0), make_desc(sQ + 256, sb + SM_ZERO - (sQ + 256), 384, 0), h,
                                   qb * 512 + pass * 256 + wgi * 64 + w4 * 16);
                if (pass == 0) publish_h();
            }
        } else {
            const ExpConst kc = make_exp_const();
#pragma unroll 1
            for (int pass = 0; pass < 2; pass++) {
                const int rbase = qb * 512 + pass * 256 + wgi * 64 + w4 * 16;
                const uint32_t sQ = sb + SM_Q + pass * 12288 + wgi * 3072;
                const uint64_t dQ = make_desc(sQ, 128, 384, 0), dQ2 = make_desc(sQ + 256, sb + SM_ZERO - (sQ + 256), 384, 0);
                float o[12], sa[32], sc[32];
                uint32_t p[16];
#pragma unroll
                for (int i = 0; i < 12; i++) o[i] = 0.f;
                fence_regs(o);
                mbar_wait(bar + (B_Q + pass) * 8, 0);
                mbar_wait(barKV + 128, 0);
                qk_tile(sa, dQ, dQ2, dK0);
                wg_wait<0>();
                fence_regs(sa);
                uint64_t dK = dK0, dV = dV0 + 7 * 384;
                uint32_t bj = barKV;
#pragma unroll 1
                for (int j = 0; j < 16; j++) {
                    mbar_wait(bj, 0);
                    if (pass == 0 && j == 2) late_tiles();
                    qk_tile(sc, dQ, dQ2, dK + 192);
                    wg_wait<1>();
                    exp_tile<0>(sa, p, kc);
                    pv_tile(o, p, dV);
                    wg_wait<1>();
                    fence_regs(sc);
                    mbar_wait(bj, 0);
                    qk_tile(sa, dQ, dQ2, dK + 384);
                    wg_wait<1>();
                    exp_tile<8>(sc, p, kc);
                    pv_tile(o, p, dV + 192);
                    wg_wait<1>();
                    fence_regs(sa);
                    dK += 384; dV = j == 8 ? dV0 : dV + 384; bj += 8;
                }
                wg_wait<0>();
                fence_regs(o);
                store_o(o, h, rbase, lane);
                if (threadIdx.x == 0) TL(2, 2 + pass);
                if (pass == 0) publish_h();
            }
        }
        __syncthreads();
        if (threadIdx.x == 64) cnt_signal(CNT_O + qb);
        cluster_arrive_relaxed();
    }

    {
        const uint32_t epoch = *reinterpret_cast<volatile uint32_t*>(smem + SM_EPOCH);
        const int ct = cl & 3, rt = (cl >> 2) * 2 + rank;
        if (threadIdx.x == 0) TL(3, 0);
        const int orow = threadIdx.x >> 3, oseg = threadIdx.x & 7;
        const size_t ooff = (size_t)(rt * 64 + orow) * DM + ct * 160 + oseg * 20;
        uint2 xr[5], br[5];
#pragma unroll
        for (int i = 0; i < 5; i++) {
            xr[i] = __ldg(reinterpret_cast<const uint2*>(x + ooff) + i);
            br[i] = __ldg(reinterpret_cast<const uint2*>(b2 + ct * 160 + oseg * 20) + i);
        }
        cluster_wait();
        float* stg = reinterpret_cast<float*>(smem);
        if (warp == 4) {
            if (elect_one()) { prefetch_map(&tm.h); prefetch_map(&tm.o); prefetch_map(&tm.w2); prefetch_map(&tm.wo); cnt_wait(CNT_H + (rt >> 1), (epoch + 1) * 8); }
            __syncwarp();
#pragma unroll 1
            for (int kb = 0; kb < 34; kb++) {
                const int s = kb & 7;
                if (kb >= 8) mbar_wait(bar + (B_E3 + s) * 8, ((kb >> 3) - 1) & 1);
                if (elect_one()) {
                    if (kb == 24) { cnt_wait(CNT_O + (rt >> 3), (epoch + 1) * 32); TL(3, 1); }
                    const uint32_t dst = sb + s * G2_STAGE, fb = bar + (B_F3 + s) * 8;
                    const CUtensorMap* mA = kb < 24 ? &tm.h : &tm.o;
                    const CUtensorMap* mB = kb < 24 ? &tm.w2 : &tm.wo;
                    const int k0 = (kb < 24 ? kb : kb - 24) * 64;
                    mbar_expect_tx(fb, G2_STAGE);
                    tma_load(dst, mA, k0, rt * 64, fb);
                    const int first = ((kb & 1) == (int)rank) ? 0 : 3, last = ((kb & 1) == (int)rank) ? 3 : 5;
                    for (int b = first; b < last; b++) tma_load_mc(dst + 8192 + b * 4096, mB, ct * 160 + b * 32, k0, fb, 3);
                }
                __syncwarp();
            }
        } else if (wgi == 0) {
            float acc[80];
#pragma unroll 1
            for (int kb = 0; kb < 34; kb++) {
                const int s = kb & 7;
                mbar_wait(bar + (B_F3 + s) * 8, (kb >> 3) & 1);
                wg_fence();
                const uint64_t dA = make_desc(sb + s * G2_STAGE, 16, 1024, 1);
                const uint64_t dB = make_desc(sb + s * G2_STAGE + 8192, 4096, 512, 2);
#pragma unroll
                for (int kk = 0; kk < 4; kk++) wgmma_n160_ss_tb(acc, dA + kk * 2, dB + kk * 64, (kb | kk) != 0);
                wg_commit();
                if (kb > 0) {
                    wg_wait<1>();
                    if (kb <= 26) release_stage(bar + (B_E3 + ((kb - 1) & 7)) * 8, peer, lane);
                }
            }
            wg_wait<0>();
            fence_regs(acc);
            if (threadIdx.x == 0) TL(3, 2);
            const int r = w4 * 16 + g;
#pragma unroll
            for (int j = 0; j < 20; j++) {
                *reinterpret_cast<float2*>(stg + r * 168 + j * 8 + 2 * c) = make_float2(acc[4 * j], acc[4 * j + 1]);
                *reinterpret_cast<float2*>(stg + (r + 8) * 168 + j * 8 + 2 * c) = make_float2(acc[4 * j + 2], acc[4 * j + 3]);
            }
        }
        __syncthreads();
        const float4* sp = reinterpret_cast<const float4*>(stg + orow * 168 + oseg * 20);
#pragma unroll
        for (int i = 0; i < 5; i++) {
            const float4 a = sp[i];
            uint2 w;
            w.x = pack_bf16(a.x + bf_lo(br[i].x) + bf_lo(xr[i].x), a.y + bf_hi(br[i].x) + bf_hi(xr[i].x));
            w.y = pack_bf16(a.z + bf_lo(br[i].y) + bf_lo(xr[i].y), a.w + bf_hi(br[i].y) + bf_hi(xr[i].y));
            reinterpret_cast<uint2*>(out + ooff)[i] = w;
        }
        if (blockIdx.x == 0 && threadIdx.x == 0) g_epoch = epoch + 1;
        if (threadIdx.x == 0) TL(3, 3);
    }
    cluster_arrive_relaxed();
    cluster_wait();
}

typedef CUresult (*EncodeTiledFn)(CUtensorMap*, CUtensorMapDataType, cuuint32_t, void*, const cuuint64_t*,
                                  const cuuint64_t*, const cuuint32_t*, const cuuint32_t*, CUtensorMapInterleave,
                                  CUtensorMapSwizzle, CUtensorMapL2promotion, CUtensorMapFloatOOBfill);

CUtensorMap make_map(EncodeTiledFn enc, const void* ptr, int rows, int cols, int box_rows, int box_cols,
                     CUtensorMapSwizzle swz) {
    CUtensorMap m;
    cuuint64_t gd[2] = {(cuuint64_t)cols, (cuuint64_t)rows};
    cuuint64_t gs[1] = {(cuuint64_t)cols * 2};
    cuuint32_t bd[2] = {(cuuint32_t)box_cols, (cuuint32_t)box_rows};
    cuuint32_t es[2] = {1, 1};
    enc(&m, CU_TENSOR_MAP_DATA_TYPE_BFLOAT16, 2, const_cast<void*>(ptr), gd, gs, bd, es, CU_TENSOR_MAP_INTERLEAVE_NONE,
        swz, CU_TENSOR_MAP_L2_PROMOTION_L2_128B, CU_TENSOR_MAP_FLOAT_OOB_FILL_NONE);
    return m;
}

}

extern "C" void kernel_launch(void* const* d_in, const int* in_sizes, int n_in, void* d_out, int out_size) {
    (void)in_sizes; (void)n_in; (void)out_size;
    const __nv_bfloat16* x = (const __nv_bfloat16*)d_in[0];
    const __nv_bfloat16* wqkv = (const __nv_bfloat16*)d_in[1];
    const __nv_bfloat16* wo = (const __nv_bfloat16*)d_in[2];
    const __nv_bfloat16* w1 = (const __nv_bfloat16*)d_in[4];
    const __nv_bfloat16* b1 = (const __nv_bfloat16*)d_in[5];
    const __nv_bfloat16* w2 = (const __nv_bfloat16*)d_in[6];
    const __nv_bfloat16* b2 = (const __nv_bfloat16*)d_in[7];
    __nv_bfloat16* out = (__nv_bfloat16*)d_out;

    static EncodeTiledFn enc = nullptr;
    static void *p_h, *p_o;
    if (!enc) {
        cudaDriverEntryPointQueryResult qr;
        cudaGetDriverEntryPoint("cuTensorMapEncodeTiled", (void**)&enc, cudaEnableDefault, &qr);
        cudaGetSymbolAddress(&p_h, g_h);
        cudaGetSymbolAddress(&p_o, g_o);
        cudaFuncSetAttribute(k_fused, cudaFuncAttributeMaxDynamicSharedMemorySize, SM_TOTAL);
    }
    Maps tm;
    tm.x = make_map(enc, x, SEQ, DM, 128, 64, CU_TENSOR_MAP_SWIZZLE_128B);
    tm.wqkv = make_map(enc, wqkv, DM, 3 * DM, 32, 64, CU_TENSOR_MAP_SWIZZLE_128B);
    tm.w1 = make_map(enc, w1, DM, FF, 32, 64, CU_TENSOR_MAP_SWIZZLE_128B);
    tm.h = make_map(enc, p_h, SEQ, FF, 64, 64, CU_TENSOR_MAP_SWIZZLE_128B);
    tm.o = make_map(enc, p_o, SEQ, DM, 64, 64, CU_TENSOR_MAP_SWIZZLE_128B);
    tm.wo = make_map(enc, wo, DM, DM, 64, 32, CU_TENSOR_MAP_SWIZZLE_64B);
    tm.w2 = make_map(enc, w2, FF, DM, 64, 32, CU_TENSOR_MAP_SWIZZLE_64B);
    k_fused<<<128, 512, SM_TOTAL, cudaStreamPerThread>>>(tm, x, (const uint8_t*)wqkv, (const uint8_t*)w1, (const uint8_t*)w2,
                                                         (const uint8_t*)wo, b1, b2, out);
}
```

```cpp
#include <cuda_runtime.h>
#include <cuda_bf16.h>
#include <cuda.h>
#include <stdint.h>

namespace {

constexpr int SEQ = 2048, DM = 640, FF = 1536;
constexpr float LN_EPS = 1e-5f;

constexpr int IMG_BYTES = 256 * 384;
constexpr uint32_t EMU_MASK = 0xD5D5u;
constexpr float SAFE_BOUND = 80.0f;
constexpr float QSCALE = 0.22360679774997896f * 1.4426950408889634f;

__device__ float4 g_stat[SEQ];
__device__ float2 g_csp[16 * 960];
__device__ float2 g_csp2[16 * 768];
__device__ __align__(1024) uint8_t g_img[96 * IMG_BYTES + 1024];
__device__ float g_nrm[64 * SEQ];
__device__ __align__(1024) __nv_bfloat16 g_h[SEQ * FF];
__device__ __align__(1024) __nv_bfloat16 g_o[SEQ * DM];
constexpr int CNT_ST = 0, CNT_QKV = 16, CNT_CS = 24, CNT_CS2 = 32, CNT_O = 40, CNT_H = 44;
__device__ uint32_t g_cnt[60 * 32];
__device__ uint32_t g_epoch;

#define TL(kern, slot) do { } while (0)
#define IT(row, i) do { } while (0)

__device__ __forceinline__ uint32_t smem_u32(const void* p) { return (uint32_t)__cvta_generic_to_shared(p); }
__device__ __forceinline__ void mbar_init(uint32_t bar, int cnt) {
    asm volatile("mbarrier.init.shared::cta.b64 [%0], %1;" ::"r"(bar), "r"(cnt));
}
__device__ __forceinline__ void mbar_expect_tx(uint32_t bar, uint32_t bytes) {
    asm volatile("mbarrier.arrive.expect_tx.shared::cta.b64 _, [%0], %1;" ::"r"(bar), "r"(bytes) : "memory");
}
__device__ __forceinline__ void mbar_wait(uint32_t bar, uint32_t parity) {
    asm volatile("{\n.reg .pred p;\n.reg .u32 n;\nmov.u32 n, 0;\n"
                 "WAIT_LOOP:\nmbarrier.try_wait.parity.shared::cta.b64 p, [%0], %1;\n@p bra WAIT_DONE;\n"
                 "add.u32 n, n, 1;\nsetp.lt.u32 p, n, 1048576;\n@p bra WAIT_LOOP;\nWAIT_DONE:\n}"
                 ::"r"(bar), "r"(parity) : "memory");
}
__device__ __forceinline__ void mbar_arrive(uint32_t bar) {
    asm volatile("mbarrier.arrive.shared::cta.b64 _, [%0];" ::"r"(bar) : "memory");
}
__device__ __forceinline__ void mbar_arrive_cluster(uint32_t bar, uint32_t cta) {
    asm volatile("{\n.reg .b32 ra;\nmapa.shared::cluster.u32 ra, %0, %1;\n"
                 "mbarrier.arrive.shared::cluster.b64 _, [ra];\n}" ::"r"(bar), "r"(cta) : "memory");
}
__device__ __forceinline__ void fence_barrier_init() { asm volatile("fence.mbarrier_init.release.cluster;" ::: "memory"); }
__device__ __forceinline__ void fence_proxy_async() { asm volatile("fence.proxy.async.shared::cta;" ::: "memory"); }
__device__ __forceinline__ void cluster_sync() {
    asm volatile("barrier.cluster.arrive.release.aligned;\nbarrier.cluster.wait.acquire.aligned;" ::: "memory");
}
__device__ __forceinline__ bool elect_one() {
    uint32_t pred;
    asm volatile("{\n.reg .pred p;\nelect.sync _|p, 0xFFFFFFFF;\nselp.b32 %0, 1, 0, p;\n}" : "=r"(pred));
    return pred != 0;
}
__device__ __forceinline__ void pdl_launch() { asm volatile("griddepcontrol.launch_dependents;" ::: "memory"); }
__device__ __forceinline__ void pdl_wait() { asm volatile("griddepcontrol.wait;" ::: "memory"); }
__device__ __forceinline__ void prefetch_map(const CUtensorMap* m) {
    asm volatile("prefetch.tensormap [%0];" ::"l"(m) : "memory");
}
__device__ __forceinline__ void tma_load(uint32_t dst, const CUtensorMap* m, int c0, int c1, uint32_t bar) {
    asm volatile("cp.async.bulk.tensor.2d.shared::cluster.global.mbarrier::complete_tx::bytes [%0], [%1, {%3, %4}], [%2];"
                 ::"r"(dst), "l"(m), "r"(bar), "r"(c0), "r"(c1) : "memory");
}
__device__ __forceinline__ void tma_load_mc(uint32_t dst, const CUtensorMap* m, int c0, int c1, uint32_t bar, uint16_t mask) {
    asm volatile("cp.async.bulk.tensor.2d.shared::cluster.global.mbarrier::complete_tx::bytes.multicast::cluster"
                 " [%0], [%1, {%3, %4}], [%2], %5;"
                 ::"r"(dst), "l"(m), "r"(bar), "r"(c0), "r"(c1), "h"(mask) : "memory");
}
__device__ __forceinline__ void tma_store(const CUtensorMap* m, uint32_t src, int c0, int c1) {
    asm volatile("cp.async.bulk.tensor.2d.global.shared::cta.bulk_group [%0, {%2, %3}], [%1];"
                 ::"l"(m), "r"(src), "r"(c0), "r"(c1) : "memory");
}
__device__ __forceinline__ void bulk_commit() { asm volatile("cp.async.bulk.commit_group;" ::: "memory"); }
__device__ __forceinline__ void bulk_wait_all() { asm volatile("cp.async.bulk.wait_group 0;" ::: "memory"); }
__device__ __forceinline__ void bulk_load(uint32_t dst, const void* src, uint32_t bytes, uint32_t bar) {
    asm volatile("cp.async.bulk.shared::cluster.global.mbarrier::complete_tx::bytes [%0], [%1], %2, [%3];"
                 ::"r"(dst), "l"(src), "r"(bytes), "r"(bar) : "memory");
}
__device__ __forceinline__ void prefetch_l2(const void* p, uint32_t bytes) {
    asm volatile("cp.async.bulk.prefetch.L2.global [%0], %1;" ::"l"(p), "r"(bytes) : "memory");
}
__device__ __forceinline__ void tma_prefetch_l2(const CUtensorMap* m, int c0, int c1) {
    asm volatile("cp.async.bulk.prefetch.tensor.2d.L2.global.tile [%0, {%1, %2}];" ::"l"(m), "r"(c0), "r"(c1) : "memory");
}
__device__ __forceinline__ void wg_fence() { asm volatile("wgmma.fence.sync.aligned;" ::: "memory"); }
__device__ __forceinline__ void wg_commit() { asm volatile("wgmma.commit_group.sync.aligned;" ::: "memory"); }
template <int N> __device__ __forceinline__ void wg_wait() {
    asm volatile("wgmma.wait_group.sync.aligned %0;" ::"n"(N) : "memory");
}
template <int N> __device__ __forceinline__ void reg_alloc() { asm volatile("setmaxnreg.inc.sync.aligned.u32 %0;" ::"n"(N)); }
template <int N> __device__ __forceinline__ void reg_dealloc() { asm volatile("setmaxnreg.dec.sync.aligned.u32 %0;" ::"n"(N)); }
template <int N> __device__ __forceinline__ void fence_regs(float (&d)[N]) {
#pragma unroll
    for (int i = 0; i < N; i++) asm volatile("" : "+f"(d[i])::"memory");
}
__device__ __forceinline__ uint64_t make_desc(uint32_t addr, uint32_t lbo, uint32_t sbo, uint32_t swz) {
    return (uint64_t)((addr & 0x3FFFF) >> 4) | ((uint64_t)(lbo >> 4) << 16) | ((uint64_t)(sbo >> 4) << 32) |
           ((uint64_t)swz << 62);
}
__device__ __forceinline__ uint32_t pack_bf16(float lo, float hi) {
    uint32_t r;
    asm("cvt.rn.bf16x2.f32 %0, %1, %2;" : "=r"(r) : "f"(hi), "f"(lo));
    return r;
}
__device__ __forceinline__ float ex2(float x) {
    float r;
    asm("ex2.approx.ftz.f32 %0, %1;" : "=f"(r) : "f"(x));
    return r;
}
__device__ __forceinline__ float bf_lo(uint32_t v) { return __uint_as_float(v << 16); }
__device__ __forceinline__ float bf_hi(uint32_t v) { return __uint_as_float(v & 0xFFFF0000u); }
__device__ __forceinline__ void stmatrix_x4(uint32_t addr, uint32_t r0, uint32_t r1, uint32_t r2, uint32_t r3) {
    asm volatile("stmatrix.sync.aligned.m8n8.x4.shared.b16 [%0], {%1, %2, %3, %4};"
                 ::"r"(addr), "r"(r0), "r"(r1), "r"(r2), "r"(r3) : "memory");
}

__device__ __forceinline__ void wgmma_n200_ss_tb(float (&d)[100], uint64_t descA, uint64_t descB, int scaleD) {
    asm volatile("{\n.reg .pred p;\nsetp.ne.b32 p, %102, 0;\n"
        "wgmma.mma_async.sync.aligned.m64n200k16.f32.bf16.bf16 {"
        "%0, %1, %2, %3, %4, %5, %6, %7, %8, %9, %10, %11, %12, %13, %14, %15, "
        "%16, %17, %18, %19, %20, %21, %22, %23, %24, %25, %26, %27, %28, %29, %30, %31, "
        "%32, %33, %34, %35, %36, %37, %38, %39, %40, %41, %42, %43, %44, %45, %46, %47, "
        "%48, %49, %50, %51, %52, %53, %54, %55, %56, %57, %58, %59, %60, %61, %62, %63, "
        "%64, %65, %66, %67, %68, %69, %70, %71, %72, %73, %74, %75, %76, %77, %78, %79, "
        "%80, %81, %82, %83, %84, %85, %86, %87, %88, %89, %90, %91, %92, %93, %94, %95, "
        "%96, %97, %98, %99}, "
        "%100, %101, p, 1, 1, 0, 1;\n}\n"
        : "+f"(d[0]), "+f"(d[1]), "+f"(d[2]), "+f"(d[3]), "+f"(d[4]), "+f"(d[5]), "+f"(d[6]), "+f"(d[7]),
          "+f"(d[8]), "+f"(d[9]), "+f"(d[10]), "+f"(d[11]), "+f"(d[12]), "+f"(d[13]), "+f"(d[14]), "+f"(d[15]),
          "+f"(d[16]), "+f"(d[17]), "+f"(d[18]), "+f"(d[19]), "+f"(d[20]), "+f"(d[21]), "+f"(d[22]), "+f"(d[23]),
          "+f"(d[24]), "+f"(d[25]), "+f"(d[26]), "+f"(d[27]), "+f"(d[28]), "+f"(d[29]), "+f"(d[30]), "+f"(d[31]),
          "+f"(d[32]), "+f"(d[33]), "+f"(d[34]), "+f"(d[35]), "+f"(d[36]), "+f"(d[37]), "+f"(d[38]), "+f"(d[39]),
          "+f"(d[40]), "+f"(d[41]), "+f"(d[42]), "+f"(d[43]), "+f"(d[44]), "+f"(d[45]), "+f"(d[46]), "+f"(d[47]),
          "+f"(d[48]), "+f"(d[49]), "+f"(d[50]), "+f"(d[51]), "+f"(d[52]), "+f"(d[53]), "+f"(d[54]), "+f"(d[55]),
          "+f"(d[56]), "+f"(d[57]), "+f"(d[58]), "+f"(d[59]), "+f"(d[60]), "+f"(d[61]), "+f"(d[62]), "+f"(d[63]),
          "+f"(d[64]), "+f"(d[65]), "+f"(d[66]), "+f"(d[67]), "+f"(d[68]), "+f"(d[69]), "+f"(d[70]), "+f"(d[71]),
          "+f"(d[72]), "+f"(d[73]), "+f"(d[74]), "+f"(d[75]), "+f"(d[76]), "+f"(d[77]), "+f"(d[78]), "+f"(d[79]),
          "+f"(d[80]), "+f"(d[81]), "+f"(d[82]), "+f"(d[83]), "+f"(d[84]), "+f"(d[85]), "+f"(d[86]), "+f"(d[87]),
          "+f"(d[88]), "+f"(d[89]), "+f"(d[90]), "+f"(d[91]), "+f"(d[92]), "+f"(d[93]), "+f"(d[94]), "+f"(d[95]),
          "+f"(d[96]), "+f"(d[97]), "+f"(d[98]), "+f"(d[99])
        : "l"(descA), "l"(descB), "r"(scaleD));
}

__device__ __forceinline__ void wgmma_n40_ss_tb(float (&d)[20], uint64_t descA, uint64_t descB, int scaleD) {
    asm volatile("{\n.reg .pred p;\nsetp.ne.b32 p, %22, 0;\n"
        "wgmma.mma_async.sync.aligned.m64n40k16.f32.bf16.bf16 {"
        "%0, %1, %2, %3, %4, %5, %6, %7, %8, %9, %10, %11, %12, %13, %14, %15, "
        "%16, %17, %18, %19}, "
        "%20, %21, p, 1, 1, 0, 1;\n}\n"
        : "+f"(d[0]), "+f"(d[1]), "+f"(d[2]), "+f"(d[3]), "+f"(d[4]), "+f"(d[5]), "+f"(d[6]), "+f"(d[7]),
          "+f"(d[8]), "+f"(d[9]), "+f"(d[10]), "+f"(d[11]), "+f"(d[12]), "+f"(d[13]), "+f"(d[14]), "+f"(d[15]),
          "+f"(d[16]), "+f"(d[17]), "+f"(d[18]), "+f"(d[19])
        : "l"(descA), "l"(descB), "r"(scaleD));
}

__device__ __forceinline__ void wgmma_n192_ss_tb(float (&d)[96], uint64_t descA, uint64_t descB, int scaleD) {
    asm volatile("{\n.reg .pred p;\nsetp.ne.b32 p, %98, 0;\n"
        "wgmma.mma_async.sync.aligned.m64n192k16.f32.bf16.bf16 {"
        "%0, %1, %2, %3, %4, %5, %6, %7, %8, %9, %10, %11, %12, %13, %14, %15, "
        "%16, %17, %18, %19, %20, %21, %22, %23, %24, %25, %26, %27, %28, %29, %30, %31, "
        "%32, %33, %34, %35, %36, %37, %38, %39, %40, %41, %42, %43, %44, %45, %46, %47, "
        "%48, %49, %50, %51, %52, %53, %54, %55, %56, %57, %58, %59, %60, %61, %62, %63, "
        "%64, %65, %66, %67, %68, %69, %70, %71, %72, %73, %74, %75, %76, %77, %78, %79, "
        "%80, %81, %82, %83, %84, %85, %86, %87, %88, %89, %90, %91, %92, %93, %94, %95}, "
        "%96, %97, p, 1, 1, 0, 1;\n}\n"
        : "+f"(d[0]), "+f"(d[1]), "+f"(d[2]), "+f"(d[3]), "+f"(d[4]), "+f"(d[5]), "+f"(d[6]), "+f"(d[7]),
          "+f"(d[8]), "+f"(d[9]), "+f"(d[10]), "+f"(d[11]), "+f"(d[12]), "+f"(d[13]), "+f"(d[14]), "+f"(d[15]),
          "+f"(d[16]), "+f"(d[17]), "+f"(d[18]), "+f"(d[19]), "+f"(d[20]), "+f"(d[21]), "+f"(d[22]), "+f"(d[23]),
          "+f"(d[24]), "+f"(d[25]), "+f"(d[26]), "+f"(d[27]), "+f"(d[28]), "+f"(d[29]), "+f"(d[30]), "+f"(d[31]),
          "+f"(d[32]), "+f"(d[33]), "+f"(d[34]), "+f"(d[35]), "+f"(d[36]), "+f"(d[37]), "+f"(d[38]), "+f"(d[39]),
          "+f"(d[40]), "+f"(d[41]), "+f"(d[42]), "+f"(d[43]), "+f"(d[44]), "+f"(d[45]), "+f"(d[46]), "+f"(d[47]),
          "+f"(d[48]), "+f"(d[49]), "+f"(d[50]), "+f"(d[51]), "+f"(d[52]), "+f"(d[53]), "+f"(d[54]), "+f"(d[55]),
          "+f"(d[56]), "+f"(d[57]), "+f"(d[58]), "+f"(d[59]), "+f"(d[60]), "+f"(d[61]), "+f"(d[62]), "+f"(d[63]),
          "+f"(d[64]), "+f"(d[65]), "+f"(d[66]), "+f"(d[67]), "+f"(d[68]), "+f"(d[69]), "+f"(d[70]), "+f"(d[71]),
          "+f"(d[72]), "+f"(d[73]), "+f"(d[74]), "+f"(d[75]), "+f"(d[76]), "+f"(d[77]), "+f"(d[78]), "+f"(d[79]),
          "+f"(d[80]), "+f"(d[81]), "+f"(d[82]), "+f"(d[83]), "+f"(d[84]), "+f"(d[85]), "+f"(d[86]), "+f"(d[87]),
          "+f"(d[88]), "+f"(d[89]), "+f"(d[90]), "+f"(d[91]), "+f"(d[92]), "+f"(d[93]), "+f"(d[94]), "+f"(d[95])
        : "l"(descA), "l"(descB), "r"(scaleD));
}

__device__ __forceinline__ void wgmma_n192_ss_tb_z(float (&d)[96], uint64_t descA, uint64_t descB) {
    asm volatile("{\n.reg .pred p;\nsetp.ne.b32 p, 0, 0;\n"
        "wgmma.mma_async.sync.aligned.m64n192k16.f32.bf16.bf16 {"
        "%0, %1, %2, %3, %4, %5, %6, %7, %8, %9, %10, %11, %12, %13, %14, %15, "
        "%16, %17, %18, %19, %20, %21, %22, %23, %24, %25, %26, %27, %28, %29, %30, %31, "
        "%32, %33, %34, %35, %36, %37, %38, %39, %40, %41, %42, %43, %44, %45, %46, %47, "
        "%48, %49, %50, %51, %52, %53, %54, %55, %56, %57, %58, %59, %60, %61, %62, %63, "
        "%64, %65, %66, %67, %68, %69, %70, %71, %72, %73, %74, %75, %76, %77, %78, %79, "
        "%80, %81, %82, %83, %84, %85, %86, %87, %88, %89, %90, %91, %92, %93, %94, %95}, "
        "%96, %97, p, 1, 1, 0, 1;\n}\n"
        : "=f"(d[0]), "=f"(d[1]), "=f"(d[2]), "=f"(d[3]), "=f"(d[4]), "=f"(d[5]), "=f"(d[6]), "=f"(d[7]),
          "=f"(d[8]), "=f"(d[9]), "=f"(d[10]), "=f"(d[11]), "=f"(d[12]), "=f"(d[13]), "=f"(d[14]), "=f"(d[15]),
          "=f"(d[16]), "=f"(d[17]), "=f"(d[18]), "=f"(d[19]), "=f"(d[20]), "=f"(d[21]), "=f"(d[22]), "=f"(d[23]),
          "=f"(d[24]), "=f"(d[25]), "=f"(d[26]), "=f"(d[27]), "=f"(d[28]), "=f"(d[29]), "=f"(d[30]), "=f"(d[31]),
          "=f"(d[32]), "=f"(d[33]), "=f"(d[34]), "=f"(d[35]), "=f"(d[36]), "=f"(d[37]), "=f"(d[38]), "=f"(d[39]),
          "=f"(d[40]), "=f"(d[41]), "=f"(d[42]), "=f"(d[43]), "=f"(d[44]), "=f"(d[45]), "=f"(d[46]), "=f"(d[47]),
          "=f"(d[48]), "=f"(d[49]), "=f"(d[50]), "=f"(d[51]), "=f"(d[52]), "=f"(d[53]), "=f"(d[54]), "=f"(d[55]),
          "=f"(d[56]), "=f"(d[57]), "=f"(d[58]), "=f"(d[59]), "=f"(d[60]), "=f"(d[61]), "=f"(d[62]), "=f"(d[63]),
          "=f"(d[64]), "=f"(d[65]), "=f"(d[66]), "=f"(d[67]), "=f"(d[68]), "=f"(d[69]), "=f"(d[70]), "=f"(d[71]),
          "=f"(d[72]), "=f"(d[73]), "=f"(d[74]), "=f"(d[75]), "=f"(d[76]), "=f"(d[77]), "=f"(d[78]), "=f"(d[79]),
          "=f"(d[80]), "=f"(d[81]), "=f"(d[82]), "=f"(d[83]), "=f"(d[84]), "=f"(d[85]), "=f"(d[86]), "=f"(d[87]),
          "=f"(d[88]), "=f"(d[89]), "=f"(d[90]), "=f"(d[91]), "=f"(d[92]), "=f"(d[93]), "=f"(d[94]), "=f"(d[95])
        : "l"(descA), "l"(descB));
}

__device__ __forceinline__ void wgmma_n160_ss_tb(float (&d)[80], uint64_t descA, uint64_t descB, int scaleD) {
    asm volatile("{\n.reg .pred p;\nsetp.ne.b32 p, %82, 0;\n"
        "wgmma.mma_async.sync.aligned.m64n160k16.f32.bf16.bf16 {"
        "%0, %1, %2, %3, %4, %5, %6, %7, %8, %9, %10, %11, %12, %13, %14, %15, "
        "%16, %17, %18, %19, %20, %21, %22, %23, %24, %25, %26, %27, %28, %29, %30, %31, "
        "%32, %33, %34, %35, %36, %37, %38, %39, %40, %41, %42, %43, %44, %45, %46, %47, "
        "%48, %49, %50, %51, %52, %53, %54, %55, %56, %57, %58, %59, %60, %61, %62, %63, "
        "%64, %65, %66, %67, %68, %69, %70, %71, %72, %73, %74, %75, %76, %77, %78, %79}, "
        "%80, %81, p, 1, 1, 0, 1;\n}\n"
        : "+f"(d[0]), "+f"(d[1]), "+f"(d[2]), "+f"(d[3]), "+f"(d[4]), "+f"(d[5]), "+f"(d[6]), "+f"(d[7]),
          "+f"(d[8]), "+f"(d[9]), "+f"(d[10]), "+f"(d[11]), "+f"(d[12]), "+f"(d[13]), "+f"(d[14]), "+f"(d[15]),
          "+f"(d[16]), "+f"(d[17]), "+f"(d[18]), "+f"(d[19]), "+f"(d[20]), "+f"(d[21]), "+f"(d[22]), "+f"(d[23]),
          "+f"(d[24]), "+f"(d[25]), "+f"(d[26]), "+f"(d[27]), "+f"(d[28]), "+f"(d[29]), "+f"(d[30]), "+f"(d[31]),
          "+f"(d[32]), "+f"(d[33]), "+f"(d[34]), "+f"(d[35]), "+f"(d[36]), "+f"(d[37]), "+f"(d[38]), "+f"(d[39]),
          "+f"(d[40]), "+f"(d[41]), "+f"(d[42]), "+f"(d[43]), "+f"(d[44]), "+f"(d[45]), "+f"(d[46]), "+f"(d[47]),
          "+f"(d[48]), "+f"(d[49]), "+f"(d[50]), "+f"(d[51]), "+f"(d[52]), "+f"(d[53]), "+f"(d[54]), "+f"(d[55]),
          "+f"(d[56]), "+f"(d[57]), "+f"(d[58]), "+f"(d[59]), "+f"(d[60]), "+f"(d[61]), "+f"(d[62]), "+f"(d[63]),
          "+f"(d[64]), "+f"(d[65]), "+f"(d[66]), "+f"(d[67]), "+f"(d[68]), "+f"(d[69]), "+f"(d[70]), "+f"(d[71]),
          "+f"(d[72]), "+f"(d[73]), "+f"(d[74]), "+f"(d[75]), "+f"(d[76]), "+f"(d[77]), "+f"(d[78]), "+f"(d[79])
        : "l"(descA), "l"(descB), "r"(scaleD));
}

__device__ __forceinline__ void wgmma_n64_rs(float (&d)[32], uint32_t a0, uint32_t a1, uint32_t a2, uint32_t a3, uint64_t descB, int scaleD) {
    asm volatile("{\n.reg .pred p;\nsetp.ne.b32 p, %37, 0;\n"
        "wgmma.mma_async.sync.aligned.m64n64k16.f32.bf16.bf16 {"
        "%0, %1, %2, %3, %4, %5, %6, %7, %8, %9, %10, %11, %12, %13, %14, %15, "
        "%16, %17, %18, %19, %20, %21, %22, %23, %24, %25, %26, %27, %28, %29, %30, %31}, "
        "{%32, %33, %34, %35}, %36, p, 1, 1, 0;\n}\n"
        : "+f"(d[0]), "+f"(d[1]), "+f"(d[2]), "+f"(d[3]), "+f"(d[4]), "+f"(d[5]), "+f"(d[6]), "+f"(d[7]),
          "+f"(d[8]), "+f"(d[9]), "+f"(d[10]), "+f"(d[11]), "+f"(d[12]), "+f"(d[13]), "+f"(d[14]), "+f"(d[15]),
          "+f"(d[16]), "+f"(d[17]), "+f"(d[18]), "+f"(d[19]), "+f"(d[20]), "+f"(d[21]), "+f"(d[22]), "+f"(d[23]),
          "+f"(d[24]), "+f"(d[25]), "+f"(d[26]), "+f"(d[27]), "+f"(d[28]), "+f"(d[29]), "+f"(d[30]), "+f"(d[31])
        : "r"(a0), "r"(a1), "r"(a2), "r"(a3), "l"(descB), "r"(scaleD));
}

__device__ __forceinline__ void wgmma_n64_rs_z(float (&d)[32], uint32_t a0, uint32_t a1, uint32_t a2, uint32_t a3, uint64_t descB) {
    asm volatile("{\n.reg .pred p;\nsetp.ne.b32 p, 0, 0;\n"
        "wgmma.mma_async.sync.aligned.m64n64k16.f32.bf16.bf16 {"
        "%0, %1, %2, %3, %4, %5, %6, %7, %8, %9, %10, %11, %12, %13, %14, %15, "
        "%16, %17, %18, %19, %20, %21, %22, %23, %24, %25, %26, %27, %28, %29, %30, %31}, "
        "{%32, %33, %34, %35}, %36, p, 1, 1, 0;\n}\n"
        : "=f"(d[0]), "=f"(d[1]), "=f"(d[2]), "=f"(d[3]), "=f"(d[4]), "=f"(d[5]), "=f"(d[6]), "=f"(d[7]),
          "=f"(d[8]), "=f"(d[9]), "=f"(d[10]), "=f"(d[11]), "=f"(d[12]), "=f"(d[13]), "=f"(d[14]), "=f"(d[15]),
          "=f"(d[16]), "=f"(d[17]), "=f"(d[18]), "=f"(d[19]), "=f"(d[20]), "=f"(d[21]), "=f"(d[22]), "=f"(d[23]),
          "=f"(d[24]), "=f"(d[25]), "=f"(d[26]), "=f"(d[27]), "=f"(d[28]), "=f"(d[29]), "=f"(d[30]), "=f"(d[31])
        : "r"(a0), "r"(a1), "r"(a2), "r"(a3), "l"(descB));
}

__device__ __forceinline__ void wgmma_n24_rs_tb(float (&d)[12], uint32_t a0, uint32_t a1, uint32_t a2, uint32_t a3, uint64_t descB, int scaleD) {
    asm volatile("{\n.reg .pred p;\nsetp.ne.b32 p, %17, 0;\n"
        "wgmma.mma_async.sync.aligned.m64n24k16.f32.bf16.bf16 {"
        "%0, %1, %2, %3, %4, %5, %6, %7, %8, %9, %10, %11}, "
        "{%12, %13, %14, %15}, %16, p, 1, 1, 1;\n}\n"
        : "+f"(d[0]), "+f"(d[1]), "+f"(d[2]), "+f"(d[3]), "+f"(d[4]), "+f"(d[5]), "+f"(d[6]), "+f"(d[7]),
          "+f"(d[8]), "+f"(d[9]), "+f"(d[10]), "+f"(d[11])
        : "r"(a0), "r"(a1), "r"(a2), "r"(a3), "l"(descB), "r"(scaleD));
}

__device__ __forceinline__ void cnt_signal(int idx) {
    asm volatile("fence.acq_rel.gpu;\nred.relaxed.gpu.global.add.u32 [%0], 1;"
                 ::"l"(g_cnt + idx * 32) : "memory");
}
__device__ __forceinline__ void cnt_wait(int idx, uint32_t target) {
    const uint32_t* p = g_cnt + idx * 32;
#pragma unroll 1
    for (uint32_t i = 0; i < (1u << 22); i++) {
        uint32_t v;
        asm volatile("ld.acquire.gpu.global.u32 %0, [%1];" : "=r"(v) : "l"(p) : "memory");
        if ((int32_t)(v - target) >= 0) break;
    }
    asm volatile("fence.proxy.async.global;" ::: "memory");
}
__device__ __forceinline__ void cluster_arrive() { asm volatile("barrier.cluster.arrive.release.aligned;" ::: "memory"); }
__device__ __forceinline__ void cluster_arrive_relaxed() { asm volatile("barrier.cluster.arrive.relaxed.aligned;" ::: "memory"); }
__device__ __forceinline__ void cluster_wait() { asm volatile("barrier.cluster.wait.acquire.aligned;" ::: "memory"); }
__device__ __forceinline__ void bulk_wait_read() { asm volatile("cp.async.bulk.wait_group.read 0;" ::: "memory"); }

__device__ __forceinline__ float gelu_half(float hx) {
    const float u = hx * fmaf(hx * hx, 8.f * 0.035677408136300125f, 2.f * 0.7978845608028654f);
    float t;
    asm("tanh.approx.f32 %0, %1;" : "=f"(t) : "f"(u));
    return fmaf(hx, t, hx);
}
__device__ __forceinline__ void release_stage(uint32_t bar, uint32_t peer, int lane) {
    if (lane == 0) { mbar_arrive(bar); mbar_arrive_cluster(bar, peer); }
}

constexpr int SM_RING = 163840;
constexpr int SM_K = 0, SM_KPAD = IMG_BYTES, SM_M = SM_KPAD + 1024, M_STAGE = 8192 + 20480;
constexpr int SM_V = SM_M + 3 * M_STAGE;
constexpr int SM_MISC = 229376;
static_assert(SM_V >= SM_RING && SM_V + 6 * 6144 <= SM_MISC, "main phase layout");
constexpr int SM_BIAS = SM_MISC, SM_RED = SM_BIAS + 384, SM_BAR = SM_RED + 128;
constexpr int B_A = 0, B_F1 = 10, B_E1 = 14, B_F2 = 18, B_E2 = 23, B_STAT = 28, B_AUX = 29, B_AUX2 = 30, B_ST = 31, B_HS = 32,
              B_DEAD = 33, B_MOK = 35, B_K = 36, B_VF = 52, B_VE = 58, B_MF = 64, B_ME = 67, B_COUNT = 70;
constexpr int SM_EPOCH = SM_BAR + B_COUNT * 8, SM_SAFE = SM_EPOCH + 4;
constexpr int SM_CS = SM_EPOCH + 8;
constexpr int SM_TOTAL = SM_CS + 1728;
static_assert(SM_TOTAL <= 232448, "shared memory budget");

struct Maps { CUtensorMap x, wqkv, w1, h, o, wo, w2; };

__device__ __forceinline__ uint32_t bf2_fma(uint32_t a, uint32_t b, uint32_t c) {
    uint32_t r;
    asm("fma.rn.bf16x2 %0, %1, %2, %3;" : "=r"(r) : "r"(a), "r"(b), "r"(c));
    return r;
}
__device__ __forceinline__ uint32_t lop_and_or(uint32_t a, uint32_t m, uint32_t o) {
    uint32_t r;
    asm("lop3.b32 %0, %1, %2, %3, 0xEA;" : "=r"(r) : "r"(a), "r"(m), "r"(o));
    return r;
}
struct ExpConst { uint32_t mask, slope; };
__device__ __forceinline__ ExpConst make_exp_const() {
    ExpConst k;
    asm volatile("mov.b32 %0, 0x007F007F;" : "=r"(k.mask));
    asm volatile("mov.b32 %0, 0x3EF83EF8;" : "=r"(k.slope));
    return k;
}
__device__ __forceinline__ uint32_t exp2_pair_fma(float t0, float t1, const ExpConst& k) {
    const uint32_t L = __byte_perm(__float_as_uint(t0), __float_as_uint(t1), 0x6521);
    const uint32_t g = lop_and_or(L, k.mask, 0x3F803F80u);
    const uint32_t u = bf2_fma(g, k.slope, 0xBF37BF37u);
    const uint32_t e = bf2_fma(u, u, 0xBD71BD71u);
    return bf2_fma(L, e, L);
}
template <int SHIFT>
__device__ __forceinline__ void exp_tile(const float (&s)[32], uint32_t (&p)[16], const ExpConst& k) {
#pragma unroll
    for (int b = 0; b < 8; b++) {
        if ((EMU_MASK >> (b + SHIFT)) & 1) {
            p[2 * b] = exp2_pair_fma(s[4 * b], s[4 * b + 1], k);
            p[2 * b + 1] = exp2_pair_fma(s[4 * b + 2], s[4 * b + 3], k);
        } else {
            p[2 * b] = pack_bf16(ex2(s[4 * b]), ex2(s[4 * b + 1]));
            p[2 * b + 1] = pack_bf16(ex2(s[4 * b + 2]), ex2(s[4 * b + 3]));
        }
    }
}

struct QFrag { uint32_t q0, q1, q2, q3, q4, q5; };
__device__ __forceinline__ QFrag load_q(int h, int rbase, int g, int c) {
    const uint8_t* gq = g_img + (size_t)h * IMG_BYTES + (rbase >> 3) * 384 + g * 16 + c * 4;
    QFrag q;
    q.q0 = __ldcg((const uint32_t*)(gq)); q.q1 = __ldcg((const uint32_t*)(gq + 384));
    q.q2 = __ldcg((const uint32_t*)(gq + 128)); q.q3 = __ldcg((const uint32_t*)(gq + 512));
    q.q4 = __ldcg((const uint32_t*)(gq + 256)); q.q5 = __ldcg((const uint32_t*)(gq + 640));
    return q;
}
__device__ __forceinline__ void qk_tile(float (&s)[32], const QFrag& q, uint64_t dK) {
    wg_fence();
    wgmma_n64_rs_z(s, q.q0, q.q1, q.q2, q.q3, dK);
    wgmma_n64_rs(s, q.q4, q.q5, 0u, 0u, dK + 16, 1);
    wg_commit();
}
__device__ __forceinline__ void pv_tile(float (&o)[12], const uint32_t (&p)[16], uint64_t dV) {
    wg_fence();
#pragma unroll
    for (int ks = 0; ks < 4; ks++)
        wgmma_n24_rs_tb(o, p[4 * ks], p[4 * ks + 1], p[4 * ks + 2], p[4 * ks + 3], dV + ks * 48, 1);
    wg_commit();
}
__device__ __forceinline__ void store_o(const float (&o)[12], int h, int rbase, int lane) {
    const int g = lane >> 2, c = lane & 3;
    const bool odd = h & 1;
    const int lsrc = (lane & ~3) | (odd ? 0 : 2);
    const float i0 = 1.f / __shfl_sync(~0u, o[8], lsrc), i1 = 1.f / __shfl_sync(~0u, o[10], lsrc);
    __nv_bfloat16* dst = g_o + (size_t)(rbase + g) * DM + h * 20;
    const int d0 = (odd ? 4 : 0) + 2 * c, d1 = d0 + 8, d2 = odd ? 2 * c - 4 : 16 + 2 * c;
    *(uint32_t*)(dst + d0) = pack_bf16(o[0] * i0, o[1] * i0);
    *(uint32_t*)(dst + d1) = pack_bf16(o[4] * i0, o[5] * i0);
    *(uint32_t*)(dst + 8 * DM + d0) = pack_bf16(o[2] * i1, o[3] * i1);
    *(uint32_t*)(dst + 8 * DM + d1) = pack_bf16(o[6] * i1, o[7] * i1);
    if (odd ? (c >= 2) : (c < 2)) {
        *(uint32_t*)(dst + d2) = pack_bf16(o[8] * i0, o[9] * i0);
        *(uint32_t*)(dst + 8 * DM + d2) = pack_bf16(o[10] * i1, o[11] * i1);
    }
}

__device__ __forceinline__ void attn_rows_maxshift(uint32_t sb, uint32_t bar, int h, int rbase, int n0) {
    const int lane = threadIdx.x & 31;
    const QFrag q = load_q(h, rbase, lane >> 2, lane & 3);
    const uint64_t dK0 = make_desc(sb + SM_K, 128, 384, 0), dV0 = make_desc(sb + SM_V, 384, 128, 0);
    float o[12], s[32];
    uint32_t p[16];
#pragma unroll
    for (int i = 0; i < 12; i++) o[i] = 0.f;
    float m0 = -3.0e38f, m1 = -3.0e38f;
#pragma unroll 1
    for (int t = 0; t < 32; t++) {
        const int n = n0 + (t >> 1), slot = n % 6;
        mbar_wait(bar + (B_K + (t >> 1)) * 8, 0);
        mbar_wait(bar + (B_VF + slot) * 8, (n / 6) & 1);
        if ((threadIdx.x >> 5) == 4 && !(t & 1) && n >= 1 && n + 5 < 48) {
            mbar_wait(bar + (B_VE + (n - 1) % 6) * 8, ((n - 1) / 6) & 1);
            if (elect_one()) {
                const uint32_t fb = bar + (B_VF + (n + 5) % 6) * 8;
                mbar_expect_tx(fb, 6144);
                bulk_load(sb + SM_V + ((n + 5) % 6) * 6144, g_img + (size_t)(64 + h) * IMG_BYTES + ((n + 5) & 15) * 6144, 6144, fb);
            }
            __syncwarp();
        }
        qk_tile(s, q, dK0 + t * 192);
        wg_wait<0>();
        fence_regs(s);
        const uint32_t mask = EMU_MASK >> ((t & 1) * 8);
        float n0_ = m0, n1_ = m1;
#pragma unroll
        for (int b = 0; b < 8; b++) {
            const bool emu = (mask >> b) & 1;
            const float f = emu ? 0.5f : 1.f, off = emu ? -383.00390625f : 0.f;
#pragma unroll
            for (int i = 0; i < 4; i++) s[4 * b + i] = fmaf(s[4 * b + i], f, off);
            n0_ = fmaxf(n0_, fmaxf(s[4 * b], s[4 * b + 1]));
            n1_ = fmaxf(n1_, fmaxf(s[4 * b + 2], s[4 * b + 3]));
        }
        n0_ = fmaxf(n0_, __shfl_xor_sync(~0u, n0_, 1)); n0_ = fmaxf(n0_, __shfl_xor_sync(~0u, n0_, 2));
        n1_ = fmaxf(n1_, __shfl_xor_sync(~0u, n1_, 1)); n1_ = fmaxf(n1_, __shfl_xor_sync(~0u, n1_, 2));
        const float c0 = ex2(m0 - n0_), c1 = ex2(m1 - n1_);
        m0 = n0_; m1 = n1_;
#pragma unroll
        for (int b = 0; b < 3; b++) { o[4 * b] *= c0; o[4 * b + 1] *= c0; o[4 * b + 2] *= c1; o[4 * b + 3] *= c1; }
#pragma unroll
        for (int b = 0; b < 8; b++) {
            p[2 * b] = pack_bf16(ex2(s[4 * b] - m0), ex2(s[4 * b + 1] - m0));
            p[2 * b + 1] = pack_bf16(ex2(s[4 * b + 2] - m1), ex2(s[4 * b + 3] - m1));
        }
        pv_tile(o, p, dV0 + slot * 384 + (t & 1) * 192);
        wg_wait<0>();
        fence_regs(o);
        if ((t & 1) && lane == 0) mbar_arrive(bar + (B_VE + slot) * 8);
    }
    store_o(o, h, rbase, lane);
}

__global__ void __launch_bounds__(512, 1) __cluster_dims__(2, 1, 1)
k_fused(const __grid_constant__ Maps tm, const __nv_bfloat16* __restrict__ x, const uint8_t* __restrict__ wqkv,
        const uint8_t* __restrict__ w1, const uint8_t* __restrict__ w2, const uint8_t* __restrict__ wo,
        const __nv_bfloat16* __restrict__ b1, const __nv_bfloat16* __restrict__ b2, __nv_bfloat16* __restrict__ out) {
    extern __shared__ __align__(1024) uint8_t smem[];
    const uint32_t sb = smem_u32(smem);
    const uint32_t bar = sb + SM_BAR;
    const int warp = __shfl_sync(~0u, threadIdx.x >> 5, 0), lane = threadIdx.x & 31;
    const int wgi = warp >> 2, w4 = warp & 3, g = lane >> 2, c = lane & 3;
    const uint32_t rank = blockIdx.x & 1, peer = rank ^ 1;
    const int cl = blockIdx.x >> 1;
    const int cg = cl >> 3, rb = (cl & 7) * 2 + rank;
    const int h = blockIdx.x >> 2, qb = blockIdx.x & 3;
    const int ct = cl & 3, rt = (cl >> 2) * 2 + rank;

    if (threadIdx.x == 0) TL(0, 0);
    if (warp == 15 && lane < 4) prefetch_map(lane == 0 ? &tm.x : lane == 1 ? &tm.wqkv : lane == 2 ? &tm.w1 : &tm.h);
    if (elect_one()) {
#pragma unroll
        for (int j = 0; j < 5; j++) {
            const int i = warp * 5 + j;
            const int cnt = (i >= B_E1 && i < B_F2) || (i >= B_E2 && i < B_STAT) ? 16
                          : i == B_STAT || i == B_ST || i == B_HS || i == B_DEAD || i == B_DEAD + 1 || i >= B_ME ? 8
                          : i == B_AUX ? 4 : i == B_AUX2 ? 3 : i == B_MOK ? 2 : (i >= B_VE && i < B_MF) ? 12 : 1;
            if (i < B_COUNT) mbar_init(bar + i * 8, cnt);
        }
        fence_barrier_init();
    }
    __syncthreads();
    if (threadIdx.x == 0) TL(0, 1);
    cluster_arrive_relaxed();
    cluster_wait();
    if (threadIdx.x == 0) TL(0, 3);

    if (wgi < 2) {
        const uint32_t sB = sb + SM_RING;
        reg_dealloc<56>();
        if (warp == 0) {
#pragma unroll 1
            for (int it = 0; it < 20; it++) {
                const int s = it & 3;
                const int kb = it < 2 ? it : (it & 1) ? (it + 1) >> 1 : 10;
                if (it >= 4) mbar_wait(bar + (B_E1 + s) * 8, ((it >> 2) - 1) & 1);
                if (elect_one()) {
                    if (kb < 10) {
                        mbar_expect_tx(bar + (B_A + kb) * 8, 16384);
                        tma_load(sb + kb * 16384, &tm.x, kb * 64, rb * 128, bar + (B_A + kb) * 8);
                    }
                    const uint32_t dst = sB + s * 16384 + rank * 8192, fb = bar + (B_F1 + s) * 8;
                    const int c0 = cg * 240 + rank * 128;
                    mbar_expect_tx(fb, 16384);
                    tma_load_mc(dst, &tm.wqkv, c0, it * 32, fb, 3);
                    tma_load_mc(dst + 4096, &tm.wqkv, c0 + 64, it * 32, fb, 3);
                }
                __syncwarp();
            }
#pragma unroll 1
            for (int it = 0; it < 20; it++) {
                const int s = it % 5;
                if (it < 5) { if (it != 3) mbar_wait(bar + (B_E1 + (it == 4 ? 3 : it)) * 8, 0); }
                else mbar_wait(bar + (B_E2 + s) * 8, ((it / 5) - 1) & 1);
                if (elect_one()) {
                    const uint32_t dst = sB + s * 12288, fb = bar + (B_F2 + s) * 8;
                    mbar_expect_tx(fb, 12288);
                    if ((it & 1) == (int)rank) {
                        tma_load_mc(dst, &tm.w1, cg * 192, it * 32, fb, 3);
                        tma_load_mc(dst + 4096, &tm.w1, cg * 192 + 64, it * 32, fb, 3);
                    } else {
                        tma_load_mc(dst + 8192, &tm.w1, cg * 192 + 128, it * 32, fb, 3);
                    }
                }
                __syncwarp();
            }
        } else {
            const int ht = threadIdx.x - 32;
            if (ht == 160) *reinterpret_cast<volatile uint32_t*>(smem + SM_EPOCH) = *(volatile uint32_t*)&g_epoch;
            auto slab_sum = [&](const uint32_t* src, int pitch) {
                float s0 = 0.f, s1 = 0.f;
                uint32_t v[40];
#pragma unroll
                for (int k = 0; k < 40; k++) v[k] = __ldg(src + k * pitch);
#pragma unroll
                for (int k = 0; k < 40; k++) { s0 += bf_lo(v[k]); s1 += bf_hi(v[k]); }
                return make_float2(s0, s1);
            };
            if (warp == 7) {
                mbar_wait(bar + B_STAT * 8, 0);
                if (elect_one()) cnt_signal(CNT_ST + rb);
                __syncwarp();
            }
            if (ht < 120) g_csp[rb * 960 + cg * 120 + ht] = slab_sum(reinterpret_cast<const uint32_t*>(wqkv) + rb * 40 * 960 + cg * 120 + ht, 960);
            if (warp != 7) asm volatile("bar.sync 8, 192;" ::: "memory");
            if (warp == 6) { if (elect_one()) cnt_signal(CNT_CS + cg); __syncwarp(); }
            if (warp <= 4) {
                const uint32_t epoch = *reinterpret_cast<volatile uint32_t*>(smem + SM_EPOCH);
                if (lane == 0) { cnt_wait(CNT_CS + cg, (epoch + 1) * 16); cnt_wait(CNT_ST + rb, (epoch + 1) * 8); }
                __syncwarp();
                if (ht < 120) {
                    float s0 = 0.f, s1 = 0.f;
#pragma unroll
                    for (int r = 0; r < 16; r++) {
                        const float2 v = __ldcg(g_csp + r * 960 + cg * 120 + ht);
                        s0 += v.x; s1 += v.y;
                    }
                    reinterpret_cast<float2*>(smem + SM_CS)[ht] = make_float2(s0, s1);
                }
                __syncwarp();
                if (lane == 0) mbar_arrive(bar + B_AUX * 8);
            } else {
                g_csp2[rb * 768 + cg * 96 + (ht - 128)] = slab_sum(reinterpret_cast<const uint32_t*>(w1) + rb * 40 * 768 + cg * 96 + (ht - 128), 768);
                reinterpret_cast<uint32_t*>(smem + SM_BIAS)[ht - 128] =
                    bf2_fma(__ldg(reinterpret_cast<const uint32_t*>(b1 + cg * 192) + (ht - 128)), 0x3F003F00u, 0x80008000u);
                asm volatile("bar.sync 9, 96;" ::: "memory");
                const uint32_t epoch2 = *reinterpret_cast<volatile uint32_t*>(smem + SM_EPOCH);
                if (warp == 5) { if (elect_one()) cnt_signal(CNT_CS2 + cg); __syncwarp(); }
                if (warp == 6 && elect_one()) {
                    prefetch_l2(w2 + blockIdx.x * 15360, 15360);
                    prefetch_l2(wo + blockIdx.x * 6400, 6400);
                    prefetch_map(&tm.o); prefetch_map(&tm.w2); prefetch_map(&tm.wo);
                }
                if (lane == 0) cnt_wait(CNT_CS2 + cg, (epoch2 + 1) * 16);
                __syncwarp();
                float s0 = 0.f, s1 = 0.f;
#pragma unroll
                for (int r = 0; r < 16; r++) {
                    const float2 v = __ldcg(g_csp2 + r * 768 + cg * 96 + (ht - 128));
                    s0 += v.x; s1 += v.y;
                }
                reinterpret_cast<float2*>(smem + SM_CS)[120 + (ht - 128)] = make_float2(s0, s1);
                __syncwarp();
                if (lane == 0) mbar_arrive(bar + B_AUX2 * 8);
            }
            if (warp == 1) {
                mbar_wait(bar + B_HS * 8, 0);
                if (lane == 0) {
                    for (int b = 0; b < 6; b++)
                        tma_store(&tm.h, sb + (7 + b % 3) * 16384 + (b / 3) * 8192, cg * 192 + (b % 3) * 64, rb * 128 + (b / 3) * 64);
                    bulk_commit();
                }
                __syncwarp();
            }
            if (wgi == 1) {
                if (warp == 4) {
                    mbar_wait(bar + B_ST * 8, 0);
                    if (elect_one()) cnt_signal(CNT_QKV + cg);
                    __syncwarp();
                }
                const uint32_t ep = *reinterpret_cast<volatile uint32_t*>(smem + SM_EPOCH);
                if (lane == 0) {
                    cnt_wait(CNT_QKV + h / 12, (ep + 1) * 16);
                    cnt_wait(CNT_QKV + (32 + h) / 12, (ep + 1) * 16);
                    cnt_wait(CNT_QKV + (64 + h) / 12, (ep + 1) * 16);
                }
                __syncwarp();
                if (threadIdx.x == 160) TL(1, 2);
                if (warp == 5) {
                    mbar_wait(bar + B_DEAD * 8, 0);
                    if (lane < 8) *reinterpret_cast<uint4*>(smem + SM_KPAD + lane * 16) = make_uint4(0, 0, 0, 0);
                    fence_proxy_async();
                    __syncwarp();
                    if (elect_one()) {
                        asm volatile("fence.proxy.async.global;" ::: "memory");
                        const uint8_t* gK = g_img + (size_t)(32 + h) * IMG_BYTES;
                        for (int i = 0; i < 16; i++) {
                            mbar_expect_tx(bar + (B_K + i) * 8, 6144);
                            bulk_load(sb + SM_K + i * 6144, gK + i * 6144, 6144, bar + (B_K + i) * 8);
                        }
                    }
                    __syncwarp();
                } else if (warp == 6) {
                    mbar_wait(bar + (B_DEAD + 1) * 8, 0);
                    if (elect_one()) {
                        asm volatile("fence.proxy.async.global;" ::: "memory");
                        const uint8_t* gV = g_img + (size_t)(64 + h) * IMG_BYTES;
                        for (int i = 0; i < 6; i++) {
                            mbar_expect_tx(bar + (B_VF + i) * 8, 6144);
                            bulk_load(sb + SM_V + i * 6144, gV + i * 6144, 6144, bar + (B_VF + i) * 8);
                        }
                    }
                    __syncwarp();
                } else {
                    const int t = (warp == 7 ? 32 : 0) + lane;
                    float kmax = 0.f, qmax = 0.f;
#pragma unroll
                    for (int i = 0; i < 8; i++) {
                        const float4 v = __ldcg(reinterpret_cast<const float4*>(g_nrm + (32 + h) * SEQ) + t + i * 64);
                        kmax = fmaxf(fmaxf(kmax, fmaxf(v.x, v.y)), fmaxf(v.z, v.w));
                    }
#pragma unroll
                    for (int i = 0; i < 2; i++) {
                        const float4 v = __ldcg(reinterpret_cast<const float4*>(g_nrm + h * SEQ + qb * 512) + t + i * 64);
                        qmax = fmaxf(fmaxf(qmax, fmaxf(v.x, v.y)), fmaxf(v.z, v.w));
                    }
#pragma unroll
                    for (int o = 16; o; o >>= 1) {
                        kmax = fmaxf(kmax, __shfl_xor_sync(~0u, kmax, o));
                        qmax = fmaxf(qmax, __shfl_xor_sync(~0u, qmax, o));
                    }
                    float* red = reinterpret_cast<float*>(smem + SM_RED);
                    if (lane == 0 && warp == 7) { red[0] = kmax; red[1] = qmax; }
                    asm volatile("bar.sync 8, 64;" ::: "memory");
                    if (warp == 4 && lane == 0)
                        *reinterpret_cast<volatile uint32_t*>(smem + SM_SAFE) =
                            fmaxf(kmax, red[0]) * fmaxf(qmax, red[1]) * 1.1f <= SAFE_BOUND * SAFE_BOUND;
                }
            }
        }
        asm volatile("bar.sync %0, 128;" ::"r"(wgi + 3) : "memory");
        reg_alloc<128>();
    } else {
        const uint32_t sB = sb + SM_RING;
        reg_alloc<200>();
        const int wi = wgi - 2;
        const int row0 = rb * 128 + wi * 64 + w4 * 16 + g;
        const uint32_t sAw = sb + wi * 8192;
        const int rbk = row0 >> 3, hs0 = cg * 12;
        {
            const int srow = rb * 128 + cg * 16 + (warp - 8) * 2 + (lane >> 4);
            uint4 xv[5];
#pragma unroll
            for (int i = 0; i < 5; i++) xv[i] = __ldg(reinterpret_cast<const uint4*>(x + (size_t)srow * DM) + (lane & 15) + 16 * i);
            float sm = 0.f;
#pragma unroll
            for (int i = 0; i < 5; i++)
                sm += ((bf_lo(xv[i].x) + bf_hi(xv[i].x)) + (bf_lo(xv[i].y) + bf_hi(xv[i].y))) +
                      ((bf_lo(xv[i].z) + bf_hi(xv[i].z)) + (bf_lo(xv[i].w) + bf_hi(xv[i].w)));
#pragma unroll
            for (int o = 8; o; o >>= 1) sm += __shfl_xor_sync(~0u, sm, o);
            const float mu = sm * (1.f / DM);
            float q0 = 0.f, q1 = 0.f;
#pragma unroll
            for (int i = 0; i < 5; i++) {
                const uint32_t w[4] = {xv[i].x, xv[i].y, xv[i].z, xv[i].w};
#pragma unroll
                for (int j = 0; j < 4; j++) {
                    const float d0 = bf_lo(w[j]) - mu, d1 = bf_hi(w[j]) - mu;
                    q0 = fmaf(d0, d0, q0); q1 = fmaf(d1, d1, q1);
                }
            }
            float q = q0 + q1;
#pragma unroll
            for (int o = 8; o; o >>= 1) q += __shfl_xor_sync(~0u, q, o);
            const float var = q * (1.f / DM);
            const float r1 = rsqrtf(var + LN_EPS);
            const float r2 = rsqrtf(var * r1 * r1 + LN_EPS);
            if ((lane & 15) == 0) g_stat[srow] = make_float4(mu, r1, r1 * r2, 0.f);
            __syncwarp();
            if (lane == 0) mbar_arrive(bar + B_STAT * 8);
        }
        {
            float accA[100], accB[20];
            const uint64_t dA0 = make_desc(sAw, 16, 1024, 1), dB0 = make_desc(sB, 4096, 1024, 1);
#pragma unroll 2
            for (int it = 0; it < 20; it++) {
                const int s = it & 3;
                if (!(it & 1)) mbar_wait(bar + (B_A + (it >> 1)) * 8, 0);
                if (threadIdx.x == 256 && it == 0) TL(0, 2);
                mbar_wait(bar + (B_F1 + s) * 8, (it >> 2) & 1);
                const uint64_t dA = dA0 + (it >> 1) * 1024 + (it & 1) * 4, dB = dB0 + s * 1024;
                wg_fence();
                wgmma_n40_ss_tb(accB, dA, dB + 769, it > 0);
                wgmma_n40_ss_tb(accB, dA + 2, dB + 769 + 128, 1);
                wgmma_n200_ss_tb(accA, dA, dB, it > 0);
                wgmma_n200_ss_tb(accA, dA + 2, dB + 128, 1);
                wg_commit();
                if (it > 0) { wg_wait<1>(); release_stage(bar + (B_E1 + ((it - 1) & 3)) * 8, peer, lane); }
            }
            mbar_wait(bar + B_AUX * 8, 0);
            const float4 st0 = __ldcg(g_stat + row0), st1 = __ldcg(g_stat + row0 + 8);
            wg_wait<0>();
            release_stage(bar + (B_E1 + 3) * 8, peer, lane);
            fence_regs(accA);
            fence_regs(accB);
            if (threadIdx.x == 256) TL(1, 1);
            const float2* cs = reinterpret_cast<const float2*>(smem + SM_CS) + c;
            uint8_t* img = g_img + (size_t)hs0 * IMG_BYTES + rbk * 384 + g * 16 + c * 4;
            const bool emu0 = (EMU_MASK >> (rbk & 15)) & 1, emu1 = (EMU_MASK >> ((rbk + 1) & 15)) & 1;
            const bool low = c < 2;
            uint32_t pk[60];
#pragma unroll
            for (int m = 0; m < 6; m++) {
                const int which = (hs0 + 2 * m) >> 5;
                const float m0 = st0.y * (which == 0 ? QSCALE : (which == 1 && emu0) ? 2.f : 1.f);
                const float m1 = st1.y * (which == 0 ? QSCALE : (which == 1 && emu1) ? 2.f : 1.f);
                const float d0 = -st0.x * m0, d1 = -st1.x * m1;
                const float* a = m < 5 ? &accA[20 * m] : accB;
#pragma unroll
                for (int b = 0; b < 5; b++) {
                    const float2 cv = cs[(5 * m + b) * 4];
                    pk[10 * m + 2 * b] = pack_bf16(fmaf(a[4 * b], m0, d0 * cv.x), fmaf(a[4 * b + 1], m0, d0 * cv.y));
                    pk[10 * m + 2 * b + 1] = pack_bf16(fmaf(a[4 * b + 2], m1, d1 * cv.x), fmaf(a[4 * b + 3], m1, d1 * cv.y));
                }
            }
            const float r20 = 0.5f * st0.z, r21 = 0.5f * st1.z, e20 = -st0.x * r20, e21 = -st1.x * r21;
            float acc2[96];
#pragma unroll
            for (int it = 0; it < 20; it++) {
                const int s = it % 5;
                mbar_wait(bar + (B_F2 + s) * 8, (it / 5) & 1);
                wg_fence();
                const uint64_t dA = make_desc(sAw + (it >> 1) * 16384 + (it & 1) * 64, 16, 1024, 1);
                const uint64_t dB = make_desc(sB + s * 12288, 4096, 1024, 1);
                if (it == 0) wgmma_n192_ss_tb_z(acc2, dA, dB); else wgmma_n192_ss_tb(acc2, dA, dB, 1);
                wgmma_n192_ss_tb(acc2, dA + 2, dB + 128, 1);
                wg_commit();
                if (it > 0) {
                    wg_wait<1>();
                    if (it <= 15) release_stage(bar + (B_E2 + (it - 1) % 5) * 8, peer, lane);
                    if (it == 14 && lane == 0) mbar_arrive(bar + B_DEAD * 8);
                }
                if (it < 6) {
                    const int m = it;
                    const int hs = hs0 + 2 * m, which = hs >> 5;
                    const uint32_t* a = pk + 10 * m;
                    uint8_t* pe = img + (2 * m) * IMG_BYTES;
                    uint8_t* po = pe + IMG_BYTES;
                    const uint32_t padv = which == 0 ? 0x3F803F80u : which == 1 ? 0xBFFF4440u : 0x00003F80u;
                    const uint32_t p0 = ((c & 1) || (which == 1 && !emu0)) ? 0u : padv;
                    const uint32_t p1 = ((c & 1) || (which == 1 && !emu1)) ? 0u : padv;
                    *(uint32_t*)(pe) = a[0];
                    *(uint32_t*)(pe + 128) = a[2];
                    *(uint32_t*)(pe + 256) = low ? a[4] : p0;
                    *(uint32_t*)(pe + 384) = a[1];
                    *(uint32_t*)(pe + 512) = a[3];
                    *(uint32_t*)(pe + 640) = low ? a[5] : p1;
                    *(uint32_t*)(po) = a[6];
                    *(uint32_t*)(po + 128) = a[8];
                    *(uint32_t*)(po + 256) = low ? p0 : a[4];
                    *(uint32_t*)(po + 384) = a[7];
                    *(uint32_t*)(po + 512) = a[9];
                    *(uint32_t*)(po + 640) = low ? p1 : a[5];
                    if (which < 2) {
                        const uint32_t u0 = bf2_fma(a[4], a[4], 0u), u1 = bf2_fma(a[5], a[5], 0u);
                        const uint32_t pe0 = bf2_fma(a[0], a[0], bf2_fma(a[2], a[2], low ? u0 : 0u));
                        const uint32_t pe1 = bf2_fma(a[1], a[1], bf2_fma(a[3], a[3], low ? u1 : 0u));
                        const uint32_t po0 = bf2_fma(a[6], a[6], bf2_fma(a[8], a[8], low ? 0u : u0));
                        const uint32_t po1 = bf2_fma(a[7], a[7], bf2_fma(a[9], a[9], low ? 0u : u1));
                        const float e0 = bf_lo(pe0) + bf_hi(pe0), e1 = bf_lo(pe1) + bf_hi(pe1);
                        const float o0 = bf_lo(po0) + bf_hi(po0), o1 = bf_lo(po1) + bf_hi(po1);
                        const bool b0 = c & 1, b1_ = c & 2;
                        const float x0 = (b0 ? e1 : e0) + __shfl_xor_sync(~0u, b0 ? e0 : e1, 1);
                        const float x1 = (b0 ? o1 : o0) + __shfl_xor_sync(~0u, b0 ? o0 : o1, 1);
                        float y = (b1_ ? x1 : x0) + __shfl_xor_sync(~0u, b1_ ? x0 : x1, 2);
                        if (which == 1 && (b0 ? emu1 : emu0)) y *= 0.25f;
                        g_nrm[(hs + (c >> 1)) * SEQ + row0 + (c & 1) * 8] = y;
                    }
                    if (it == 5) { __syncwarp(); if (lane == 0) mbar_arrive(bar + B_ST * 8); }
                }
            }
            wg_wait<0>();
            fence_regs(acc2);
            if (lane == 0) mbar_arrive(bar + (B_DEAD + 1) * 8);
            mbar_wait(bar + B_AUX2 * 8, 0);
            const uint32_t* bias = reinterpret_cast<const uint32_t*>(smem + SM_BIAS) + c;
            const int mrow = w4 * 16 + (lane & 15);
            const uint32_t stage = sAw + 7 * 16384;
            const uint32_t st_row = stage + mrow * 128;
#pragma unroll
            for (int j = 0; j < 24; j += 2) {
                const uint32_t bA = bias[j * 4], bB = bias[j * 4 + 4];
                const float2 cA = cs[(30 + j) * 4], cB = cs[(31 + j) * 4];
                const float* a = acc2 + j * 4;
                const uint32_t r00 = pack_bf16(gelu_half(fmaf(a[0], r20, fmaf(e20, cA.x, bf_lo(bA)))), gelu_half(fmaf(a[1], r20, fmaf(e20, cA.y, bf_hi(bA)))));
                const uint32_t r10 = pack_bf16(gelu_half(fmaf(a[2], r21, fmaf(e21, cA.x, bf_lo(bA)))), gelu_half(fmaf(a[3], r21, fmaf(e21, cA.y, bf_hi(bA)))));
                const uint32_t r01 = pack_bf16(gelu_half(fmaf(a[4], r20, fmaf(e20, cB.x, bf_lo(bB)))), gelu_half(fmaf(a[5], r20, fmaf(e20, cB.y, bf_hi(bB)))));
                const uint32_t r11 = pack_bf16(gelu_half(fmaf(a[6], r21, fmaf(e21, cB.x, bf_lo(bB)))), gelu_half(fmaf(a[7], r21, fmaf(e21, cB.y, bf_hi(bB)))));
                const int chunk = (j & 7) + (lane >> 4);
                stmatrix_x4(st_row + (j >> 3) * 16384 + ((chunk ^ (mrow & 7)) << 4), r00, r10, r01, r11);
            }
            fence_proxy_async();
            __syncwarp();
            if (lane == 0) mbar_arrive(bar + B_HS * 8);
            asm volatile("bar.sync %0, 128;" ::"r"(wgi + 3) : "memory");
            reg_dealloc<128>();
            if (threadIdx.x == 256) TL(1, 3);
        }
    }

    float* stg = reinterpret_cast<float*>(smem + SM_M);
    if (wgi == 0) {
        const uint32_t epoch = *reinterpret_cast<volatile uint32_t*>(smem + SM_EPOCH);
        if (warp == 1) {
            if (lane == 0) {
                bulk_wait_read();
                mbar_arrive(bar + B_MOK * 8);
                mbar_arrive_cluster(bar + B_MOK * 8, peer);
                bulk_wait_all();
                cnt_signal(CNT_H + rb);
            }
            __syncwarp();
        }
        auto issue = [&](int n, int slot) {
            const uint32_t dst = sb + SM_M + slot * M_STAGE, fb = bar + (B_MF + slot) * 8;
            const bool fc2 = n < 24;
            const int k0 = (fc2 ? n : n - 24) * 64;
            if (n == 24) cnt_wait(CNT_O + (rt >> 3), (epoch + 1) * 32);
            mbar_expect_tx(fb, M_STAGE);
            tma_load(dst, fc2 ? &tm.h : &tm.o, k0, rt * 64, fb);
            const CUtensorMap* mB = fc2 ? &tm.w2 : &tm.wo;
            if ((n & 1) == (int)rank) {
                tma_load_mc(dst + 8192, mB, ct * 160, k0, fb, 3);
                tma_load_mc(dst + 8192 + 4096, mB, ct * 160 + 32, k0, fb, 3);
                tma_load_mc(dst + 8192 + 8192, mB, ct * 160 + 64, k0, fb, 3);
            } else {
                tma_load_mc(dst + 8192 + 12288, mB, ct * 160 + 96, k0, fb, 3);
                tma_load_mc(dst + 8192 + 16384, mB, ct * 160 + 128, k0, fb, 3);
            }
        };
        if (warp == 0) {
            mbar_wait(bar + B_MOK * 8, 0);
            if (elect_one()) {
                cnt_wait(CNT_H + (rt >> 1), (epoch + 1) * 8);
                issue(0, 0); issue(1, 1); issue(2, 2);
            }
            __syncwarp();
        }
        if (threadIdx.x == 0) TL(3, 0);
        {
            float acc[80];
            const uint64_t dA0 = make_desc(sb + SM_M, 16, 1024, 1), dB0 = make_desc(sb + SM_M + 8192, 4096, 512, 2);
            int slot = 0, prev = 2;
            uint32_t ph = 0, pph = 1;
#pragma unroll 1
            for (int n = 0; n < 34; n++) {
                mbar_wait(bar + (B_MF + slot) * 8, ph);
                const uint64_t dA = dA0 + slot * (M_STAGE / 16), dB = dB0 + slot * (M_STAGE / 16);
                wg_fence();
#pragma unroll
                for (int kk = 0; kk < 4; kk++) wgmma_n160_ss_tb(acc, dA + kk * 2, dB + kk * 64, n > 0 || kk > 0);
                wg_commit();
                if (n > 0) {
                    wg_wait<1>();
                    if (n + 2 < 34) {
                        release_stage(bar + (B_ME + prev) * 8, peer, lane);
                        if (warp == 0) {
                            mbar_wait(bar + (B_ME + prev) * 8, pph);
                            if (elect_one()) issue(n + 2, prev);
                            __syncwarp();
                        }
                    }
                }
                if (n == 23 && threadIdx.x == 0) TL(3, 2);
                if (n == 0 && threadIdx.x == 0) TL(3, 1);
                prev = slot; pph = ph;
                if (++slot == 3) { slot = 0; ph ^= 1; }
            }
            wg_wait<0>();
            fence_regs(acc);
            const int r = w4 * 16 + g;
#pragma unroll
            for (int j = 0; j < 20; j++) {
                *reinterpret_cast<float2*>(stg + r * 168 + j * 8 + 2 * c) = make_float2(acc[4 * j], acc[4 * j + 1]);
                *reinterpret_cast<float2*>(stg + (r + 8) * 168 + j * 8 + 2 * c) = make_float2(acc[4 * j + 2], acc[4 * j + 3]);
            }
        }
        if (blockIdx.x == 0 && threadIdx.x == 0x0) g_epoch = epoch + 1;
        __syncthreads();
    } else {
        asm volatile("bar.sync 7, 384;" ::: "memory");
        const bool safe = __all_sync(~0u, *reinterpret_cast<volatile uint32_t*>(smem + SM_SAFE) != 0);
        if (threadIdx.x == 128) TL(2, 0);
        const int aw = wgi - 1, ntile = aw < 2 ? 3 : 2;
        if (!safe) {
#pragma unroll 1
            for (int pass = 0; pass < ntile; pass++)
                attn_rows_maxshift(sb, bar, h, qb * 512 + (aw + 3 * pass) * 64 + w4 * 16, pass * 16);
        } else {
            const ExpConst kc = make_exp_const();
            const uint64_t dK0 = make_desc(sb + SM_K, 128, 384, 0), dV0 = make_desc(sb + SM_V, 384, 128, 0);
            uint32_t slot = 0, ph = 0;
#pragma unroll 1
            for (int pass = 0; pass < ntile; pass++) {
                const int rbase = qb * 512 + (aw + 3 * pass) * 64 + w4 * 16;
                const QFrag q = load_q(h, rbase, g, c);
                float o[12], sa[32], sc[32];
                uint32_t p[16];
#pragma unroll
                for (int i = 0; i < 12; i++) o[i] = 0.f;
                fence_regs(o);
                mbar_wait(bar + B_K * 8, 0);
                qk_tile(sa, q, dK0);
                wg_wait<0>();
                fence_regs(sa);
                uint64_t dK = dK0;
                uint32_t bk = bar + (B_K + 1) * 8;
#pragma unroll 1
                for (int j = 0; j < 16; j++) {
                    mbar_wait(bar + (B_VF + slot) * 8, ph);
                    qk_tile(sc, q, dK + 192);
                    wg_wait<1>();
                    const uint32_t prev = slot == 0 ? 5 : slot - 1;
                    if (j > 0 && lane == 0) mbar_arrive(bar + (B_VE + prev) * 8);
                    const uint64_t dV = dV0 + slot * 384;
                    exp_tile<0>(sa, p, kc);
                    pv_tile(o, p, dV);
                    wg_wait<1>();
                    fence_regs(sc);
                    if (j < 15) mbar_wait(bk, 0);
                    if (warp == 4) {
                        const int n = pass * 16 + j;
                        if (n >= 2 && n + 4 < 48) {
                            const uint32_t old = (n - 2) % 6;
                            mbar_wait(bar + (B_VE + old) * 8, ((n - 2) / 6) & 1);
                            if (elect_one()) {
                                mbar_expect_tx(bar + (B_VF + old) * 8, 6144);
                                bulk_load(sb + SM_V + old * 6144, g_img + (size_t)(64 + h) * IMG_BYTES + ((n + 4) & 15) * 6144, 6144,
                                          bar + (B_VF + old) * 8);
                            }
                            __syncwarp();
                        }
                    }
                    qk_tile(sa, q, dK + 384);
                    wg_wait<1>();
                    exp_tile<8>(sc, p, kc);
                    pv_tile(o, p, dV + 192);
                    wg_wait<1>();
                    fence_regs(sa);
                    dK += 384; bk += 8;
                    if (++slot == 6) { slot = 0; ph ^= 1; }
                }
                wg_wait<0>();
                fence_regs(o);
                if (lane == 0) mbar_arrive(bar + (B_VE + (slot == 0 ? 5 : slot - 1)) * 8);
                store_o(o, h, rbase, lane);
                if (threadIdx.x == 128 && pass != 1) TL(2, 1 + (pass >> 1));
            }
        }
        if (aw == 2) {
            for (int n = 32; n < 48; n++) {
                mbar_wait(bar + (B_VF + n % 6) * 8, (n / 6) & 1);
                if (lane == 0) mbar_arrive(bar + (B_VE + n % 6) * 8);
            }
        }
        asm volatile("bar.sync 7, 384;" ::: "memory");
        if (threadIdx.x == 192) cnt_signal(CNT_O + qb);
        if (threadIdx.x == 128) TL(2, 3);
        const int ot = threadIdx.x - 128, orow = ot / 5, oseg = ot % 5;
        const size_t ooff = (size_t)(rt * 64 + orow) * DM + ct * 160 + oseg * 32;
        uint4 xr[4], br[4];
        if (ot < 320) {
#pragma unroll
            for (int i = 0; i < 4; i++) {
                asm volatile("ld.global.nc.v4.u32 {%0, %1, %2, %3}, [%4];" : "=r"(xr[i].x), "=r"(xr[i].y), "=r"(xr[i].z), "=r"(xr[i].w)
                             : "l"(reinterpret_cast<const uint4*>(x + ooff) + i));
                asm volatile("ld.global.nc.v4.u32 {%0, %1, %2, %3}, [%4];" : "=r"(br[i].x), "=r"(br[i].y), "=r"(br[i].z), "=r"(br[i].w)
                             : "l"(reinterpret_cast<const uint4*>(b2 + ct * 160 + oseg * 32) + i));
            }
        }
        __syncthreads();
        if (ot < 320) {
            const float4* sp = reinterpret_cast<const float4*>(stg + orow * 168 + oseg * 32);
#pragma unroll
            for (int i = 0; i < 4; i++) {
                const float4 a = sp[2 * i], b = sp[2 * i + 1];
                uint4 w;
                w.x = pack_bf16(a.x + bf_lo(br[i].x) + bf_lo(xr[i].x), a.y + bf_hi(br[i].x) + bf_hi(xr[i].x));
                w.y = pack_bf16(a.z + bf_lo(br[i].y) + bf_lo(xr[i].y), a.w + bf_hi(br[i].y) + bf_hi(xr[i].y));
                w.z = pack_bf16(b.x + bf_lo(br[i].z) + bf_lo(xr[i].z), b.y + bf_hi(br[i].z) + bf_hi(xr[i].z));
                w.w = pack_bf16(b.z + bf_lo(br[i].w) + bf_lo(xr[i].w), b.w + bf_hi(br[i].w) + bf_hi(xr[i].w));
                reinterpret_cast<uint4*>(out + ooff)[i] = w;
            }
        }
        if (threadIdx.x == 128) TL(3, 3);
    }
    cluster_arrive_relaxed();
    cluster_wait();
}

typedef CUresult (*EncodeTiledFn)(CUtensorMap*, CUtensorMapDataType, cuuint32_t, void*, const cuuint64_t*,
                                  const cuuint64_t*, const cuuint32_t*, const cuuint32_t*, CUtensorMapInterleave,
                                  CUtensorMapSwizzle, CUtensorMapL2promotion, CUtensorMapFloatOOBfill);

CUtensorMap make_map(EncodeTiledFn enc, const void* ptr, int rows, int cols, int box_rows, int box_cols,
                     CUtensorMapSwizzle swz) {
    CUtensorMap m;
    cuuint64_t gd[2] = {(cuuint64_t)cols, (cuuint64_t)rows};
    cuuint64_t gs[1] = {(cuuint64_t)cols * 2};
    cuuint32_t bd[2] = {(cuuint32_t)box_cols, (cuuint32_t)box_rows};
    cuuint32_t es[2] = {1, 1};
    enc(&m, CU_TENSOR_MAP_DATA_TYPE_BFLOAT16, 2, const_cast<void*>(ptr), gd, gs, bd, es, CU_TENSOR_MAP_INTERLEAVE_NONE,
        swz, CU_TENSOR_MAP_L2_PROMOTION_L2_128B, CU_TENSOR_MAP_FLOAT_OOB_FILL_NONE);
    return m;
}

}

extern "C" void kernel_launch(void* const* d_in, const int* in_sizes, int n_in, void* d_out, int out_size) {
    (void)in_sizes; (void)n_in; (void)out_size;
    const __nv_bfloat16* x = (const __nv_bfloat16*)d_in[0];
    const __nv_bfloat16* wqkv = (const __nv_bfloat16*)d_in[1];
    const __nv_bfloat16* wo = (const __nv_bfloat16*)d_in[2];
    const __nv_bfloat16* w1 = (const __nv_bfloat16*)d_in[4];
    const __nv_bfloat16* b1 = (const __nv_bfloat16*)d_in[5];
    const __nv_bfloat16* w2 = (const __nv_bfloat16*)d_in[6];
    const __nv_bfloat16* b2 = (const __nv_bfloat16*)d_in[7];
    __nv_bfloat16* out = (__nv_bfloat16*)d_out;

    static EncodeTiledFn enc = nullptr;
    static void *p_h, *p_o;
    if (!enc) {
        cudaDriverEntryPointQueryResult qr;
        cudaGetDriverEntryPoint("cuTensorMapEncodeTiled", (void**)&enc, cudaEnableDefault, &qr);
        cudaGetSymbolAddress(&p_h, g_h);
        cudaGetSymbolAddress(&p_o, g_o);
        cudaFuncSetAttribute(k_fused, cudaFuncAttributeMaxDynamicSharedMemorySize, SM_TOTAL);
    }
    Maps tm;
    tm.x = make_map(enc, x, SEQ, DM, 128, 64, CU_TENSOR_MAP_SWIZZLE_128B);
    tm.wqkv = make_map(enc, wqkv, DM, 3 * DM, 32, 64, CU_TENSOR_MAP_SWIZZLE_128B);
    tm.w1 = make_map(enc, w1, DM, FF, 32, 64, CU_TENSOR_MAP_SWIZZLE_128B);
    tm.h = make_map(enc, p_h, SEQ, FF, 64, 64, CU_TENSOR_MAP_SWIZZLE_128B);
    tm.o = make_map(enc, p_o, SEQ, DM, 64, 64, CU_TENSOR_MAP_SWIZZLE_128B);
    tm.wo = make_map(enc, wo, DM, DM, 64, 32, CU_TENSOR_MAP_SWIZZLE_64B);
    tm.w2 = make_map(enc, w2, FF, DM, 64, 32, CU_TENSOR_MAP_SWIZZLE_64B);
    k_fused<<<128, 512, SM_TOTAL, cudaStreamPerThread>>>(tm, x, (const uint8_t*)wqkv, (const uint8_t*)w1, (const uint8_t*)w2,
                                                         (const uint8_t*)wo, b1, b2, out);
}
```

```cpp
#include <cuda_runtime.h>
#include <cuda_bf16.h>
#include <cuda.h>
#include <stdint.h>

namespace {

constexpr int SEQ = 2048, DM = 640, FF = 1536;
constexpr float LN_EPS = 1e-5f;

constexpr int IMG_BYTES = 256 * 384;
constexpr uint32_t EMU_MASK = 0xD5D5u;
constexpr float SAFE_BOUND = 80.0f;
#define XV_IT 1
#define PACE_NS 200
constexpr float QSCALE = 0.22360679774997896f * 1.4426950408889634f;

__device__ float4 g_stat[SEQ];
__device__ float2 g_csp[16 * 1728];
__device__ __align__(1024) uint8_t g_img[96 * IMG_BYTES + 1024];
__device__ float g_nrm[64 * SEQ];
__device__ __align__(1024) __nv_bfloat16 g_h[SEQ * FF];
__device__ __align__(1024) __nv_bfloat16 g_o[SEQ * DM];
constexpr int CNT_ST = 0, CNT_QKV = 16, CNT_H = 24, CNT_O = 40, CNT_CS = 44, CNT_CS2 = 52;
__device__ uint32_t g_cnt[60 * 32];
__device__ uint32_t g_epoch;

#define TL(kern, slot) do { } while (0)
#define IT(row, i) do { } while (0)

__device__ __forceinline__ uint32_t smem_u32(const void* p) { return (uint32_t)__cvta_generic_to_shared(p); }
__device__ __forceinline__ void mbar_init(uint32_t bar, int cnt) {
    asm volatile("mbarrier.init.shared::cta.b64 [%0], %1;" ::"r"(bar), "r"(cnt));
}
__device__ __forceinline__ void mbar_expect_tx(uint32_t bar, uint32_t bytes) {
    asm volatile("mbarrier.arrive.expect_tx.shared::cta.b64 _, [%0], %1;" ::"r"(bar), "r"(bytes) : "memory");
}
__device__ __forceinline__ void mbar_wait(uint32_t bar, uint32_t parity) {
    asm volatile("{\n.reg .pred p;\n.reg .u32 n;\nmov.u32 n, 0;\n"
                 "WAIT_LOOP:\nmbarrier.try_wait.parity.shared::cta.b64 p, [%0], %1;\n@p bra WAIT_DONE;\n"
                 "add.u32 n, n, 1;\nsetp.lt.u32 p, n, 4194304;\n@p bra WAIT_LOOP;\nWAIT_DONE:\n}"
                 ::"r"(bar), "r"(parity) : "memory");
}
__device__ __forceinline__ void mbar_arrive(uint32_t bar) {
    asm volatile("mbarrier.arrive.shared::cta.b64 _, [%0];" ::"r"(bar) : "memory");
}
__device__ __forceinline__ void mbar_arrive_cluster(uint32_t bar, uint32_t cta) {
    asm volatile("{\n.reg .b32 ra;\nmapa.shared::cluster.u32 ra, %0, %1;\n"
                 "mbarrier.arrive.shared::cluster.b64 _, [ra];\n}" ::"r"(bar), "r"(cta) : "memory");
}
__device__ __forceinline__ void fence_barrier_init() { asm volatile("fence.mbarrier_init.release.cluster;" ::: "memory"); }
__device__ __forceinline__ void fence_proxy_async() { asm volatile("fence.proxy.async.shared::cta;" ::: "memory"); }
__device__ __forceinline__ void cluster_sync() {
    asm volatile("barrier.cluster.arrive.release.aligned;\nbarrier.cluster.wait.acquire.aligned;" ::: "memory");
}
__device__ __forceinline__ bool elect_one() {
    uint32_t pred;
    asm volatile("{\n.reg .pred p;\nelect.sync _|p, 0xFFFFFFFF;\nselp.b32 %0, 1, 0, p;\n}" : "=r"(pred));
    return pred != 0;
}
__device__ __forceinline__ void pdl_launch() { asm volatile("griddepcontrol.launch_dependents;" ::: "memory"); }
__device__ __forceinline__ void pdl_wait() { asm volatile("griddepcontrol.wait;" ::: "memory"); }
__device__ __forceinline__ void prefetch_map(const CUtensorMap* m) {
    asm volatile("prefetch.tensormap [%0];" ::"l"(m) : "memory");
}
__device__ __forceinline__ void tma_load(uint32_t dst, const CUtensorMap* m, int c0, int c1, uint32_t bar) {
    asm volatile("cp.async.bulk.tensor.2d.shared::cluster.global.mbarrier::complete_tx::bytes [%0], [%1, {%3, %4}], [%2];"
                 ::"r"(dst), "l"(m), "r"(bar), "r"(c0), "r"(c1) : "memory");
}
__device__ __forceinline__ void tma_load_mc(uint32_t dst, const CUtensorMap* m, int c0, int c1, uint32_t bar, uint16_t mask) {
    asm volatile("cp.async.bulk.tensor.2d.shared::cluster.global.mbarrier::complete_tx::bytes.multicast::cluster"
                 " [%0], [%1, {%3, %4}], [%2], %5;"
                 ::"r"(dst), "l"(m), "r"(bar), "r"(c0), "r"(c1), "h"(mask) : "memory");
}
__device__ __forceinline__ void tma_store(const CUtensorMap* m, uint32_t src, int c0, int c1) {
    asm volatile("cp.async.bulk.tensor.2d.global.shared::cta.bulk_group [%0, {%2, %3}], [%1];"
                 ::"l"(m), "r"(src), "r"(c0), "r"(c1) : "memory");
}
__device__ __forceinline__ void bulk_commit() { asm volatile("cp.async.bulk.commit_group;" ::: "memory"); }
__device__ __forceinline__ void bulk_wait_all() { asm volatile("cp.async.bulk.wait_group 0;" ::: "memory"); }
__device__ __forceinline__ void bulk_load(uint32_t dst, const void* src, uint32_t bytes, uint32_t bar) {
    asm volatile("cp.async.bulk.shared::cluster.global.mbarrier::complete_tx::bytes [%0], [%1], %2, [%3];"
                 ::"r"(dst), "l"(src), "r"(bytes), "r"(bar) : "memory");
}
__device__ __forceinline__ void prefetch_l2(const void* p, uint32_t bytes) {
    asm volatile("cp.async.bulk.prefetch.L2.global [%0], %1;" ::"l"(p), "r"(bytes) : "memory");
}
__device__ __forceinline__ void tma_prefetch_l2(const CUtensorMap* m, int c0, int c1) {
    asm volatile("cp.async.bulk.prefetch.tensor.2d.L2.global.tile [%0, {%1, %2}];" ::"l"(m), "r"(c0), "r"(c1) : "memory");
}
__device__ __forceinline__ void wg_fence() { asm volatile("wgmma.fence.sync.aligned;" ::: "memory"); }
__device__ __forceinline__ void wg_commit() { asm volatile("wgmma.commit_group.sync.aligned;" ::: "memory"); }
template <int N> __device__ __forceinline__ void wg_wait() {
    asm volatile("wgmma.wait_group.sync.aligned %0;" ::"n"(N) : "memory");
}
template <int N> __device__ __forceinline__ void reg_alloc() { asm volatile("setmaxnreg.inc.sync.aligned.u32 %0;" ::"n"(N)); }
template <int N> __device__ __forceinline__ void reg_dealloc() { asm volatile("setmaxnreg.dec.sync.aligned.u32 %0;" ::"n"(N)); }
template <int N> __device__ __forceinline__ void fence_regs(float (&d)[N]) {
#pragma unroll
    for (int i = 0; i < N; i++) asm volatile("" : "+f"(d[i])::"memory");
}
__device__ __forceinline__ uint64_t make_desc(uint32_t addr, uint32_t lbo, uint32_t sbo, uint32_t swz) {
    return (uint64_t)((addr & 0x3FFFF) >> 4) | ((uint64_t)(lbo >> 4) << 16) | ((uint64_t)(sbo >> 4) << 32) |
           ((uint64_t)swz << 62);
}
__device__ __forceinline__ uint32_t pack_bf16(float lo, float hi) {
    uint32_t r;
    asm("cvt.rn.bf16x2.f32 %0, %1, %2;" : "=r"(r) : "f"(hi), "f"(lo));
    return r;
}
__device__ __forceinline__ float ex2(float x) {
    float r;
    asm("ex2.approx.ftz.f32 %0, %1;" : "=f"(r) : "f"(x));
    return r;
}
__device__ __forceinline__ float bf_lo(uint32_t v) { return __uint_as_float(v << 16); }
__device__ __forceinline__ float bf_hi(uint32_t v) { return __uint_as_float(v & 0xFFFF0000u); }
__device__ __forceinline__ void stmatrix_x4(uint32_t addr, uint32_t r0, uint32_t r1, uint32_t r2, uint32_t r3) {
    asm volatile("stmatrix.sync.aligned.m8n8.x4.shared.b16 [%0], {%1, %2, %3, %4};"
                 ::"r"(addr), "r"(r0), "r"(r1), "r"(r2), "r"(r3) : "memory");
}

__device__ __forceinline__ void wgmma_n200_ss_tb(float (&d)[100], uint64_t descA, uint64_t descB, int scaleD) {
    asm volatile("{\n.reg .pred p;\nsetp.ne.b32 p, %102, 0;\n"
        "wgmma.mma_async.sync.aligned.m64n200k16.f32.bf16.bf16 {"
        "%0, %1, %2, %3, %4, %5, %6, %7, %8, %9, %10, %11, %12, %13, %14, %15, "
        "%16, %17, %18, %19, %20, %21, %22, %23, %24, %25, %26, %27, %28, %29, %30, %31, "
        "%32, %33, %34, %35, %36, %37, %38, %39, %40, %41, %42, %43, %44, %45, %46, %47, "
        "%48, %49, %50, %51, %52, %53, %54, %55, %56, %57, %58, %59, %60, %61, %62, %63, "
        "%64, %65, %66, %67, %68, %69, %70, %71, %72, %73, %74, %75, %76, %77, %78, %79, "
        "%80, %81, %82, %83, %84, %85, %86, %87, %88, %89, %90, %91, %92, %93, %94, %95, "
        "%96, %97, %98, %99}, "
        "%100, %101, p, 1, 1, 0, 1;\n}\n"
        : "+f"(d[0]), "+f"(d[1]), "+f"(d[2]), "+f"(d[3]), "+f"(d[4]), "+f"(d[5]), "+f"(d[6]), "+f"(d[7]),
          "+f"(d[8]), "+f"(d[9]), "+f"(d[10]), "+f"(d[11]), "+f"(d[12]), "+f"(d[13]), "+f"(d[14]), "+f"(d[15]),
          "+f"(d[16]), "+f"(d[17]), "+f"(d[18]), "+f"(d[19]), "+f"(d[20]), "+f"(d[21]), "+f"(d[22]), "+f"(d[23]),
          "+f"(d[24]), "+f"(d[25]), "+f"(d[26]), "+f"(d[27]), "+f"(d[28]), "+f"(d[29]), "+f"(d[30]), "+f"(d[31]),
          "+f"(d[32]), "+f"(d[33]), "+f"(d[34]), "+f"(d[35]), "+f"(d[36]), "+f"(d[37]), "+f"(d[38]), "+f"(d[39]),
          "+f"(d[40]), "+f"(d[41]), "+f"(d[42]), "+f"(d[43]), "+f"(d[44]), "+f"(d[45]), "+f"(d[46]), "+f"(d[47]),
          "+f"(d[48]), "+f"(d[49]), "+f"(d[50]), "+f"(d[51]), "+f"(d[52]), "+f"(d[53]), "+f"(d[54]), "+f"(d[55]),
          "+f"(d[56]), "+f"(d[57]), "+f"(d[58]), "+f"(d[59]), "+f"(d[60]), "+f"(d[61]), "+f"(d[62]), "+f"(d[63]),
          "+f"(d[64]), "+f"(d[65]), "+f"(d[66]), "+f"(d[67]), "+f"(d[68]), "+f"(d[69]), "+f"(d[70]), "+f"(d[71]),
          "+f"(d[72]), "+f"(d[73]), "+f"(d[74]), "+f"(d[75]), "+f"(d[76]), "+f"(d[77]), "+f"(d[78]), "+f"(d[79]),
          "+f"(d[80]), "+f"(d[81]), "+f"(d[82]), "+f"(d[83]), "+f"(d[84]), "+f"(d[85]), "+f"(d[86]), "+f"(d[87]),
          "+f"(d[88]), "+f"(d[89]), "+f"(d[90]), "+f"(d[91]), "+f"(d[92]), "+f"(d[93]), "+f"(d[94]), "+f"(d[95]),
          "+f"(d[96]), "+f"(d[97]), "+f"(d[98]), "+f"(d[99])
        : "l"(descA), "l"(descB), "r"(scaleD));
}

__device__ __forceinline__ void wgmma_n40_ss_tb(float (&d)[20], uint64_t descA, uint64_t descB, int scaleD) {
    asm volatile("{\n.reg .pred p;\nsetp.ne.b32 p, %22, 0;\n"
        "wgmma.mma_async.sync.aligned.m64n40k16.f32.bf16.bf16 {"
        "%0, %1, %2, %3, %4, %5, %6, %7, %8, %9, %10, %11, %12, %13, %14, %15, "
        "%16, %17, %18, %19}, "
        "%20, %21, p, 1, 1, 0, 1;\n}\n"
        : "+f"(d[0]), "+f"(d[1]), "+f"(d[2]), "+f"(d[3]), "+f"(d[4]), "+f"(d[5]), "+f"(d[6]), "+f"(d[7]),
          "+f"(d[8]), "+f"(d[9]), "+f"(d[10]), "+f"(d[11]), "+f"(d[12]), "+f"(d[13]), "+f"(d[14]), "+f"(d[15]),
          "+f"(d[16]), "+f"(d[17]), "+f"(d[18]), "+f"(d[19])
        : "l"(descA), "l"(descB), "r"(scaleD));
}

__device__ __forceinline__ void wgmma_n192_ss_tb(float (&d)[96], uint64_t descA, uint64_t descB, int scaleD) {
    asm volatile("{\n.reg .pred p;\nsetp.ne.b32 p, %98, 0;\n"
        "wgmma.mma_async.sync.aligned.m64n192k16.f32.bf16.bf16 {"
        "%0, %1, %2, %3, %4, %5, %6, %7, %8, %9, %10, %11, %12, %13, %14, %15, "
        "%16, %17, %18, %19, %20, %21, %22, %23, %24, %25, %26, %27, %28, %29, %30, %31, "
        "%32, %33, %34, %35, %36, %37, %38, %39, %40, %41, %42, %43, %44, %45, %46, %47, "
        "%48, %49, %50, %51, %52, %53, %54, %55, %56, %57, %58, %59, %60, %61, %62, %63, "
        "%64, %65, %66, %67, %68, %69, %70, %71, %72, %73, %74, %75, %76, %77, %78, %79, "
        "%80, %81, %82, %83, %84, %85, %86, %87, %88, %89, %90, %91, %92, %93, %94, %95}, "
        "%96, %97, p, 1, 1, 0, 1;\n}\n"
        : "+f"(d[0]), "+f"(d[1]), "+f"(d[2]), "+f"(d[3]), "+f"(d[4]), "+f"(d[5]), "+f"(d[6]), "+f"(d[7]),
          "+f"(d[8]), "+f"(d[9]), "+f"(d[10]), "+f"(d[11]), "+f"(d[12]), "+f"(d[13]), "+f"(d[14]), "+f"(d[15]),
          "+f"(d[16]), "+f"(d[17]), "+f"(d[18]), "+f"(d[19]), "+f"(d[20]), "+f"(d[21]), "+f"(d[22]), "+f"(d[23]),
          "+f"(d[24]), "+f"(d[25]), "+f"(d[26]), "+f"(d[27]), "+f"(d[28]), "+f"(d[29]), "+f"(d[30]), "+f"(d[31]),
          "+f"(d[32]), "+f"(d[33]), "+f"(d[34]), "+f"(d[35]), "+f"(d[36]), "+f"(d[37]), "+f"(d[38]), "+f"(d[39]),
          "+f"(d[40]), "+f"(d[41]), "+f"(d[42]), "+f"(d[43]), "+f"(d[44]), "+f"(d[45]), "+f"(d[46]), "+f"(d[47]),
          "+f"(d[48]), "+f"(d[49]), "+f"(d[50]), "+f"(d[51]), "+f"(d[52]), "+f"(d[53]), "+f"(d[54]), "+f"(d[55]),
          "+f"(d[56]), "+f"(d[57]), "+f"(d[58]), "+f"(d[59]), "+f"(d[60]), "+f"(d[61]), "+f"(d[62]), "+f"(d[63]),
          "+f"(d[64]), "+f"(d[65]), "+f"(d[66]), "+f"(d[67]), "+f"(d[68]), "+f"(d[69]), "+f"(d[70]), "+f"(d[71]),
          "+f"(d[72]), "+f"(d[73]), "+f"(d[74]), "+f"(d[75]), "+f"(d[76]), "+f"(d[77]), "+f"(d[78]), "+f"(d[79]),
          "+f"(d[80]), "+f"(d[81]), "+f"(d[82]), "+f"(d[83]), "+f"(d[84]), "+f"(d[85]), "+f"(d[86]), "+f"(d[87]),
          "+f"(d[88]), "+f"(d[89]), "+f"(d[90]), "+f"(d[91]), "+f"(d[92]), "+f"(d[93]), "+f"(d[94]), "+f"(d[95])
        : "l"(descA), "l"(descB), "r"(scaleD));
}

__device__ __forceinline__ void wgmma_n192_ss_tb_z(float (&d)[96], uint64_t descA, uint64_t descB) {
    asm volatile("{\n.reg .pred p;\nsetp.ne.b32 p, 0, 0;\n"
        "wgmma.mma_async.sync.aligned.m64n192k16.f32.bf16.bf16 {"
        "%0, %1, %2, %3, %4, %5, %6, %7, %8, %9, %10, %11, %12, %13, %14, %15, "
        "%16, %17, %18, %19, %20, %21, %22, %23, %24, %25, %26, %27, %28, %29, %30, %31, "
        "%32, %33, %34, %35, %36, %37, %38, %39, %40, %41, %42, %43, %44, %45, %46, %47, "
        "%48, %49, %50, %51, %52, %53, %54, %55, %56, %57, %58, %59, %60, %61, %62, %63, "
        "%64, %65, %66, %67, %68, %69, %70, %71, %72, %73, %74, %75, %76, %77, %78, %79, "
        "%80, %81, %82, %83, %84, %85, %86, %87, %88, %89, %90, %91, %92, %93, %94, %95}, "
        "%96, %97, p, 1, 1, 0, 1;\n}\n"
        : "=f"(d[0]), "=f"(d[1]), "=f"(d[2]), "=f"(d[3]), "=f"(d[4]), "=f"(d[5]), "=f"(d[6]), "=f"(d[7]),
          "=f"(d[8]), "=f"(d[9]), "=f"(d[10]), "=f"(d[11]), "=f"(d[12]), "=f"(d[13]), "=f"(d[14]), "=f"(d[15]),
          "=f"(d[16]), "=f"(d[17]), "=f"(d[18]), "=f"(d[19]), "=f"(d[20]), "=f"(d[21]), "=f"(d[22]), "=f"(d[23]),
          "=f"(d[24]), "=f"(d[25]), "=f"(d[26]), "=f"(d[27]), "=f"(d[28]), "=f"(d[29]), "=f"(d[30]), "=f"(d[31]),
          "=f"(d[32]), "=f"(d[33]), "=f"(d[34]), "=f"(d[35]), "=f"(d[36]), "=f"(d[37]), "=f"(d[38]), "=f"(d[39]),
          "=f"(d[40]), "=f"(d[41]), "=f"(d[42]), "=f"(d[43]), "=f"(d[44]), "=f"(d[45]), "=f"(d[46]), "=f"(d[47]),
          "=f"(d[48]), "=f"(d[49]), "=f"(d[50]), "=f"(d[51]), "=f"(d[52]), "=f"(d[53]), "=f"(d[54]), "=f"(d[55]),
          "=f"(d[56]), "=f"(d[57]), "=f"(d[58]), "=f"(d[59]), "=f"(d[60]), "=f"(d[61]), "=f"(d[62]), "=f"(d[63]),
          "=f"(d[64]), "=f"(d[65]), "=f"(d[66]), "=f"(d[67]), "=f"(d[68]), "=f"(d[69]), "=f"(d[70]), "=f"(d[71]),
          "=f"(d[72]), "=f"(d[73]), "=f"(d[74]), "=f"(d[75]), "=f"(d[76]), "=f"(d[77]), "=f"(d[78]), "=f"(d[79]),
          "=f"(d[80]), "=f"(d[81]), "=f"(d[82]), "=f"(d[83]), "=f"(d[84]), "=f"(d[85]), "=f"(d[86]), "=f"(d[87]),
          "=f"(d[88]), "=f"(d[89]), "=f"(d[90]), "=f"(d[91]), "=f"(d[92]), "=f"(d[93]), "=f"(d[94]), "=f"(d[95])
        : "l"(descA), "l"(descB));
}

__device__ __forceinline__ void wgmma_n160_ss_tb(float (&d)[80], uint64_t descA, uint64_t descB, int scaleD) {
    asm volatile("{\n.reg .pred p;\nsetp.ne.b32 p, %82, 0;\n"
        "wgmma.mma_async.sync.aligned.m64n160k16.f32.bf16.bf16 {"
        "%0, %1, %2, %3, %4, %5, %6, %7, %8, %9, %10, %11, %12, %13, %14, %15, "
        "%16, %17, %18, %19, %20, %21, %22, %23, %24, %25, %26, %27, %28, %29, %30, %31, "
        "%32, %33, %34, %35, %36, %37, %38, %39, %40, %41, %42, %43, %44, %45, %46, %47, "
        "%48, %49, %50, %51, %52, %53, %54, %55, %56, %57, %58, %59, %60, %61, %62, %63, "
        "%64, %65, %66, %67, %68, %69, %70, %71, %72, %73, %74, %75, %76, %77, %78, %79}, "
        "%80, %81, p, 1, 1, 0, 1;\n}\n"
        : "+f"(d[0]), "+f"(d[1]), "+f"(d[2]), "+f"(d[3]), "+f"(d[4]), "+f"(d[5]), "+f"(d[6]), "+f"(d[7]),
          "+f"(d[8]), "+f"(d[9]), "+f"(d[10]), "+f"(d[11]), "+f"(d[12]), "+f"(d[13]), "+f"(d[14]), "+f"(d[15]),
          "+f"(d[16]), "+f"(d[17]), "+f"(d[18]), "+f"(d[19]), "+f"(d[20]), "+f"(d[21]), "+f"(d[22]), "+f"(d[23]),
          "+f"(d[24]), "+f"(d[25]), "+f"(d[26]), "+f"(d[27]), "+f"(d[28]), "+f"(d[29]), "+f"(d[30]), "+f"(d[31]),
          "+f"(d[32]), "+f"(d[33]), "+f"(d[34]), "+f"(d[35]), "+f"(d[36]), "+f"(d[37]), "+f"(d[38]), "+f"(d[39]),
          "+f"(d[40]), "+f"(d[41]), "+f"(d[42]), "+f"(d[43]), "+f"(d[44]), "+f"(d[45]), "+f"(d[46]), "+f"(d[47]),
          "+f"(d[48]), "+f"(d[49]), "+f"(d[50]), "+f"(d[51]), "+f"(d[52]), "+f"(d[53]), "+f"(d[54]), "+f"(d[55]),
          "+f"(d[56]), "+f"(d[57]), "+f"(d[58]), "+f"(d[59]), "+f"(d[60]), "+f"(d[61]), "+f"(d[62]), "+f"(d[63]),
          "+f"(d[64]), "+f"(d[65]), "+f"(d[66]), "+f"(d[67]), "+f"(d[68]), "+f"(d[69]), "+f"(d[70]), "+f"(d[71]),
          "+f"(d[72]), "+f"(d[73]), "+f"(d[74]), "+f"(d[75]), "+f"(d[76]), "+f"(d[77]), "+f"(d[78]), "+f"(d[79])
        : "l"(descA), "l"(descB), "r"(scaleD));
}

__device__ __forceinline__ void wgmma_n64_ss(float (&d)[32], uint64_t descA, uint64_t descB, int scaleD) {
    asm volatile("{\n.reg .pred p;\nsetp.ne.b32 p, %34, 0;\n"
        "wgmma.mma_async.sync.aligned.m64n64k16.f32.bf16.bf16 {"
        "%0, %1, %2, %3, %4, %5, %6, %7, %8, %9, %10, %11, %12, %13, %14, %15, "
        "%16, %17, %18, %19, %20, %21, %22, %23, %24, %25, %26, %27, %28, %29, %30, %31}, "
        "%32, %33, p, 1, 1, 0, 0;\n}\n"
        : "+f"(d[0]), "+f"(d[1]), "+f"(d[2]), "+f"(d[3]), "+f"(d[4]), "+f"(d[5]), "+f"(d[6]), "+f"(d[7]),
          "+f"(d[8]), "+f"(d[9]), "+f"(d[10]), "+f"(d[11]), "+f"(d[12]), "+f"(d[13]), "+f"(d[14]), "+f"(d[15]),
          "+f"(d[16]), "+f"(d[17]), "+f"(d[18]), "+f"(d[19]), "+f"(d[20]), "+f"(d[21]), "+f"(d[22]), "+f"(d[23]),
          "+f"(d[24]), "+f"(d[25]), "+f"(d[26]), "+f"(d[27]), "+f"(d[28]), "+f"(d[29]), "+f"(d[30]), "+f"(d[31])
        : "l"(descA), "l"(descB), "r"(scaleD));
}

__device__ __forceinline__ void wgmma_n64_ss_z(float (&d)[32], uint64_t descA, uint64_t descB) {
    asm volatile("{\n.reg .pred p;\nsetp.ne.b32 p, 0, 0;\n"
        "wgmma.mma_async.sync.aligned.m64n64k16.f32.bf16.bf16 {"
        "%0, %1, %2, %3, %4, %5, %6, %7, %8, %9, %10, %11, %12, %13, %14, %15, "
        "%16, %17, %18, %19, %20, %21, %22, %23, %24, %25, %26, %27, %28, %29, %30, %31}, "
        "%32, %33, p, 1, 1, 0, 0;\n}\n"
        : "=f"(d[0]), "=f"(d[1]), "=f"(d[2]), "=f"(d[3]), "=f"(d[4]), "=f"(d[5]), "=f"(d[6]), "=f"(d[7]),
          "=f"(d[8]), "=f"(d[9]), "=f"(d[10]), "=f"(d[11]), "=f"(d[12]), "=f"(d[13]), "=f"(d[14]), "=f"(d[15]),
          "=f"(d[16]), "=f"(d[17]), "=f"(d[18]), "=f"(d[19]), "=f"(d[20]), "=f"(d[21]), "=f"(d[22]), "=f"(d[23]),
          "=f"(d[24]), "=f"(d[25]), "=f"(d[26]), "=f"(d[27]), "=f"(d[28]), "=f"(d[29]), "=f"(d[30]), "=f"(d[31])
        : "l"(descA), "l"(descB));
}

__device__ __forceinline__ void wgmma_n24_rs_tb(float (&d)[12], uint32_t a0, uint32_t a1, uint32_t a2, uint32_t a3, uint64_t descB, int scaleD) {
    asm volatile("{\n.reg .pred p;\nsetp.ne.b32 p, %17, 0;\n"
        "wgmma.mma_async.sync.aligned.m64n24k16.f32.bf16.bf16 {"
        "%0, %1, %2, %3, %4, %5, %6, %7, %8, %9, %10, %11}, "
        "{%12, %13, %14, %15}, %16, p, 1, 1, 1;\n}\n"
        : "+f"(d[0]), "+f"(d[1]), "+f"(d[2]), "+f"(d[3]), "+f"(d[4]), "+f"(d[5]), "+f"(d[6]), "+f"(d[7]),
          "+f"(d[8]), "+f"(d[9]), "+f"(d[10]), "+f"(d[11])
        : "r"(a0), "r"(a1), "r"(a2), "r"(a3), "l"(descB), "r"(scaleD));
}

__device__ __forceinline__ void cnt_signal(int idx) {
    asm volatile("fence.acq_rel.gpu;\nred.relaxed.gpu.global.add.u32 [%0], 1;"
                 ::"l"(g_cnt + idx * 32) : "memory");
}
__device__ __forceinline__ void cnt_wait(int idx, uint32_t target) {
    const uint32_t* p = g_cnt + idx * 32;
#pragma unroll 1
    for (uint32_t i = 0; i < (1u << 22); i++) {
        uint32_t v;
        asm volatile("ld.acquire.gpu.global.u32 %0, [%1];" : "=r"(v) : "l"(p) : "memory");
        if ((int32_t)(v - target) >= 0) break;
    }
    asm volatile("fence.proxy.async.global;" ::: "memory");
}
__device__ __forceinline__ void cluster_arrive() { asm volatile("barrier.cluster.arrive.release.aligned;" ::: "memory"); }
__device__ __forceinline__ void cluster_arrive_relaxed() { asm volatile("barrier.cluster.arrive.relaxed.aligned;" ::: "memory"); }
__device__ __forceinline__ void cluster_wait() { asm volatile("barrier.cluster.wait.acquire.aligned;" ::: "memory"); }
__device__ __forceinline__ void bulk_wait_read() { asm volatile("cp.async.bulk.wait_group.read 0;" ::: "memory"); }

__device__ __forceinline__ float gelu_half(float hx) {
    const float u = hx * fmaf(hx * hx, 8.f * 0.035677408136300125f, 2.f * 0.7978845608028654f);
    float t;
    asm("tanh.approx.f32 %0, %1;" : "=f"(t) : "f"(u));
    return fmaf(hx, t, hx);
}
__device__ __forceinline__ void release_stage(uint32_t bar, uint32_t peer, int lane) {
    if (lane == 0) { mbar_arrive(bar); mbar_arrive_cluster(bar, peer); }
}

constexpr int SM_RING = 163840;
constexpr int SM_Q = 0, SM_ZERO = 24576, SM_K = SM_ZERO + 3072, SM_V = SM_K + IMG_BYTES;
constexpr int G2_STAGE = 8192 + 20480;
constexpr int SM_MISC = 229376;
constexpr int SM_BIAS = SM_MISC, SM_RED = SM_BIAS + 384, SM_BAR = SM_RED + 128;
constexpr int B_A = 0, B_F1 = 10, B_E1 = 14, B_F2 = 18, B_E2 = 23, B_KV = 28, B_Q = 45, B_F3 = 47, B_E3 = 55, B_ST = 63, B_STAT = 65, B_AUX = 66, B_AUX2 = 67, B_DEAD = 68, B_COUNT = 70;
constexpr int SM_EPOCH = SM_BAR + 568, SM_SAFE = SM_EPOCH + 4;
constexpr int SM_CS = SM_EPOCH + 8;
constexpr int SM_TOTAL = SM_CS + 1728;
static_assert(SM_TOTAL <= 232448, "shared memory budget");

struct Maps { CUtensorMap x, wqkv, w1, h, o, wo, w2; };

__device__ __forceinline__ uint32_t bf2_fma(uint32_t a, uint32_t b, uint32_t c) {
    uint32_t r;
    asm("fma.rn.bf16x2 %0, %1, %2, %3;" : "=r"(r) : "r"(a), "r"(b), "r"(c));
    return r;
}
__device__ __forceinline__ uint32_t lop_and_or(uint32_t a, uint32_t m, uint32_t o) {
    uint32_t r;
    asm("lop3.b32 %0, %1, %2, %3, 0xEA;" : "=r"(r) : "r"(a), "r"(m), "r"(o));
    return r;
}
struct ExpConst { uint32_t mask, slope; };
__device__ __forceinline__ ExpConst make_exp_const() {
    ExpConst k;
    asm volatile("mov.b32 %0, 0x007F007F;" : "=r"(k.mask));
    asm volatile("mov.b32 %0, 0x3EF83EF8;" : "=r"(k.slope));
    return k;
}
__device__ __forceinline__ uint32_t exp2_pair_fma(float t0, float t1, const ExpConst& k) {
    const uint32_t L = __byte_perm(__float_as_uint(t0), __float_as_uint(t1), 0x6521);
    const uint32_t g = lop_and_or(L, k.mask, 0x3F803F80u);
    const uint32_t u = bf2_fma(g, k.slope, 0xBF37BF37u);
    const uint32_t e = bf2_fma(u, u, 0xBD71BD71u);
    return bf2_fma(L, e, L);
}
template <int SHIFT>
__device__ __forceinline__ void exp_tile(const float (&s)[32], uint32_t (&p)[16], const ExpConst& k) {
#pragma unroll
    for (int b = 0; b < 8; b++) {
        if ((EMU_MASK >> (b + SHIFT)) & 1) {
            p[2 * b] = exp2_pair_fma(s[4 * b], s[4 * b + 1], k);
            p[2 * b + 1] = exp2_pair_fma(s[4 * b + 2], s[4 * b + 3], k);
        } else {
            p[2 * b] = pack_bf16(ex2(s[4 * b]), ex2(s[4 * b + 1]));
            p[2 * b + 1] = pack_bf16(ex2(s[4 * b + 2]), ex2(s[4 * b + 3]));
        }
    }
}

__device__ __forceinline__ void qk_tile(float (&s)[32], uint64_t dQ, uint64_t dQ2, uint64_t dK) {
    wg_fence();
    wgmma_n64_ss_z(s, dQ, dK);
    wgmma_n64_ss(s, dQ2, dK + 16, 1);
    wg_commit();
}
__device__ __forceinline__ void pv_tile(float (&o)[12], const uint32_t (&p)[16], uint64_t dV) {
    wg_fence();
#pragma unroll
    for (int ks = 0; ks < 4; ks++)
        wgmma_n24_rs_tb(o, p[4 * ks], p[4 * ks + 1], p[4 * ks + 2], p[4 * ks + 3], dV + ks * 48, 1);
    wg_commit();
}
__device__ __forceinline__ void store_o(const float (&o)[12], int h, int rbase, int lane) {
    const int g = lane >> 2, c = lane & 3;
    const bool odd = h & 1;
    const int lsrc = (lane & ~3) | (odd ? 0 : 2);
    const float i0 = 1.f / __shfl_sync(~0u, o[8], lsrc), i1 = 1.f / __shfl_sync(~0u, o[10], lsrc);
    __nv_bfloat16* dst = g_o + (size_t)(rbase + g) * DM + h * 20;
    const int d0 = (odd ? 4 : 0) + 2 * c, d1 = d0 + 8, d2 = odd ? 2 * c - 4 : 16 + 2 * c;
    *(uint32_t*)(dst + d0) = pack_bf16(o[0] * i0, o[1] * i0);
    *(uint32_t*)(dst + d1) = pack_bf16(o[4] * i0, o[5] * i0);
    *(uint32_t*)(dst + 8 * DM + d0) = pack_bf16(o[2] * i1, o[3] * i1);
    *(uint32_t*)(dst + 8 * DM + d1) = pack_bf16(o[6] * i1, o[7] * i1);
    if (odd ? (c >= 2) : (c < 2)) {
        *(uint32_t*)(dst + d2) = pack_bf16(o[8] * i0, o[9] * i0);
        *(uint32_t*)(dst + 8 * DM + d2) = pack_bf16(o[10] * i1, o[11] * i1);
    }
}

__device__ __forceinline__ void attn_rows_maxshift(uint32_t sK, uint32_t barKV, uint64_t dQ, uint64_t dQ2, int h, int rbase) {
    const int lane = threadIdx.x & 31;
    const uint64_t dK0 = make_desc(sK, 128, 384, 0), dV0 = make_desc(sK + IMG_BYTES, 384, 128, 0);
    float o[12], s[32];
    uint32_t p[16];
#pragma unroll
    for (int i = 0; i < 12; i++) o[i] = 0.f;
    float m0 = -3.0e38f, m1 = -3.0e38f;
    mbar_wait(barKV + 128, 0);
#pragma unroll 1
    for (int t = 0; t < 32; t++) {
        mbar_wait(barKV + (t >> 1) * 8, 0);
        qk_tile(s, dQ, dQ2, dK0 + t * 192);
        wg_wait<0>();
        fence_regs(s);
        const uint32_t mask = EMU_MASK >> ((t & 1) * 8);
        float n0 = m0, n1 = m1;
#pragma unroll
        for (int b = 0; b < 8; b++) {
            const bool emu = (mask >> b) & 1;
            const float f = emu ? 0.5f : 1.f, off = emu ? -383.00390625f : 0.f;
#pragma unroll
            for (int i = 0; i < 4; i++) s[4 * b + i] = fmaf(s[4 * b + i], f, off);
            n0 = fmaxf(n0, fmaxf(s[4 * b], s[4 * b + 1]));
            n1 = fmaxf(n1, fmaxf(s[4 * b + 2], s[4 * b + 3]));
        }
        n0 = fmaxf(n0, __shfl_xor_sync(~0u, n0, 1)); n0 = fmaxf(n0, __shfl_xor_sync(~0u, n0, 2));
        n1 = fmaxf(n1, __shfl_xor_sync(~0u, n1, 1)); n1 = fmaxf(n1, __shfl_xor_sync(~0u, n1, 2));
        const float c0 = ex2(m0 - n0), c1 = ex2(m1 - n1);
        m0 = n0; m1 = n1;
#pragma unroll
        for (int b = 0; b < 3; b++) { o[4 * b] *= c0; o[4 * b + 1] *= c0; o[4 * b + 2] *= c1; o[4 * b + 3] *= c1; }
#pragma unroll
        for (int b = 0; b < 8; b++) {
            p[2 * b] = pack_bf16(ex2(s[4 * b] - m0), ex2(s[4 * b + 1] - m0));
            p[2 * b + 1] = pack_bf16(ex2(s[4 * b + 2] - m1), ex2(s[4 * b + 3] - m1));
        }
        pv_tile(o, p, dV0 + (((t >> 1) + 7) & 15) * 384 + (t & 1) * 192);
        wg_wait<0>();
        fence_regs(o);
    }
    store_o(o, h, rbase, lane);
}

__global__ void __launch_bounds__(512, 1) __cluster_dims__(2, 1, 1)
k_fused(const __grid_constant__ Maps tm, const __nv_bfloat16* __restrict__ x, const uint8_t* __restrict__ wqkv,
        const uint8_t* __restrict__ w1, const uint8_t* __restrict__ w2, const uint8_t* __restrict__ wo,
        const __nv_bfloat16* __restrict__ b1, const __nv_bfloat16* __restrict__ b2, __nv_bfloat16* __restrict__ out) {
    extern __shared__ __align__(1024) uint8_t smem[];
    const uint32_t sb = smem_u32(smem);
    const uint32_t bar = sb + SM_BAR;
    const int warp = __shfl_sync(~0u, threadIdx.x >> 5, 0), lane = threadIdx.x & 31;
    const int wgi = warp >> 2, w4 = warp & 3, g = lane >> 2, c = lane & 3;
    const uint32_t rank = blockIdx.x & 1, peer = rank ^ 1;
    const int cl = blockIdx.x >> 1;
    const int cg = cl >> 3, rb = (cl & 7) * 2 + rank;

    if (threadIdx.x == 0) TL(0, 0);
    if (warp == 15 && lane < 4) prefetch_map(lane == 0 ? &tm.x : lane == 1 ? &tm.wqkv : lane == 2 ? &tm.w1 : &tm.h);
    if (elect_one()) {
#pragma unroll
        for (int j = 0; j < 5; j++) {
            const int i = warp * 5 + j;
            const int cnt = (i >= B_E1 && i < B_F2) || (i >= B_E2 && i < B_KV) ? 16
                          : (i >= B_E3 && i <= B_ST + 1) || i == B_STAT || i == B_DEAD || i == B_DEAD + 1 ? 8 : i == B_AUX ? 4 : i == B_AUX2 ? 3 : 1;
            if (i < B_COUNT) mbar_init(bar + i * 8, cnt);
        }
        fence_barrier_init();
    }
    __syncthreads();
    if (threadIdx.x == 0) TL(0, 1);
    cluster_arrive_relaxed();
    cluster_wait();
    if (threadIdx.x == 0) TL(0, 3);

    {
        const uint32_t sB = sb + SM_RING;
        if (threadIdx.x == 0) TL(1, 0);
        if (wgi < 2) {
            reg_dealloc<56>();
            if (warp == 0) {
#pragma unroll 1
                for (int it = 0; it < 20; it++) {
                    const int s = it & 3;
                    const int kb = it < 2 ? it : (it & 1) ? (it + 1) >> 1 : 10;
                    if (it >= 4) mbar_wait(bar + (B_E1 + s) * 8, ((it >> 2) - 1) & 1);
                    else if (it > 0) __nanosleep(PACE_NS);
                    if (elect_one()) {
                        if (kb < 10) {
                            mbar_expect_tx(bar + (B_A + kb) * 8, 16384);
                            tma_load(sb + kb * 16384, &tm.x, kb * 64, rb * 128, bar + (B_A + kb) * 8);
                        }
                        const uint32_t dst = sB + s * 16384 + rank * 8192, fb = bar + (B_F1 + s) * 8;
                        const int c0 = cg * 240 + rank * 128;
                        mbar_expect_tx(fb, 16384);
                        tma_load_mc(dst, &tm.wqkv, c0, it * 32, fb, 3);
                        tma_load_mc(dst + 4096, &tm.wqkv, c0 + 64, it * 32, fb, 3);
                    }
                    __syncwarp();
                }
#pragma unroll 1
                for (int it = 0; it < 20; it++) {
                    const int s = it % 5;
                    if (it < 5) { if (it != 3) mbar_wait(bar + (B_E1 + (it == 4 ? 3 : it)) * 8, 0); }
                    else mbar_wait(bar + (B_E2 + s) * 8, ((it / 5) - 1) & 1);
                    if (elect_one()) {
                        const uint32_t dst = sB + s * 12288, fb = bar + (B_F2 + s) * 8;
                        mbar_expect_tx(fb, 12288);
                        if ((it & 1) == (int)rank) {
                            tma_load_mc(dst, &tm.w1, cg * 192, it * 32, fb, 3);
                            tma_load_mc(dst + 4096, &tm.w1, cg * 192 + 64, it * 32, fb, 3);
                        } else {
                            tma_load_mc(dst + 8192, &tm.w1, cg * 192 + 128, it * 32, fb, 3);
                        }
                    }
                    __syncwarp();
                }
            } else {
                const int ht = threadIdx.x - 32;
                if (ht == 160) *reinterpret_cast<volatile uint32_t*>(smem + SM_EPOCH) = *(volatile uint32_t*)&g_epoch;
                auto slab_sum = [&](const uint32_t* src, int pitch) {
                    float s0 = 0.f, s1 = 0.f;
                    uint32_t v[40];
#pragma unroll
                    for (int k = 0; k < 40; k++) v[k] = __ldg(src + k * pitch);
#pragma unroll
                    for (int k = 0; k < 40; k++) { s0 += bf_lo(v[k]); s1 += bf_hi(v[k]); }
                    return make_float2(s0, s1);
                };
                auto gather = [&](int idx) {
                    float s0 = 0.f, s1 = 0.f;
#pragma unroll
                    for (int r = 0; r < 16; r++) {
                        const float2 v = __ldcg(g_csp + r * 1728 + cg * 216 + idx);
                        s0 += v.x; s1 += v.y;
                    }
                    reinterpret_cast<float2*>(smem + SM_CS)[idx] = make_float2(s0, s1);
                };
                if (warp == 7) {
                    mbar_wait(bar + B_STAT * 8, 0);
                    if (elect_one()) cnt_signal(CNT_ST + rb);
                    __syncwarp();
                }
                if (ht < 120)
                    g_csp[rb * 1728 + cg * 216 + ht] = slab_sum(reinterpret_cast<const uint32_t*>(wqkv) + rb * 40 * 960 + cg * 120 + ht, 960);
                if (threadIdx.x == 64) IT(3, 0);
                if (threadIdx.x == 192) IT(3, 1);
                if (warp != 7) asm volatile("bar.sync 8, 192;" ::: "memory");
                const uint32_t epoch = *reinterpret_cast<volatile uint32_t*>(smem + SM_EPOCH);
                if (warp == 6) { if (elect_one()) cnt_signal(CNT_CS + cg); __syncwarp(); }

                if (threadIdx.x == 64) IT(3, 2);
                if (warp <= 4) {
                    if (lane == 0) { cnt_wait(CNT_CS + cg, (epoch + 1) * 16); cnt_wait(CNT_ST + rb, (epoch + 1) * 8); }
                    __syncwarp();
                    if (threadIdx.x == 64) IT(3, 4);
                    if (ht < 120) gather(ht);
                    __syncwarp();
                    if (threadIdx.x == 64) IT(3, 5);
                    if (lane == 0) mbar_arrive(bar + B_AUX * 8);
                }
                if (ht >= 128) {
                    g_csp[rb * 1728 + cg * 216 + 120 + (ht - 128)] = slab_sum(reinterpret_cast<const uint32_t*>(w1) + rb * 40 * 768 + cg * 96 + (ht - 128), 768);
                    reinterpret_cast<uint32_t*>(smem + SM_BIAS)[ht - 128] =
                        bf2_fma(__ldg(reinterpret_cast<const uint32_t*>(b1 + cg * 192) + (ht - 128)), 0x3F003F00u, 0x80008000u);
                    asm volatile("bar.sync 9, 96;" ::: "memory");
                    const uint32_t epoch2 = *reinterpret_cast<volatile uint32_t*>(smem + SM_EPOCH);
                    if (warp == 5) { if (elect_one()) cnt_signal(CNT_CS2 + cg); __syncwarp(); }
                    if (warp == 6 && elect_one()) {
                        prefetch_l2(w2 + blockIdx.x * 15360, 15360);
                        prefetch_l2(wo + blockIdx.x * 6400, 6400);
                    }
                    if (lane == 0) cnt_wait(CNT_CS2 + cg, (epoch2 + 1) * 16);
                    __syncwarp();
                    gather(120 + (ht - 128));
                    __syncwarp();
                    if (lane == 0) mbar_arrive(bar + B_AUX2 * 8);
                }
                if (warp == 4) {
                    mbar_wait(bar + B_ST * 8, 0);
                    if (elect_one()) cnt_signal(CNT_QKV + cg);
                    __syncwarp();
                }
                const int h = blockIdx.x >> 2, qb = blockIdx.x & 3;
                const uint32_t ep = *reinterpret_cast<volatile uint32_t*>(smem + SM_EPOCH);
                if (lane == 0 && warp != 5) {
                    cnt_wait(CNT_QKV + h / 12, (ep + 1) * 16);
                    cnt_wait(CNT_QKV + (32 + h) / 12, (ep + 1) * 16);
                    cnt_wait(CNT_QKV + (64 + h) / 12, (ep + 1) * 16);
                }
                __syncwarp();
                if (threadIdx.x == 64) TL(5, 0);
                if (warp == 1 || warp == 4 || warp >= 6) {
                    const int w = warp == 1 ? 0 : warp == 4 ? 1 : warp - 4, t = w * 32 + lane;
                    float kmax = 0.f, qmax = 0.f;
#pragma unroll
                    for (int i = 0; i < 4; i++) {
                        const float4 v = __ldcg(reinterpret_cast<const float4*>(g_nrm + (32 + h) * SEQ) + t + i * 128);
                        kmax = fmaxf(fmaxf(kmax, fmaxf(v.x, v.y)), fmaxf(v.z, v.w));
                    }
                    {
                        const float4 v = __ldcg(reinterpret_cast<const float4*>(g_nrm + h * SEQ + qb * 512) + t);
                        qmax = fmaxf(fmaxf(v.x, v.y), fmaxf(v.z, v.w));
                    }
#pragma unroll
                    for (int o = 16; o; o >>= 1) {
                        kmax = fmaxf(kmax, __shfl_xor_sync(~0u, kmax, o));
                        qmax = fmaxf(qmax, __shfl_xor_sync(~0u, qmax, o));
                    }
                    float* red = reinterpret_cast<float*>(smem + SM_RED);
                    if (lane == 0) { red[w] = kmax; red[8 + w] = qmax; }
                    asm volatile("bar.sync 8, 128;" ::: "memory");
                    if (warp == 1 && lane == 0) {
                        for (int u = 1; u < 4; u++) { kmax = fmaxf(kmax, red[u]); qmax = fmaxf(qmax, red[8 + u]); }
                        *reinterpret_cast<volatile uint32_t*>(smem + SM_SAFE) = kmax * qmax * 1.1f <= SAFE_BOUND * SAFE_BOUND;
                    }
                }
                const uint32_t barKV = bar + B_KV * 8;
                const uint8_t* gK = g_img + (size_t)(32 + h) * IMG_BYTES;
                const uint8_t* gV = g_img + (size_t)(64 + h) * IMG_BYTES;
                if (warp == 2) {
                    if (lane == 0) TL(5, 1);
                    mbar_wait(bar + B_DEAD * 8, 0);
                    if (lane == 0) TL(5, 2);
                    for (int i = lane; i < 192; i += 32) *reinterpret_cast<uint4*>(smem + SM_ZERO + i * 16) = make_uint4(0, 0, 0, 0);
                    fence_proxy_async();
                    __syncwarp();
                    if (elect_one()) {
                        asm volatile("fence.proxy.async.global;" ::: "memory");
                        const uint8_t* gQ = g_img + (size_t)h * IMG_BYTES + qb * 64 * 384;
                        mbar_expect_tx(barKV + 128, 6144);
                        bulk_load(sb + SM_K, gK, 6144, barKV + 128);
                        for (int p = 0; p < 2; p++) {
                            mbar_expect_tx(bar + (B_Q + p) * 8, 12288);
                            bulk_load(sb + SM_Q + p * 12288, gQ + p * 12288, 12288, bar + (B_Q + p) * 8);
                        }
                        for (int i = 0; i < 13; i++) {
                            mbar_expect_tx(barKV + i * 8, 12288);
                            bulk_load(sb + SM_K + (i + 1) * 6144, gK + (i + 1) * 6144, 6144, barKV + i * 8);
                        }
                    }
                    __syncwarp();
                    if (lane == 0) TL(5, 3);
                } else if (warp == 5) {
                    mbar_wait(bar + (B_ST + 1) * 8, 0);
                    if (lane == 0) {
                        for (int b = 0; b < 6; b++)
                            tma_store(&tm.h, sb + (7 + b % 3) * 16384 + (b / 3) * 8192, cg * 192 + (b % 3) * 64, rb * 128 + (b / 3) * 64);
                        bulk_commit();
                    }
                    __syncwarp();
                } else if (warp == 3) {
                    mbar_wait(bar + (B_DEAD + 1) * 8, 0);
                    if (elect_one()) {
                        asm volatile("fence.proxy.async.global;" ::: "memory");
                        for (int i = 0; i < 9; i++) bulk_load(sb + SM_V + (i + 7) * 6144, gV + i * 6144, 6144, barKV + i * 8);
                    }
                    __syncwarp();
                }
            }
            if (lane == 0) TL(6, warp);
            asm volatile("bar.sync %0, 128;" ::"r"(wgi + 3) : "memory");
            reg_alloc<128>();
        } else {
            reg_alloc<200>();
            const int wi = wgi - 2;
            const int row0 = rb * 128 + wi * 64 + w4 * 16 + g;
            const uint32_t sAw = sb + wi * 8192;
            const int rbk = row0 >> 3, hs0 = cg * 12;
            {
                const int srow = rb * 128 + cg * 16 + (warp - 8) * 2 + (lane >> 4);
                uint4 xv[5];
#pragma unroll
                for (int i = 0; i < 5; i++) xv[i] = __ldg(reinterpret_cast<const uint4*>(x + (size_t)srow * DM) + (lane & 15) + 16 * i);
                float sm = 0.f;
#pragma unroll
                for (int i = 0; i < 5; i++)
                    sm += ((bf_lo(xv[i].x) + bf_hi(xv[i].x)) + (bf_lo(xv[i].y) + bf_hi(xv[i].y))) +
                          ((bf_lo(xv[i].z) + bf_hi(xv[i].z)) + (bf_lo(xv[i].w) + bf_hi(xv[i].w)));
#pragma unroll
                for (int o = 8; o; o >>= 1) sm += __shfl_xor_sync(~0u, sm, o);
                const float mu = sm * (1.f / DM);
                float q0 = 0.f, q1 = 0.f;
#pragma unroll
                for (int i = 0; i < 5; i++) {
                    const uint32_t w[4] = {xv[i].x, xv[i].y, xv[i].z, xv[i].w};
#pragma unroll
                    for (int j = 0; j < 4; j++) {
                        const float d0 = bf_lo(w[j]) - mu, d1 = bf_hi(w[j]) - mu;
                        q0 = fmaf(d0, d0, q0); q1 = fmaf(d1, d1, q1);
                    }
                }
                float q = q0 + q1;
#pragma unroll
                for (int o = 8; o; o >>= 1) q += __shfl_xor_sync(~0u, q, o);
                const float var = q * (1.f / DM);
                const float r1 = rsqrtf(var + LN_EPS);
                const float r2 = rsqrtf(var * r1 * r1 + LN_EPS);
                if ((lane & 15) == 0) g_stat[srow] = make_float4(mu, r1, r1 * r2, 0.f);
                __syncwarp();
                if (lane == 0) mbar_arrive(bar + B_STAT * 8);
            }
            float accA[100], accB[20];
            const uint64_t dA0 = make_desc(sAw, 16, 1024, 1), dB0 = make_desc(sB, 4096, 1024, 1);
#pragma unroll 2
            for (int it = 0; it < 20; it++) {
                const int s = it & 3;
                if (!(it & 1)) mbar_wait(bar + (B_A + (it >> 1)) * 8, 0);
                if (threadIdx.x == 256 && it == 0) TL(0, 2);
                if (threadIdx.x == 256) IT(0, it);
                mbar_wait(bar + (B_F1 + s) * 8, (it >> 2) & 1);
                if (threadIdx.x == 256) IT(1, it);
                const uint64_t dA = dA0 + (it >> 1) * 1024 + (it & 1) * 4, dB = dB0 + s * 1024;
                wg_fence();
                wgmma_n40_ss_tb(accB, dA, dB + 769, it > 0);
                wgmma_n40_ss_tb(accB, dA + 2, dB + 769 + 128, 1);
                wgmma_n200_ss_tb(accA, dA, dB, it > 0);
                wgmma_n200_ss_tb(accA, dA + 2, dB + 128, 1);
                wg_commit();
                if (it > 0) { wg_wait<1>(); release_stage(bar + (B_E1 + ((it - 1) & 3)) * 8, peer, lane); }
            }
            if (threadIdx.x == 256) IT(2, 0);
            mbar_wait(bar + B_AUX * 8, 0);
            if (threadIdx.x == 256) IT(2, 1);
            const float4 st0 = __ldcg(g_stat + row0), st1 = __ldcg(g_stat + row0 + 8);
            wg_wait<0>();
            release_stage(bar + (B_E1 + 3) * 8, peer, lane);
            fence_regs(accA);
            fence_regs(accB);
            if (threadIdx.x == 256) TL(1, 1);
            const float2* cs = reinterpret_cast<const float2*>(smem + SM_CS) + c;
            uint8_t* img = g_img + (size_t)hs0 * IMG_BYTES + rbk * 384 + g * 16 + c * 4;
            const bool emu0 = (EMU_MASK >> (rbk & 15)) & 1, emu1 = (EMU_MASK >> ((rbk + 1) & 15)) & 1;
            const bool low = c < 2;
            uint32_t pk[60];
#pragma unroll
            for (int m = 0; m < 6; m++) {
                const int which = (hs0 + 2 * m) >> 5;
                const float m0 = st0.y * (which == 0 ? QSCALE : (which == 1 && emu0) ? 2.f : 1.f);
                const float m1 = st1.y * (which == 0 ? QSCALE : (which == 1 && emu1) ? 2.f : 1.f);
                const float d0 = -st0.x * m0, d1 = -st1.x * m1;
                const float* a = m < 5 ? &accA[20 * m] : accB;
#pragma unroll
                for (int b = 0; b < 5; b++) {
                    const float2 cv = cs[(5 * m + b) * 4];
                    pk[10 * m + 2 * b] = pack_bf16(fmaf(a[4 * b], m0, d0 * cv.x), fmaf(a[4 * b + 1], m0, d0 * cv.y));
                    pk[10 * m + 2 * b + 1] = pack_bf16(fmaf(a[4 * b + 2], m1, d1 * cv.x), fmaf(a[4 * b + 3], m1, d1 * cv.y));
                }
            }
            const float r20 = 0.5f * st0.z, r21 = 0.5f * st1.z, e20 = -st0.x * r20, e21 = -st1.x * r21;
            if (threadIdx.x == 256) IT(2, 2);
            float acc2[96];
#pragma unroll
            for (int it = 0; it < 20; it++) {
                const int s = it % 5;
                if (threadIdx.x == 256) IT(0, 20 + it);
                mbar_wait(bar + (B_F2 + s) * 8, (it / 5) & 1);
                if (threadIdx.x == 256) IT(1, 20 + it);
                wg_fence();
                const uint64_t dA = make_desc(sAw + (it >> 1) * 16384 + (it & 1) * 64, 16, 1024, 1);
                const uint64_t dB = make_desc(sB + s * 12288, 4096, 1024, 1);
                if (it == 0) wgmma_n192_ss_tb_z(acc2, dA, dB); else wgmma_n192_ss_tb(acc2, dA, dB, 1);
                wgmma_n192_ss_tb(acc2, dA + 2, dB + 128, 1);
                wg_commit();
                if (it > 0) {
                    wg_wait<1>();
                    if (it <= 15) release_stage(bar + (B_E2 + (it - 1) % 5) * 8, peer, lane);
                    if (it == 14 && lane == 0) mbar_arrive(bar + B_DEAD * 8);
                }
                if (it < 6) {
                    const int m = it;
                    const int hs = hs0 + 2 * m, which = hs >> 5;
                    const uint32_t* a = pk + 10 * m;
                    uint8_t* pe = img + (2 * m) * IMG_BYTES;
                    uint8_t* po = pe + IMG_BYTES;
                    const uint32_t padv = which == 0 ? 0x3F803F80u : which == 1 ? 0xBFFF4440u : 0x00003F80u;
                    const uint32_t p0 = ((c & 1) || (which == 1 && !emu0)) ? 0u : padv;
                    const uint32_t p1 = ((c & 1) || (which == 1 && !emu1)) ? 0u : padv;
                    *(uint32_t*)(pe) = a[0];
                    *(uint32_t*)(pe + 128) = a[2];
                    *(uint32_t*)(pe + 256) = low ? a[4] : p0;
                    *(uint32_t*)(pe + 384) = a[1];
                    *(uint32_t*)(pe + 512) = a[3];
                    *(uint32_t*)(pe + 640) = low ? a[5] : p1;
                    *(uint32_t*)(po) = a[6];
                    *(uint32_t*)(po + 128) = a[8];
                    *(uint32_t*)(po + 256) = low ? p0 : a[4];
                    *(uint32_t*)(po + 384) = a[7];
                    *(uint32_t*)(po + 512) = a[9];
                    *(uint32_t*)(po + 640) = low ? p1 : a[5];
                    if (which < 2) {
                        const uint32_t u0 = bf2_fma(a[4], a[4], 0u), u1 = bf2_fma(a[5], a[5], 0u);
                        const uint32_t pe0 = bf2_fma(a[0], a[0], bf2_fma(a[2], a[2], low ? u0 : 0u));
                        const uint32_t pe1 = bf2_fma(a[1], a[1], bf2_fma(a[3], a[3], low ? u1 : 0u));
                        const uint32_t po0 = bf2_fma(a[6], a[6], bf2_fma(a[8], a[8], low ? 0u : u0));
                        const uint32_t po1 = bf2_fma(a[7], a[7], bf2_fma(a[9], a[9], low ? 0u : u1));
                        const float e0 = bf_lo(pe0) + bf_hi(pe0), e1 = bf_lo(pe1) + bf_hi(pe1);
                        const float o0 = bf_lo(po0) + bf_hi(po0), o1 = bf_lo(po1) + bf_hi(po1);
                        const bool b0 = c & 1, b1_ = c & 2;
                        const float x0 = (b0 ? e1 : e0) + __shfl_xor_sync(~0u, b0 ? e0 : e1, 1);
                        const float x1 = (b0 ? o1 : o0) + __shfl_xor_sync(~0u, b0 ? o0 : o1, 1);
                        float y = (b1_ ? x1 : x0) + __shfl_xor_sync(~0u, b1_ ? x0 : x1, 2);
                        if (which == 1 && (b0 ? emu1 : emu0)) y *= 0.25f;
                        g_nrm[(hs + (c >> 1)) * SEQ + row0 + (c & 1) * 8] = y;
                    }
                    if (it == 5) { __syncwarp(); if (lane == 0) mbar_arrive(bar + B_ST * 8); }
                }
            }
            wg_wait<0>();
            fence_regs(acc2);
            if (lane == 0) mbar_arrive(bar + (B_DEAD + 1) * 8);
            if (threadIdx.x == 256) TL(1, 2);
            mbar_wait(bar + B_AUX2 * 8, 0);
            if (threadIdx.x == 256) TL(4, 0);
            const uint32_t* bias = reinterpret_cast<const uint32_t*>(smem + SM_BIAS) + c;
            const int mrow = w4 * 16 + (lane & 15);
            const uint32_t stage = sAw + 7 * 16384;
            const uint32_t st_row = stage + mrow * 128;
#pragma unroll
            for (int j = 0; j < 24; j += 2) {
                const uint32_t bA = bias[j * 4], bB = bias[j * 4 + 4];
                const float2 cA = cs[(30 + j) * 4], cB = cs[(31 + j) * 4];
                const float* a = acc2 + j * 4;
                const uint32_t r00 = pack_bf16(gelu_half(fmaf(a[0], r20, fmaf(e20, cA.x, bf_lo(bA)))), gelu_half(fmaf(a[1], r20, fmaf(e20, cA.y, bf_hi(bA)))));
                const uint32_t r10 = pack_bf16(gelu_half(fmaf(a[2], r21, fmaf(e21, cA.x, bf_lo(bA)))), gelu_half(fmaf(a[3], r21, fmaf(e21, cA.y, bf_hi(bA)))));
                const uint32_t r01 = pack_bf16(gelu_half(fmaf(a[4], r20, fmaf(e20, cB.x, bf_lo(bB)))), gelu_half(fmaf(a[5], r20, fmaf(e20, cB.y, bf_hi(bB)))));
                const uint32_t r11 = pack_bf16(gelu_half(fmaf(a[6], r21, fmaf(e21, cB.x, bf_lo(bB)))), gelu_half(fmaf(a[7], r21, fmaf(e21, cB.y, bf_hi(bB)))));
                const int chunk = (j & 7) + (lane >> 4);
                stmatrix_x4(st_row + (j >> 3) * 16384 + ((chunk ^ (mrow & 7)) << 4), r00, r10, r01, r11);
            }
            if (threadIdx.x == 256) TL(4, 1);
            fence_proxy_async();
            __syncwarp();
            if (lane == 0) mbar_arrive(bar + (B_ST + 1) * 8);
            asm volatile("bar.sync %0, 128;" ::"r"(wgi + 3) : "memory");
            reg_dealloc<128>();
            if (threadIdx.x == 256) TL(4, 3);
        }
        __syncthreads();
        if (threadIdx.x == 0) TL(1, 3);
    }

    {
        const int h = blockIdx.x >> 2, qb = blockIdx.x & 3;
        const uint32_t sK = sb + SM_K, sV = sb + SM_V, barKV = bar + B_KV * 8;
        if (threadIdx.x == 0) TL(2, 0);
        auto late_tiles = [&]() {
            if (warp == 5 && lane == 0) {
                bulk_wait_read();
                asm volatile("fence.proxy.async.global;" ::: "memory");
                const uint8_t* gK = g_img + (size_t)(32 + h) * IMG_BYTES;
                const uint8_t* gV = g_img + (size_t)(64 + h) * IMG_BYTES;
                for (int i = 9; i < 16; i++) {
                    if (i >= 13) mbar_expect_tx(barKV + i * 8, i < 15 ? 12288 : 6144);
                    bulk_load(sV + ((i + 7) & 15) * 6144, gV + i * 6144, 6144, barKV + i * 8);
                    if (i >= 13 && i < 15) bulk_load(sK + (i + 1) * 6144, gK + (i + 1) * 6144, 6144, barKV + i * 8);
                }
            }
            __syncwarp();
        };
        const bool safe = __all_sync(~0u, *reinterpret_cast<volatile uint32_t*>(smem + SM_SAFE) != 0);
        if (threadIdx.x == 0) TL(2, 1);
        const uint64_t dK0 = make_desc(sK, 128, 384, 0), dV0 = make_desc(sV, 384, 128, 0);
        auto publish_h = [&]() {
            if (warp == 5) {
                if (lane == 0) { bulk_wait_all(); cnt_signal(CNT_H + rb); }
                __syncwarp();
            }
        };
        if (!safe) {
            late_tiles();
#pragma unroll 1
            for (int pass = 0; pass < 2; pass++) {
                const uint32_t sQ = sb + SM_Q + pass * 12288 + wgi * 3072;
                mbar_wait(bar + (B_Q + pass) * 8, 0);
                attn_rows_maxshift(sK, barKV, make_desc(sQ, 128, 384, 0), make_desc(sQ + 256, sb + SM_ZERO - (sQ + 256), 384, 0), h,
                                   qb * 512 + pass * 256 + wgi * 64 + w4 * 16);
                if (pass == 0) publish_h();
            }
        } else {
            const ExpConst kc = make_exp_const();
#pragma unroll 1
            for (int pass = 0; pass < 2; pass++) {
                const int rbase = qb * 512 + pass * 256 + wgi * 64 + w4 * 16;
                const uint32_t sQ = sb + SM_Q + pass * 12288 + wgi * 3072;
                const uint64_t dQ = make_desc(sQ, 128, 384, 0), dQ2 = make_desc(sQ + 256, sb + SM_ZERO - (sQ + 256), 384, 0);
                float o[12], sa[32], sc[32];
                uint32_t p[16];
#pragma unroll
                for (int i = 0; i < 12; i++) o[i] = 0.f;
                fence_regs(o);
                mbar_wait(bar + (B_Q + pass) * 8, 0);
                mbar_wait(barKV + 128, 0);
                qk_tile(sa, dQ, dQ2, dK0);
                wg_wait<0>();
                fence_regs(sa);
                uint64_t dK = dK0, dV = dV0 + 7 * 384;
                uint32_t bj = barKV;
#pragma unroll 1
                for (int j = 0; j < 16; j++) {
                    mbar_wait(bj, 0);
                    if (pass == 0 && j == 2) late_tiles();
                    qk_tile(sc, dQ, dQ2, dK + 192);
                    wg_wait<1>();
                    exp_tile<0>(sa, p, kc);
                    pv_tile(o, p, dV);
                    wg_wait<1>();
                    fence_regs(sc);
                    mbar_wait(bj, 0);
                    qk_tile(sa, dQ, dQ2, dK + 384);
                    wg_wait<1>();
                    exp_tile<8>(sc, p, kc);
                    pv_tile(o, p, dV + 192);
                    wg_wait<1>();
                    fence_regs(sa);
                    dK += 384; dV = j == 8 ? dV0 : dV + 384; bj += 8;
                }
                wg_wait<0>();
                fence_regs(o);
                store_o(o, h, rbase, lane);
                if (threadIdx.x == 0) TL(2, 2 + pass);
                if (pass == 0) publish_h();
            }
        }
        __syncthreads();
        if (threadIdx.x == 64) cnt_signal(CNT_O + qb);
        cluster_arrive_relaxed();
    }

    {
        const uint32_t epoch = *reinterpret_cast<volatile uint32_t*>(smem + SM_EPOCH);
        const int ct = cl & 3, rt = (cl >> 2) * 2 + rank;
        if (threadIdx.x == 0) TL(3, 0);
        const int ot = threadIdx.x - 192, orow = ot / 5, oseg = ot - orow * 5;
        const size_t ooff = (size_t)(rt * 64 + orow) * DM + ct * 160 + oseg * 32;
        uint4 xr[4], br[4];
        if (ot >= 0) {
#pragma unroll
            for (int i = 0; i < 4; i++) {
                asm volatile("ld.global.nc.v4.u32 {%0, %1, %2, %3}, [%4];" : "=r"(xr[i].x), "=r"(xr[i].y), "=r"(xr[i].z), "=r"(xr[i].w)
                             : "l"(reinterpret_cast<const uint4*>(x + ooff) + i));
                asm volatile("ld.global.nc.v4.u32 {%0, %1, %2, %3}, [%4];" : "=r"(br[i].x), "=r"(br[i].y), "=r"(br[i].z), "=r"(br[i].w)
                             : "l"(reinterpret_cast<const uint4*>(b2 + ct * 160 + oseg * 32) + i));
            }
        }
        cluster_wait();
        float* stg = reinterpret_cast<float*>(smem);
        if (warp == 4) {
            if (elect_one()) { prefetch_map(&tm.h); prefetch_map(&tm.o); prefetch_map(&tm.w2); prefetch_map(&tm.wo); cnt_wait(CNT_H + (rt >> 1), (epoch + 1) * 8); }
            __syncwarp();
#pragma unroll 1
            for (int kb = 0; kb < 34; kb++) {
                const int s = kb & 7;
                if (kb >= 8) mbar_wait(bar + (B_E3 + s) * 8, ((kb >> 3) - 1) & 1);
                if (elect_one()) {
                    if (kb == 24) { cnt_wait(CNT_O + (rt >> 3), (epoch + 1) * 32); TL(3, 1); }
                    const uint32_t dst = sb + s * G2_STAGE, fb = bar + (B_F3 + s) * 8;
                    const CUtensorMap* mA = kb < 24 ? &tm.h : &tm.o;
                    const CUtensorMap* mB = kb < 24 ? &tm.w2 : &tm.wo;
                    const int k0 = (kb < 24 ? kb : kb - 24) * 64;
                    mbar_expect_tx(fb, G2_STAGE);
                    tma_load(dst, mA, k0, rt * 64, fb);
                    const int first = ((kb & 1) == (int)rank) ? 0 : 3, last = ((kb & 1) == (int)rank) ? 3 : 5;
                    for (int b = first; b < last; b++) tma_load_mc(dst + 8192 + b * 4096, mB, ct * 160 + b * 32, k0, fb, 3);
                }
                __syncwarp();
            }
        } else if (wgi == 0) {
            float acc[80];
#pragma unroll 1
            for (int kb = 0; kb < 34; kb++) {
                const int s = kb & 7;
                mbar_wait(bar + (B_F3 + s) * 8, (kb >> 3) & 1);
                wg_fence();
                const uint64_t dA = make_desc(sb + s * G2_STAGE, 16, 1024, 1);
                const uint64_t dB = make_desc(sb + s * G2_STAGE + 8192, 4096, 512, 2);
#pragma unroll
                for (int kk = 0; kk < 4; kk++) wgmma_n160_ss_tb(acc, dA + kk * 2, dB + kk * 64, (kb | kk) != 0);
                wg_commit();
                if (kb > 0) {
                    wg_wait<1>();
                    if (kb <= 26) release_stage(bar + (B_E3 + ((kb - 1) & 7)) * 8, peer, lane);
                }
            }
            wg_wait<0>();
            fence_regs(acc);
            if (threadIdx.x == 0) TL(3, 2);
            const int r = w4 * 16 + g;
#pragma unroll
            for (int j = 0; j < 20; j++) {
                *reinterpret_cast<float2*>(stg + r * 184 + j * 8 + (j >> 2) * 4 + 2 * c) = make_float2(acc[4 * j], acc[4 * j + 1]);
                *reinterpret_cast<float2*>(stg + (r + 8) * 184 + j * 8 + (j >> 2) * 4 + 2 * c) = make_float2(acc[4 * j + 2], acc[4 * j + 3]);
            }
        }
        __syncthreads();
        if (ot >= 0) {
            const float4* sp = reinterpret_cast<const float4*>(stg + orow * 184 + oseg * 36);
#pragma unroll
            for (int i = 0; i < 4; i++) {
                const float4 a = sp[2 * i], b = sp[2 * i + 1];
                uint4 w;
                w.x = pack_bf16(a.x + bf_lo(br[i].x) + bf_lo(xr[i].x), a.y + bf_hi(br[i].x) + bf_hi(xr[i].x));
                w.y = pack_bf16(a.z + bf_lo(br[i].y) + bf_lo(xr[i].y), a.w + bf_hi(br[i].y) + bf_hi(xr[i].y));
                w.z = pack_bf16(b.x + bf_lo(br[i].z) + bf_lo(xr[i].z), b.y + bf_hi(br[i].z) + bf_hi(xr[i].z));
                w.w = pack_bf16(b.z + bf_lo(br[i].w) + bf_lo(xr[i].w), b.w + bf_hi(br[i].w) + bf_hi(xr[i].w));
                reinterpret_cast<uint4*>(out + ooff)[i] = w;
            }
        }
        if (blockIdx.x == 0 && threadIdx.x == 0) g_epoch = epoch + 1;
        if (threadIdx.x == 256) TL(3, 3);
    }
    cluster_arrive_relaxed();
    cluster_wait();
}

typedef CUresult (*EncodeTiledFn)(CUtensorMap*, CUtensorMapDataType, cuuint32_t, void*, const cuuint64_t*,
                                  const cuuint64_t*, const cuuint32_t*, const cuuint32_t*, CUtensorMapInterleave,
                                  CUtensorMapSwizzle, CUtensorMapL2promotion, CUtensorMapFloatOOBfill);

CUtensorMap make_map(EncodeTiledFn enc, const void* ptr, int rows, int cols, int box_rows, int box_cols,
                     CUtensorMapSwizzle swz) {
    CUtensorMap m;
    cuuint64_t gd[2] = {(cuuint64_t)cols, (cuuint64_t)rows};
    cuuint64_t gs[1] = {(cuuint64_t)cols * 2};
    cuuint32_t bd[2] = {(cuuint32_t)box_cols, (cuuint32_t)box_rows};
    cuuint32_t es[2] = {1, 1};
    enc(&m, CU_TENSOR_MAP_DATA_TYPE_BFLOAT16, 2, const_cast<void*>(ptr), gd, gs, bd, es, CU_TENSOR_MAP_INTERLEAVE_NONE,
        swz, CU_TENSOR_MAP_L2_PROMOTION_L2_128B, CU_TENSOR_MAP_FLOAT_OOB_FILL_NONE);
    return m;
}

}

extern "C" void kernel_launch(void* const* d_in, const int* in_sizes, int n_in, void* d_out, int out_size) {
    (void)in_sizes; (void)n_in; (void)out_size;
    const __nv_bfloat16* x = (const __nv_bfloat16*)d_in[0];
    const __nv_bfloat16* wqkv = (const __nv_bfloat16*)d_in[1];
    const __nv_bfloat16* wo = (const __nv_bfloat16*)d_in[2];
    const __nv_bfloat16* w1 = (const __nv_bfloat16*)d_in[4];
    const __nv_bfloat16* b1 = (const __nv_bfloat16*)d_in[5];
    const __nv_bfloat16* w2 = (const __nv_bfloat16*)d_in[6];
    const __nv_bfloat16* b2 = (const __nv_bfloat16*)d_in[7];
    __nv_bfloat16* out = (__nv_bfloat16*)d_out;

    static EncodeTiledFn enc = nullptr;
    static void *p_h, *p_o;
    if (!enc) {
        cudaDriverEntryPointQueryResult qr;
        cudaGetDriverEntryPoint("cuTensorMapEncodeTiled", (void**)&enc, cudaEnableDefault, &qr);
        cudaGetSymbolAddress(&p_h, g_h);
        cudaGetSymbolAddress(&p_o, g_o);
        cudaFuncSetAttribute(k_fused, cudaFuncAttributeMaxDynamicSharedMemorySize, SM_TOTAL);
    }
    Maps tm;
    tm.x = make_map(enc, x, SEQ, DM, 128, 64, CU_TENSOR_MAP_SWIZZLE_128B);
    tm.wqkv = make_map(enc, wqkv, DM, 3 * DM, 32, 64, CU_TENSOR_MAP_SWIZZLE_128B);
    tm.w1 = make_map(enc, w1, DM, FF, 32, 64, CU_TENSOR_MAP_SWIZZLE_128B);
    tm.h = make_map(enc, p_h, SEQ, FF, 64, 64, CU_TENSOR_MAP_SWIZZLE_128B);
    tm.o = make_map(enc, p_o, SEQ, DM, 64, 64, CU_TENSOR_MAP_SWIZZLE_128B);
    tm.wo = make_map(enc, wo, DM, DM, 64, 32, CU_TENSOR_MAP_SWIZZLE_64B);
    tm.w2 = make_map(enc, w2, FF, DM, 64, 32, CU_TENSOR_MAP_SWIZZLE_64B);
    k_fused<<<128, 512, SM_TOTAL, cudaStreamPerThread>>>(tm, x, (const uint8_t*)wqkv, (const uint8_t*)w1, (const uint8_t*)w2,
                                                         (const uint8_t*)wo, b1, b2, out);
}
```

```cpp
#include <cuda_runtime.h>
#include <cuda_bf16.h>
#include <cuda.h>
#include <stdint.h>

namespace {

constexpr int SEQ = 2048, DM = 640, FF = 1536;
constexpr float LN_EPS = 1e-5f;

constexpr int IMG_BYTES = 256 * 384;
constexpr uint32_t EMU_MASK = 0xD5D5u;
constexpr float SAFE_BOUND = 80.0f;
#define XV_IT 1
#define PACE_NS 200
constexpr float QSCALE = 0.22360679774997896f * 1.4426950408889634f;

__device__ float4 g_stat[SEQ];
__device__ float2 g_csp[16 * 1728];
__device__ __align__(1024) uint8_t g_img[96 * IMG_BYTES + 1024];
__device__ float g_nrm[64 * SEQ];
__device__ __align__(1024) __nv_bfloat16 g_h[SEQ * FF];
__device__ __align__(1024) __nv_bfloat16 g_o[SEQ * DM];
constexpr int CNT_ST = 0, CNT_QKV = 16, CNT_H = 24, CNT_O = 40, CNT_CS = 44, CNT_CS2 = 52;
__device__ uint32_t g_cnt[60 * 32];
__device__ uint32_t g_epoch;

#define TL(kern, slot) do { } while (0)
#define IT(row, i) do { } while (0)

__device__ __forceinline__ uint32_t smem_u32(const void* p) { return (uint32_t)__cvta_generic_to_shared(p); }
__device__ __forceinline__ void mbar_init(uint32_t bar, int cnt) {
    asm volatile("mbarrier.init.shared::cta.b64 [%0], %1;" ::"r"(bar), "r"(cnt));
}
__device__ __forceinline__ void mbar_expect_tx(uint32_t bar, uint32_t bytes) {
    asm volatile("mbarrier.arrive.expect_tx.shared::cta.b64 _, [%0], %1;" ::"r"(bar), "r"(bytes) : "memory");
}
__device__ __forceinline__ void mbar_wait(uint32_t bar, uint32_t parity) {
    asm volatile("{\n.reg .pred p;\n.reg .u32 n;\nmov.u32 n, 0;\n"
                 "WAIT_LOOP:\nmbarrier.try_wait.parity.shared::cta.b64 p, [%0], %1;\n@p bra WAIT_DONE;\n"
                 "add.u32 n, n, 1;\nsetp.lt.u32 p, n, 4194304;\n@p bra WAIT_LOOP;\nWAIT_DONE:\n}"
                 ::"r"(bar), "r"(parity) : "memory");
}
__device__ __forceinline__ void mbar_arrive(uint32_t bar) {
    asm volatile("mbarrier.arrive.shared::cta.b64 _, [%0];" ::"r"(bar) : "memory");
}
__device__ __forceinline__ void mbar_arrive_cluster(uint32_t bar, uint32_t cta) {
    asm volatile("{\n.reg .b32 ra;\nmapa.shared::cluster.u32 ra, %0, %1;\n"
                 "mbarrier.arrive.shared::cluster.b64 _, [ra];\n}" ::"r"(bar), "r"(cta) : "memory");
}
__device__ __forceinline__ void fence_barrier_init() { asm volatile("fence.mbarrier_init.release.cluster;" ::: "memory"); }
__device__ __forceinline__ void fence_proxy_async() { asm volatile("fence.proxy.async.shared::cta;" ::: "memory"); }
__device__ __forceinline__ void cluster_sync() {
    asm volatile("barrier.cluster.arrive.release.aligned;\nbarrier.cluster.wait.acquire.aligned;" ::: "memory");
}
__device__ __forceinline__ bool elect_one() {
    uint32_t pred;
    asm volatile("{\n.reg .pred p;\nelect.sync _|p, 0xFFFFFFFF;\nselp.b32 %0, 1, 0, p;\n}" : "=r"(pred));
    return pred != 0;
}
__device__ __forceinline__ void pdl_launch() { asm volatile("griddepcontrol.launch_dependents;" ::: "memory"); }
__device__ __forceinline__ void pdl_wait() { asm volatile("griddepcontrol.wait;" ::: "memory"); }
__device__ __forceinline__ void prefetch_map(const CUtensorMap* m) {
    asm volatile("prefetch.tensormap [%0];" ::"l"(m) : "memory");
}
__device__ __forceinline__ void tma_load(uint32_t dst, const CUtensorMap* m, int c0, int c1, uint32_t bar) {
    asm volatile("cp.async.bulk.tensor.2d.shared::cluster.global.mbarrier::complete_tx::bytes [%0], [%1, {%3, %4}], [%2];"
                 ::"r"(dst), "l"(m), "r"(bar), "r"(c0), "r"(c1) : "memory");
}
__device__ __forceinline__ void tma_load_mc(uint32_t dst, const CUtensorMap* m, int c0, int c1, uint32_t bar, uint16_t mask) {
    asm volatile("cp.async.bulk.tensor.2d.shared::cluster.global.mbarrier::complete_tx::bytes.multicast::cluster"
                 " [%0], [%1, {%3, %4}], [%2], %5;"
                 ::"r"(dst), "l"(m), "r"(bar), "r"(c0), "r"(c1), "h"(mask) : "memory");
}
__device__ __forceinline__ void tma_store(const CUtensorMap* m, uint32_t src, int c0, int c1) {
    asm volatile("cp.async.bulk.tensor.2d.global.shared::cta.bulk_group [%0, {%2, %3}], [%1];"
                 ::"l"(m), "r"(src), "r"(c0), "r"(c1) : "memory");
}
__device__ __forceinline__ void bulk_commit() { asm volatile("cp.async.bulk.commit_group;" ::: "memory"); }
__device__ __forceinline__ void bulk_wait_all() { asm volatile("cp.async.bulk.wait_group 0;" ::: "memory"); }
__device__ __forceinline__ void bulk_load(uint32_t dst, const void* src, uint32_t bytes, uint32_t bar) {
    asm volatile("cp.async.bulk.shared::cluster.global.mbarrier::complete_tx::bytes [%0], [%1], %2, [%3];"
                 ::"r"(dst), "l"(src), "r"(bytes), "r"(bar) : "memory");
}
__device__ __forceinline__ void prefetch_l2(const void* p, uint32_t bytes) {
    asm volatile("cp.async.bulk.prefetch.L2.global [%0], %1;" ::"l"(p), "r"(bytes) : "memory");
}
__device__ __forceinline__ void tma_prefetch_l2(const CUtensorMap* m, int c0, int c1) {
    asm volatile("cp.async.bulk.prefetch.tensor.2d.L2.global.tile [%0, {%1, %2}];" ::"l"(m), "r"(c0), "r"(c1) : "memory");
}
__device__ __forceinline__ void wg_fence() { asm volatile("wgmma.fence.sync.aligned;" ::: "memory"); }
__device__ __forceinline__ void wg_commit() { asm volatile("wgmma.commit_group.sync.aligned;" ::: "memory"); }
template <int N> __device__ __forceinline__ void wg_wait() {
    asm volatile("wgmma.wait_group.sync.aligned %0;" ::"n"(N) : "memory");
}
template <int N> __device__ __forceinline__ void reg_alloc() { asm volatile("setmaxnreg.inc.sync.aligned.u32 %0;" ::"n"(N)); }
template <int N> __device__ __forceinline__ void reg_dealloc() { asm volatile("setmaxnreg.dec.sync.aligned.u32 %0;" ::"n"(N)); }
template <int N> __device__ __forceinline__ void fence_regs(float (&d)[N]) {
#pragma unroll
    for (int i = 0; i < N; i++) asm volatile("" : "+f"(d[i])::"memory");
}
__device__ __forceinline__ uint64_t make_desc(uint32_t addr, uint32_t lbo, uint32_t sbo, uint32_t swz) {
    return (uint64_t)((addr & 0x3FFFF) >> 4) | ((uint64_t)(lbo >> 4) << 16) | ((uint64_t)(sbo >> 4) << 32) |
           ((uint64_t)swz << 62);
}
__device__ __forceinline__ uint32_t pack_bf16(float lo, float hi) {
    uint32_t r;
    asm("cvt.rn.bf16x2.f32 %0, %1, %2;" : "=r"(r) : "f"(hi), "f"(lo));
    return r;
}
__device__ __forceinline__ float ex2(float x) {
    float r;
    asm("ex2.approx.ftz.f32 %0, %1;" : "=f"(r) : "f"(x));
    return r;
}
__device__ __forceinline__ float bf_lo(uint32_t v) { return __uint_as_float(v << 16); }
__device__ __forceinline__ float bf_hi(uint32_t v) { return __uint_as_float(v & 0xFFFF0000u); }
__device__ __forceinline__ void stmatrix_x4(uint32_t addr, uint32_t r0, uint32_t r1, uint32_t r2, uint32_t r3) {
    asm volatile("stmatrix.sync.aligned.m8n8.x4.shared.b16 [%0], {%1, %2, %3, %4};"
                 ::"r"(addr), "r"(r0), "r"(r1), "r"(r2), "r"(r3) : "memory");
}

__device__ __forceinline__ void wgmma_n200_ss_tb(float (&d)[100], uint64_t descA, uint64_t descB, int scaleD) {
    asm volatile("{\n.reg .pred p;\nsetp.ne.b32 p, %102, 0;\n"
        "wgmma.mma_async.sync.aligned.m64n200k16.f32.bf16.bf16 {"
        "%0, %1, %2, %3, %4, %5, %6, %7, %8, %9, %10, %11, %12, %13, %14, %15, "
        "%16, %17, %18, %19, %20, %21, %22, %23, %24, %25, %26, %27, %28, %29, %30, %31, "
        "%32, %33, %34, %35, %36, %37, %38, %39, %40, %41, %42, %43, %44, %45, %46, %47, "
        "%48, %49, %50, %51, %52, %53, %54, %55, %56, %57, %58, %59, %60, %61, %62, %63, "
        "%64, %65, %66, %67, %68, %69, %70, %71, %72, %73, %74, %75, %76, %77, %78, %79, "
        "%80, %81, %82, %83, %84, %85, %86, %87, %88, %89, %90, %91, %92, %93, %94, %95, "
        "%96, %97, %98, %99}, "
        "%100, %101, p, 1, 1, 0, 1;\n}\n"
        : "+f"(d[0]), "+f"(d[1]), "+f"(d[2]), "+f"(d[3]), "+f"(d[4]), "+f"(d[5]), "+f"(d[6]), "+f"(d[7]),
          "+f"(d[8]), "+f"(d[9]), "+f"(d[10]), "+f"(d[11]), "+f"(d[12]), "+f"(d[13]), "+f"(d[14]), "+f"(d[15]),
          "+f"(d[16]), "+f"(d[17]), "+f"(d[18]), "+f"(d[19]), "+f"(d[20]), "+f"(d[21]), "+f"(d[22]), "+f"(d[23]),
          "+f"(d[24]), "+f"(d[25]), "+f"(d[26]), "+f"(d[27]), "+f"(d[28]), "+f"(d[29]), "+f"(d[30]), "+f"(d[31]),
          "+f"(d[32]), "+f"(d[33]), "+f"(d[34]), "+f"(d[35]), "+f"(d[36]), "+f"(d[37]), "+f"(d[38]), "+f"(d[39]),
          "+f"(d[40]), "+f"(d[41]), "+f"(d[42]), "+f"(d[43]), "+f"(d[44]), "+f"(d[45]), "+f"(d[46]), "+f"(d[47]),
          "+f"(d[48]), "+f"(d[49]), "+f"(d[50]), "+f"(d[51]), "+f"(d[52]), "+f"(d[53]), "+f"(d[54]), "+f"(d[55]),
          "+f"(d[56]), "+f"(d[57]), "+f"(d[58]), "+f"(d[59]), "+f"(d[60]), "+f"(d[61]), "+f"(d[62]), "+f"(d[63]),
          "+f"(d[64]), "+f"(d[65]), "+f"(d[66]), "+f"(d[67]), "+f"(d[68]), "+f"(d[69]), "+f"(d[70]), "+f"(d[71]),
          "+f"(d[72]), "+f"(d[73]), "+f"(d[74]), "+f"(d[75]), "+f"(d[76]), "+f"(d[77]), "+f"(d[78]), "+f"(d[79]),
          "+f"(d[80]), "+f"(d[81]), "+f"(d[82]), "+f"(d[83]), "+f"(d[84]), "+f"(d[85]), "+f"(d[86]), "+f"(d[87]),
          "+f"(d[88]), "+f"(d[89]), "+f"(d[90]), "+f"(d[91]), "+f"(d[92]), "+f"(d[93]), "+f"(d[94]), "+f"(d[95]),
          "+f"(d[96]), "+f"(d[97]), "+f"(d[98]), "+f"(d[99])
        : "l"(descA), "l"(descB), "r"(scaleD));
}

__device__ __forceinline__ void wgmma_n40_ss_tb(float (&d)[20], uint64_t descA, uint64_t descB, int scaleD) {
    asm volatile("{\n.reg .pred p;\nsetp.ne.b32 p, %22, 0;\n"
        "wgmma.mma_async.sync.aligned.m64n40k16.f32.bf16.bf16 {"
        "%0, %1, %2, %3, %4, %5, %6, %7, %8, %9, %10, %11, %12, %13, %14, %15, "
        "%16, %17, %18, %19}, "
        "%20, %21, p, 1, 1, 0, 1;\n}\n"
        : "+f"(d[0]), "+f"(d[1]), "+f"(d[2]), "+f"(d[3]), "+f"(d[4]), "+f"(d[5]), "+f"(d[6]), "+f"(d[7]),
          "+f"(d[8]), "+f"(d[9]), "+f"(d[10]), "+f"(d[11]), "+f"(d[12]), "+f"(d[13]), "+f"(d[14]), "+f"(d[15]),
          "+f"(d[16]), "+f"(d[17]), "+f"(d[18]), "+f"(d[19])
        : "l"(descA), "l"(descB), "r"(scaleD));
}

__device__ __forceinline__ void wgmma_n192_ss_tb(float (&d)[96], uint64_t descA, uint64_t descB, int scaleD) {
    asm volatile("{\n.reg .pred p;\nsetp.ne.b32 p, %98, 0;\n"
        "wgmma.mma_async.sync.aligned.m64n192k16.f32.bf16.bf16 {"
        "%0, %1, %2, %3, %4, %5, %6, %7, %8, %9, %10, %11, %12, %13, %14, %15, "
        "%16, %17, %18, %19, %20, %21, %22, %23, %24, %25, %26, %27, %28, %29, %30, %31, "
        "%32, %33, %34, %35, %36, %37, %38, %39, %40, %41, %42, %43, %44, %45, %46, %47, "
        "%48, %49, %50, %51, %52, %53, %54, %55, %56, %57, %58, %59, %60, %61, %62, %63, "
        "%64, %65, %66, %67, %68, %69, %70, %71, %72, %73, %74, %75, %76, %77, %78, %79, "
        "%80, %81, %82, %83, %84, %85, %86, %87, %88, %89, %90, %91, %92, %93, %94, %95}, "
        "%96, %97, p, 1, 1, 0, 1;\n}\n"
        : "+f"(d[0]), "+f"(d[1]), "+f"(d[2]), "+f"(d[3]), "+f"(d[4]), "+f"(d[5]), "+f"(d[6]), "+f"(d[7]),
          "+f"(d[8]), "+f"(d[9]), "+f"(d[10]), "+f"(d[11]), "+f"(d[12]), "+f"(d[13]), "+f"(d[14]), "+f"(d[15]),
          "+f"(d[16]), "+f"(d[17]), "+f"(d[18]), "+f"(d[19]), "+f"(d[20]), "+f"(d[21]), "+f"(d[22]), "+f"(d[23]),
          "+f"(d[24]), "+f"(d[25]), "+f"(d[26]), "+f"(d[27]), "+f"(d[28]), "+f"(d[29]), "+f"(d[30]), "+f"(d[31]),
          "+f"(d[32]), "+f"(d[33]), "+f"(d[34]), "+f"(d[35]), "+f"(d[36]), "+f"(d[37]), "+f"(d[38]), "+f"(d[39]),
          "+f"(d[40]), "+f"(d[41]), "+f"(d[42]), "+f"(d[43]), "+f"(d[44]), "+f"(d[45]), "+f"(d[46]), "+f"(d[47]),
          "+f"(d[48]), "+f"(d[49]), "+f"(d[50]), "+f"(d[51]), "+f"(d[52]), "+f"(d[53]), "+f"(d[54]), "+f"(d[55]),
          "+f"(d[56]), "+f"(d[57]), "+f"(d[58]), "+f"(d[59]), "+f"(d[60]), "+f"(d[61]), "+f"(d[62]), "+f"(d[63]),
          "+f"(d[64]), "+f"(d[65]), "+f"(d[66]), "+f"(d[67]), "+f"(d[68]), "+f"(d[69]), "+f"(d[70]), "+f"(d[71]),
          "+f"(d[72]), "+f"(d[73]), "+f"(d[74]), "+f"(d[75]), "+f"(d[76]), "+f"(d[77]), "+f"(d[78]), "+f"(d[79]),
          "+f"(d[80]), "+f"(d[81]), "+f"(d[82]), "+f"(d[83]), "+f"(d[84]), "+f"(d[85]), "+f"(d[86]), "+f"(d[87]),
          "+f"(d[88]), "+f"(d[89]), "+f"(d[90]), "+f"(d[91]), "+f"(d[92]), "+f"(d[93]), "+f"(d[94]), "+f"(d[95])
        : "l"(descA), "l"(descB), "r"(scaleD));
}

__device__ __forceinline__ void wgmma_n192_ss_tb_z(float (&d)[96], uint64_t descA, uint64_t descB) {
    asm volatile("{\n.reg .pred p;\nsetp.ne.b32 p, 0, 0;\n"
        "wgmma.mma_async.sync.aligned.m64n192k16.f32.bf16.bf16 {"
        "%0, %1, %2, %3, %4, %5, %6, %7, %8, %9, %10, %11, %12, %13, %14, %15, "
        "%16, %17, %18, %19, %20, %21, %22, %23, %24, %25, %26, %27, %28, %29, %30, %31, "
        "%32, %33, %34, %35, %36, %37, %38, %39, %40, %41, %42, %43, %44, %45, %46, %47, "
        "%48, %49, %50, %51, %52, %53, %54, %55, %56, %57, %58, %59, %60, %61, %62, %63, "
        "%64, %65, %66, %67, %68, %69, %70, %71, %72, %73, %74, %75, %76, %77, %78, %79, "
        "%80, %81, %82, %83, %84, %85, %86, %87, %88, %89, %90, %91, %92, %93, %94, %95}, "
        "%96, %97, p, 1, 1, 0, 1;\n}\n"
        : "=f"(d[0]), "=f"(d[1]), "=f"(d[2]), "=f"(d[3]), "=f"(d[4]), "=f"(d[5]), "=f"(d[6]), "=f"(d[7]),
          "=f"(d[8]), "=f"(d[9]), "=f"(d[10]), "=f"(d[11]), "=f"(d[12]), "=f"(d[13]), "=f"(d[14]), "=f"(d[15]),
          "=f"(d[16]), "=f"(d[17]), "=f"(d[18]), "=f"(d[19]), "=f"(d[20]), "=f"(d[21]), "=f"(d[22]), "=f"(d[23]),
          "=f"(d[24]), "=f"(d[25]), "=f"(d[26]), "=f"(d[27]), "=f"(d[28]), "=f"(d[29]), "=f"(d[30]), "=f"(d[31]),
          "=f"(d[32]), "=f"(d[33]), "=f"(d[34]), "=f"(d[35]), "=f"(d[36]), "=f"(d[37]), "=f"(d[38]), "=f"(d[39]),
          "=f"(d[40]), "=f"(d[41]), "=f"(d[42]), "=f"(d[43]), "=f"(d[44]), "=f"(d[45]), "=f"(d[46]), "=f"(d[47]),
          "=f"(d[48]), "=f"(d[49]), "=f"(d[50]), "=f"(d[51]), "=f"(d[52]), "=f"(d[53]), "=f"(d[54]), "=f"(d[55]),
          "=f"(d[56]), "=f"(d[57]), "=f"(d[58]), "=f"(d[59]), "=f"(d[60]), "=f"(d[61]), "=f"(d[62]), "=f"(d[63]),
          "=f"(d[64]), "=f"(d[65]), "=f"(d[66]), "=f"(d[67]), "=f"(d[68]), "=f"(d[69]), "=f"(d[70]), "=f"(d[71]),
          "=f"(d[72]), "=f"(d[73]), "=f"(d[74]), "=f"(d[75]), "=f"(d[76]), "=f"(d[77]), "=f"(d[78]), "=f"(d[79]),
          "=f"(d[80]), "=f"(d[81]), "=f"(d[82]), "=f"(d[83]), "=f"(d[84]), "=f"(d[85]), "=f"(d[86]), "=f"(d[87]),
          "=f"(d[88]), "=f"(d[89]), "=f"(d[90]), "=f"(d[91]), "=f"(d[92]), "=f"(d[93]), "=f"(d[94]), "=f"(d[95])
        : "l"(descA), "l"(descB));
}

__device__ __forceinline__ void wgmma_n160_ss_tb(float (&d)[80], uint64_t descA, uint64_t descB, int scaleD) {
    asm volatile("{\n.reg .pred p;\nsetp.ne.b32 p, %82, 0;\n"
        "wgmma.mma_async.sync.aligned.m64n160k16.f32.bf16.bf16 {"
        "%0, %1, %2, %3, %4, %5, %6, %7, %8, %9, %10, %11, %12, %13, %14, %15, "
        "%16, %17, %18, %19, %20, %21, %22, %23, %24, %25, %26, %27, %28, %29, %30, %31, "
        "%32, %33, %34, %35, %36, %37, %38, %39, %40, %41, %42, %43, %44, %45, %46, %47, "
        "%48, %49, %50, %51, %52, %53, %54, %55, %56, %57, %58, %59, %60, %61, %62, %63, "
        "%64, %65, %66, %67, %68, %69, %70, %71, %72, %73, %74, %75, %76, %77, %78, %79}, "
        "%80, %81, p, 1, 1, 0, 1;\n}\n"
        : "+f"(d[0]), "+f"(d[1]), "+f"(d[2]), "+f"(d[3]), "+f"(d[4]), "+f"(d[5]), "+f"(d[6]), "+f"(d[7]),
          "+f"(d[8]), "+f"(d[9]), "+f"(d[10]), "+f"(d[11]), "+f"(d[12]), "+f"(d[13]), "+f"(d[14]), "+f"(d[15]),
          "+f"(d[16]), "+f"(d[17]), "+f"(d[18]), "+f"(d[19]), "+f"(d[20]), "+f"(d[21]), "+f"(d[22]), "+f"(d[23]),
          "+f"(d[24]), "+f"(d[25]), "+f"(d[26]), "+f"(d[27]), "+f"(d[28]), "+f"(d[29]), "+f"(d[30]), "+f"(d[31]),
          "+f"(d[32]), "+f"(d[33]), "+f"(d[34]), "+f"(d[35]), "+f"(d[36]), "+f"(d[37]), "+f"(d[38]), "+f"(d[39]),
          "+f"(d[40]), "+f"(d[41]), "+f"(d[42]), "+f"(d[43]), "+f"(d[44]), "+f"(d[45]), "+f"(d[46]), "+f"(d[47]),
          "+f"(d[48]), "+f"(d[49]), "+f"(d[50]), "+f"(d[51]), "+f"(d[52]), "+f"(d[53]), "+f"(d[54]), "+f"(d[55]),
          "+f"(d[56]), "+f"(d[57]), "+f"(d[58]), "+f"(d[59]), "+f"(d[60]), "+f"(d[61]), "+f"(d[62]), "+f"(d[63]),
          "+f"(d[64]), "+f"(d[65]), "+f"(d[66]), "+f"(d[67]), "+f"(d[68]), "+f"(d[69]), "+f"(d[70]), "+f"(d[71]),
          "+f"(d[72]), "+f"(d[73]), "+f"(d[74]), "+f"(d[75]), "+f"(d[76]), "+f"(d[77]), "+f"(d[78]), "+f"(d[79])
        : "l"(descA), "l"(descB), "r"(scaleD));
}

__device__ __forceinline__ void wgmma_n64_ss(float (&d)[32], uint64_t descA, uint64_t descB, int scaleD) {
    asm volatile("{\n.reg .pred p;\nsetp.ne.b32 p, %34, 0;\n"
        "wgmma.mma_async.sync.aligned.m64n64k16.f32.bf16.bf16 {"
        "%0, %1, %2, %3, %4, %5, %6, %7, %8, %9, %10, %11, %12, %13, %14, %15, "
        "%16, %17, %18, %19, %20, %21, %22, %23, %24, %25, %26, %27, %28, %29, %30, %31}, "
        "%32, %33, p, 1, 1, 0, 0;\n}\n"
        : "+f"(d[0]), "+f"(d[1]), "+f"(d[2]), "+f"(d[3]), "+f"(d[4]), "+f"(d[5]), "+f"(d[6]), "+f"(d[7]),
          "+f"(d[8]), "+f"(d[9]), "+f"(d[10]), "+f"(d[11]), "+f"(d[12]), "+f"(d[13]), "+f"(d[14]), "+f"(d[15]),
          "+f"(d[16]), "+f"(d[17]), "+f"(d[18]), "+f"(d[19]), "+f"(d[20]), "+f"(d[21]), "+f"(d[22]), "+f"(d[23]),
          "+f"(d[24]), "+f"(d[25]), "+f"(d[26]), "+f"(d[27]), "+f"(d[28]), "+f"(d[29]), "+f"(d[30]), "+f"(d[31])
        : "l"(descA), "l"(descB), "r"(scaleD));
}

__device__ __forceinline__ void wgmma_n64_ss_z(float (&d)[32], uint64_t descA, uint64_t descB) {
    asm volatile("{\n.reg .pred p;\nsetp.ne.b32 p, 0, 0;\n"
        "wgmma.mma_async.sync.aligned.m64n64k16.f32.bf16.bf16 {"
        "%0, %1, %2, %3, %4, %5, %6, %7, %8, %9, %10, %11, %12, %13, %14, %15, "
        "%16, %17, %18, %19, %20, %21, %22, %23, %24, %25, %26, %27, %28, %29, %30, %31}, "
        "%32, %33, p, 1, 1, 0, 0;\n}\n"
        : "=f"(d[0]), "=f"(d[1]), "=f"(d[2]), "=f"(d[3]), "=f"(d[4]), "=f"(d[5]), "=f"(d[6]), "=f"(d[7]),
          "=f"(d[8]), "=f"(d[9]), "=f"(d[10]), "=f"(d[11]), "=f"(d[12]), "=f"(d[13]), "=f"(d[14]), "=f"(d[15]),
          "=f"(d[16]), "=f"(d[17]), "=f"(d[18]), "=f"(d[19]), "=f"(d[20]), "=f"(d[21]), "=f"(d[22]), "=f"(d[23]),
          "=f"(d[24]), "=f"(d[25]), "=f"(d[26]), "=f"(d[27]), "=f"(d[28]), "=f"(d[29]), "=f"(d[30]), "=f"(d[31])
        : "l"(descA), "l"(descB));
}

__device__ __forceinline__ void wgmma_n24_rs_tb(float (&d)[12], uint32_t a0, uint32_t a1, uint32_t a2, uint32_t a3, uint64_t descB, int scaleD) {
    asm volatile("{\n.reg .pred p;\nsetp.ne.b32 p, %17, 0;\n"
        "wgmma.mma_async.sync.aligned.m64n24k16.f32.bf16.bf16 {"
        "%0, %1, %2, %3, %4, %5, %6, %7, %8, %9, %10, %11}, "
        "{%12, %13, %14, %15}, %16, p, 1, 1, 1;\n}\n"
        : "+f"(d[0]), "+f"(d[1]), "+f"(d[2]), "+f"(d[3]), "+f"(d[4]), "+f"(d[5]), "+f"(d[6]), "+f"(d[7]),
          "+f"(d[8]), "+f"(d[9]), "+f"(d[10]), "+f"(d[11])
        : "r"(a0), "r"(a1), "r"(a2), "r"(a3), "l"(descB), "r"(scaleD));
}

__device__ __forceinline__ void cnt_signal(int idx) {
    asm volatile("fence.acq_rel.gpu;\nred.relaxed.gpu.global.add.u32 [%0], 1;"
                 ::"l"(g_cnt + idx * 32) : "memory");
}
__device__ __forceinline__ void cnt_wait(int idx, uint32_t target) {
    const uint32_t* p = g_cnt + idx * 32;
#pragma unroll 1
    for (uint32_t i = 0; i < (1u << 22); i++) {
        uint32_t v;
        asm volatile("ld.acquire.gpu.global.u32 %0, [%1];" : "=r"(v) : "l"(p) : "memory");
        if ((int32_t)(v - target) >= 0) break;
    }
    asm volatile("fence.proxy.async.global;" ::: "memory");
}
__device__ __forceinline__ void cluster_arrive() { asm volatile("barrier.cluster.arrive.release.aligned;" ::: "memory"); }
__device__ __forceinline__ void cluster_arrive_relaxed() { asm volatile("barrier.cluster.arrive.relaxed.aligned;" ::: "memory"); }
__device__ __forceinline__ void cluster_wait() { asm volatile("barrier.cluster.wait.acquire.aligned;" ::: "memory"); }
__device__ __forceinline__ void bulk_wait_read() { asm volatile("cp.async.bulk.wait_group.read 0;" ::: "memory"); }

__device__ __forceinline__ float gelu_half(float hx) {
    const float u = hx * fmaf(hx * hx, 8.f * 0.035677408136300125f, 2.f * 0.7978845608028654f);
    float t;
    asm("tanh.approx.f32 %0, %1;" : "=f"(t) : "f"(u));
    return fmaf(hx, t, hx);
}
__device__ __forceinline__ void release_stage(uint32_t bar, uint32_t peer, int lane) {
    if (lane == 0) { mbar_arrive(bar); mbar_arrive_cluster(bar, peer); }
}

constexpr int SM_RING = 163840;
constexpr int SM_Q = 0, SM_ZERO = 24576, SM_K = SM_ZERO + 3072, SM_V = SM_K + IMG_BYTES;
constexpr int G2_STAGE = 8192 + 20480;
__device__ __forceinline__ uint32_t g2_slot(int i) { return SM_K + ((0x4326150 >> (4 * i)) & 7) * G2_STAGE; }
constexpr int SM_MISC = 229376;
constexpr int SM_BIAS = SM_MISC, SM_RED = SM_BIAS + 384, SM_BAR = SM_RED + 128;
constexpr int B_A = 0, B_F1 = 10, B_E1 = 14, B_F2 = 18, B_E2 = 23, B_KV = 28, B_Q = 45, B_F3 = 47, B_E3 = 55, B_ST = 63, B_STAT = 65, B_AUX = 66, B_AUX2 = 67, B_DEAD = 68, B_PF = 70, B_COUNT = 73;
constexpr int SM_EPOCH = SM_BAR + 584, SM_SAFE = SM_EPOCH + 4;
constexpr int SM_CS = SM_EPOCH + 8;
constexpr int SM_TOTAL = SM_CS + 1728;
static_assert(SM_TOTAL <= 232448, "shared memory budget");

struct Maps { CUtensorMap x, wqkv, w1, h, o, wo, w2; };

__device__ __forceinline__ uint32_t bf2_fma(uint32_t a, uint32_t b, uint32_t c) {
    uint32_t r;
    asm("fma.rn.bf16x2 %0, %1, %2, %3;" : "=r"(r) : "r"(a), "r"(b), "r"(c));
    return r;
}
__device__ __forceinline__ uint32_t lop_and_or(uint32_t a, uint32_t m, uint32_t o) {
    uint32_t r;
    asm("lop3.b32 %0, %1, %2, %3, 0xEA;" : "=r"(r) : "r"(a), "r"(m), "r"(o));
    return r;
}
struct ExpConst { uint32_t mask, slope; };
__device__ __forceinline__ ExpConst make_exp_const() {
    ExpConst k;
    asm volatile("mov.b32 %0, 0x007F007F;" : "=r"(k.mask));
    asm volatile("mov.b32 %0, 0x3EF83EF8;" : "=r"(k.slope));
    return k;
}
__device__ __forceinline__ uint32_t exp2_pair_fma(float t0, float t1, const ExpConst& k) {
    const uint32_t L = __byte_perm(__float_as_uint(t0), __float_as_uint(t1), 0x6521);
    const uint32_t g = lop_and_or(L, k.mask, 0x3F803F80u);
    const uint32_t u = bf2_fma(g, k.slope, 0xBF37BF37u);
    const uint32_t e = bf2_fma(u, u, 0xBD71BD71u);
    return bf2_fma(L, e, L);
}
template <int SHIFT>
__device__ __forceinline__ void exp_tile(const float (&s)[32], uint32_t (&p)[16], const ExpConst& k) {
#pragma unroll
    for (int b = 0; b < 8; b++) {
        if ((EMU_MASK >> (b + SHIFT)) & 1) {
            p[2 * b] = exp2_pair_fma(s[4 * b], s[4 * b + 1], k);
            p[2 * b + 1] = exp2_pair_fma(s[4 * b + 2], s[4 * b + 3], k);
        } else {
            p[2 * b] = pack_bf16(ex2(s[4 * b]), ex2(s[4 * b + 1]));
            p[2 * b + 1] = pack_bf16(ex2(s[4 * b + 2]), ex2(s[4 * b + 3]));
        }
    }
}

__device__ __forceinline__ void qk_tile(float (&s)[32], uint64_t dQ, uint64_t dQ2, uint64_t dK) {
    wg_fence();
    wgmma_n64_ss_z(s, dQ, dK);
    wgmma_n64_ss(s, dQ2, dK + 16, 1);
    wg_commit();
}
__device__ __forceinline__ void pv_tile(float (&o)[12], const uint32_t (&p)[16], uint64_t dV) {
    wg_fence();
#pragma unroll
    for (int ks = 0; ks < 4; ks++)
        wgmma_n24_rs_tb(o, p[4 * ks], p[4 * ks + 1], p[4 * ks + 2], p[4 * ks + 3], dV + ks * 48, 1);
    wg_commit();
}
__device__ __forceinline__ void store_o(const float (&o)[12], int h, int rbase, int lane) {
    const int g = lane >> 2, c = lane & 3;
    const bool odd = h & 1;
    const int lsrc = (lane & ~3) | (odd ? 0 : 2);
    const float i0 = 1.f / __shfl_sync(~0u, o[8], lsrc), i1 = 1.f / __shfl_sync(~0u, o[10], lsrc);
    __nv_bfloat16* dst = g_o + (size_t)(rbase + g) * DM + h * 20;
    const int d0 = (odd ? 4 : 0) + 2 * c, d1 = d0 + 8, d2 = odd ? 2 * c - 4 : 16 + 2 * c;
    *(uint32_t*)(dst + d0) = pack_bf16(o[0] * i0, o[1] * i0);
    *(uint32_t*)(dst + d1) = pack_bf16(o[4] * i0, o[5] * i0);
    *(uint32_t*)(dst + 8 * DM + d0) = pack_bf16(o[2] * i1, o[3] * i1);
    *(uint32_t*)(dst + 8 * DM + d1) = pack_bf16(o[6] * i1, o[7] * i1);
    if (odd ? (c >= 2) : (c < 2)) {
        *(uint32_t*)(dst + d2) = pack_bf16(o[8] * i0, o[9] * i0);
        *(uint32_t*)(dst + 8 * DM + d2) = pack_bf16(o[10] * i1, o[11] * i1);
    }
}

__device__ __forceinline__ void attn_rows_maxshift(uint32_t sK, uint32_t barKV, uint64_t dQ, uint64_t dQ2, int h, int rbase) {
    const int lane = threadIdx.x & 31;
    const uint64_t dK0 = make_desc(sK, 128, 384, 0), dV0 = make_desc(sK + IMG_BYTES, 384, 128, 0);
    float o[12], s[32];
    uint32_t p[16];
#pragma unroll
    for (int i = 0; i < 12; i++) o[i] = 0.f;
    float m0 = -3.0e38f, m1 = -3.0e38f;
    mbar_wait(barKV + 128, 0);
#pragma unroll 1
    for (int t = 0; t < 32; t++) {
        mbar_wait(barKV + (t >> 1) * 8, 0);
        qk_tile(s, dQ, dQ2, dK0 + t * 192);
        wg_wait<0>();
        fence_regs(s);
        const uint32_t mask = EMU_MASK >> ((t & 1) * 8);
        float n0 = m0, n1 = m1;
#pragma unroll
        for (int b = 0; b < 8; b++) {
            const bool emu = (mask >> b) & 1;
            const float f = emu ? 0.5f : 1.f, off = emu ? -383.00390625f : 0.f;
#pragma unroll
            for (int i = 0; i < 4; i++) s[4 * b + i] = fmaf(s[4 * b + i], f, off);
            n0 = fmaxf(n0, fmaxf(s[4 * b], s[4 * b + 1]));
            n1 = fmaxf(n1, fmaxf(s[4 * b + 2], s[4 * b + 3]));
        }
        n0 = fmaxf(n0, __shfl_xor_sync(~0u, n0, 1)); n0 = fmaxf(n0, __shfl_xor_sync(~0u, n0, 2));
        n1 = fmaxf(n1, __shfl_xor_sync(~0u, n1, 1)); n1 = fmaxf(n1, __shfl_xor_sync(~0u, n1, 2));
        const float c0 = ex2(m0 - n0), c1 = ex2(m1 - n1);
        m0 = n0; m1 = n1;
#pragma unroll
        for (int b = 0; b < 3; b++) { o[4 * b] *= c0; o[4 * b + 1] *= c0; o[4 * b + 2] *= c1; o[4 * b + 3] *= c1; }
#pragma unroll
        for (int b = 0; b < 8; b++) {
            p[2 * b] = pack_bf16(ex2(s[4 * b] - m0), ex2(s[4 * b + 1] - m0));
            p[2 * b + 1] = pack_bf16(ex2(s[4 * b + 2] - m1), ex2(s[4 * b + 3] - m1));
        }
        pv_tile(o, p, dV0 + (((t >> 1) + 7) & 15) * 384 + (t & 1) * 192);
        wg_wait<0>();
        fence_regs(o);
    }
    store_o(o, h, rbase, lane);
}

__global__ void __launch_bounds__(512, 1) __cluster_dims__(2, 1, 1)
k_fused(const __grid_constant__ Maps tm, const __nv_bfloat16* __restrict__ x, const uint8_t* __restrict__ wqkv,
        const uint8_t* __restrict__ w1, const uint8_t* __restrict__ w2, const uint8_t* __restrict__ wo,
        const __nv_bfloat16* __restrict__ b1, const __nv_bfloat16* __restrict__ b2, __nv_bfloat16* __restrict__ out) {
    extern __shared__ __align__(1024) uint8_t smem[];
    const uint32_t sb = smem_u32(smem);
    const uint32_t bar = sb + SM_BAR;
    const int warp = __shfl_sync(~0u, threadIdx.x >> 5, 0), lane = threadIdx.x & 31;
    const int wgi = warp >> 2, w4 = warp & 3, g = lane >> 2, c = lane & 3;
    const uint32_t rank = blockIdx.x & 1, peer = rank ^ 1;
    const int cl = blockIdx.x >> 1;
    const int cg = cl >> 3, rb = (cl & 7) * 2 + rank;

    if (threadIdx.x == 0) TL(0, 0);
    if (warp == 15 && lane < 4) prefetch_map(lane == 0 ? &tm.x : lane == 1 ? &tm.wqkv : lane == 2 ? &tm.w1 : &tm.h);
    if (elect_one()) {
#pragma unroll
        for (int j = 0; j < 5; j++) {
            const int i = warp * 5 + j;
            const int cnt = i >= B_PF ? 32 : (i >= B_E1 && i < B_F2) || (i >= B_E2 && i < B_KV) ? 16
                          : (i >= B_E3 && i <= B_ST + 1) || i == B_STAT || i == B_DEAD || i == B_DEAD + 1 ? 8 : i == B_AUX ? 4 : i == B_AUX2 ? 3 : 1;
            if (i < B_COUNT) mbar_init(bar + i * 8, cnt);
        }
        fence_barrier_init();
    }
    __syncthreads();
    if (threadIdx.x == 0) TL(0, 1);
    cluster_arrive_relaxed();
    cluster_wait();
    if (threadIdx.x == 0) TL(0, 3);

    {
        const uint32_t sB = sb + SM_RING;
        if (threadIdx.x == 0) TL(1, 0);
        if (wgi < 2) {
            reg_dealloc<56>();
            if (warp == 0) {
#pragma unroll 1
                for (int it = 0; it < 20; it++) {
                    const int s = it & 3;
                    const int kb = it < 2 ? it : (it & 1) ? (it + 1) >> 1 : 10;
                    if (it >= 4) mbar_wait(bar + (B_E1 + s) * 8, ((it >> 2) - 1) & 1);
                    else if (it > 0) __nanosleep(PACE_NS);
                    if (elect_one()) {
                        if (kb < 10) {
                            mbar_expect_tx(bar + (B_A + kb) * 8, 16384);
                            tma_load(sb + kb * 16384, &tm.x, kb * 64, rb * 128, bar + (B_A + kb) * 8);
                        }
                        const uint32_t dst = sB + s * 16384 + rank * 8192, fb = bar + (B_F1 + s) * 8;
                        const int c0 = cg * 240 + rank * 128;
                        mbar_expect_tx(fb, 16384);
                        tma_load_mc(dst, &tm.wqkv, c0, it * 32, fb, 3);
                        tma_load_mc(dst + 4096, &tm.wqkv, c0 + 64, it * 32, fb, 3);
                    }
                    __syncwarp();
                }
#pragma unroll 1
                for (int it = 0; it < 20; it++) {
                    const int s = it % 5;
                    if (it < 5) { if (it != 3) mbar_wait(bar + (B_E1 + (it == 4 ? 3 : it)) * 8, 0); }
                    else mbar_wait(bar + (B_E2 + s) * 8, ((it / 5) - 1) & 1);
                    if (elect_one()) {
                        const uint32_t dst = sB + s * 12288, fb = bar + (B_F2 + s) * 8;
                        mbar_expect_tx(fb, 12288);
                        if ((it & 1) == (int)rank) {
                            tma_load_mc(dst, &tm.w1, cg * 192, it * 32, fb, 3);
                            tma_load_mc(dst + 4096, &tm.w1, cg * 192 + 64, it * 32, fb, 3);
                        } else {
                            tma_load_mc(dst + 8192, &tm.w1, cg * 192 + 128, it * 32, fb, 3);
                        }
                    }
                    __syncwarp();
                }
            } else {
                const int ht = threadIdx.x - 32;
                if (ht == 160) *reinterpret_cast<volatile uint32_t*>(smem + SM_EPOCH) = *(volatile uint32_t*)&g_epoch;
                auto slab_sum = [&](const uint32_t* src, int pitch) {
                    float s0 = 0.f, s1 = 0.f;
                    uint32_t v[40];
#pragma unroll
                    for (int k = 0; k < 40; k++) v[k] = __ldg(src + k * pitch);
#pragma unroll
                    for (int k = 0; k < 40; k++) { s0 += bf_lo(v[k]); s1 += bf_hi(v[k]); }
                    return make_float2(s0, s1);
                };
                auto gather = [&](int idx) {
                    float s0 = 0.f, s1 = 0.f;
#pragma unroll
                    for (int r = 0; r < 16; r++) {
                        const float2 v = __ldcg(g_csp + r * 1728 + cg * 216 + idx);
                        s0 += v.x; s1 += v.y;
                    }
                    reinterpret_cast<float2*>(smem + SM_CS)[idx] = make_float2(s0, s1);
                };
                if (warp == 7) {
                    mbar_wait(bar + B_STAT * 8, 0);
                    if (elect_one()) cnt_signal(CNT_ST + rb);
                    __syncwarp();
                }
                if (ht < 120)
                    g_csp[rb * 1728 + cg * 216 + ht] = slab_sum(reinterpret_cast<const uint32_t*>(wqkv) + rb * 40 * 960 + cg * 120 + ht, 960);
                if (threadIdx.x == 64) IT(3, 0);
                if (threadIdx.x == 192) IT(3, 1);
                if (warp != 7) asm volatile("bar.sync 8, 192;" ::: "memory");
                const uint32_t epoch = *reinterpret_cast<volatile uint32_t*>(smem + SM_EPOCH);
                if (warp == 6) { if (elect_one()) cnt_signal(CNT_CS + cg); __syncwarp(); }

                if (threadIdx.x == 64) IT(3, 2);
                if (warp <= 4) {
                    if (lane == 0) { cnt_wait(CNT_CS + cg, (epoch + 1) * 16); cnt_wait(CNT_ST + rb, (epoch + 1) * 8); }
                    __syncwarp();
                    if (threadIdx.x == 64) IT(3, 4);
                    if (ht < 120) gather(ht);
                    __syncwarp();
                    if (threadIdx.x == 64) IT(3, 5);
                    if (lane == 0) mbar_arrive(bar + B_AUX * 8);
                }
                if (ht >= 128) {
                    g_csp[rb * 1728 + cg * 216 + 120 + (ht - 128)] = slab_sum(reinterpret_cast<const uint32_t*>(w1) + rb * 40 * 768 + cg * 96 + (ht - 128), 768);
                    reinterpret_cast<uint32_t*>(smem + SM_BIAS)[ht - 128] =
                        bf2_fma(__ldg(reinterpret_cast<const uint32_t*>(b1 + cg * 192) + (ht - 128)), 0x3F003F00u, 0x80008000u);
                    asm volatile("bar.sync 9, 96;" ::: "memory");
                    const uint32_t epoch2 = *reinterpret_cast<volatile uint32_t*>(smem + SM_EPOCH);
                    if (warp == 5) { if (elect_one()) cnt_signal(CNT_CS2 + cg); __syncwarp(); }
                    if (warp == 6 && elect_one()) {
                        prefetch_l2(w2 + blockIdx.x * 15360, 15360);
                        prefetch_l2(wo + blockIdx.x * 6400, 6400);
                    }
                    if (lane == 0) cnt_wait(CNT_CS2 + cg, (epoch2 + 1) * 16);
                    __syncwarp();
                    gather(120 + (ht - 128));
                    __syncwarp();
                    if (lane == 0) mbar_arrive(bar + B_AUX2 * 8);
                }
                if (warp == 4) {
                    mbar_wait(bar + B_ST * 8, 0);
                    if (elect_one()) cnt_signal(CNT_QKV + cg);
                    __syncwarp();
                }
                const int h = blockIdx.x >> 2, qb = blockIdx.x & 3;
                const uint32_t ep = *reinterpret_cast<volatile uint32_t*>(smem + SM_EPOCH);
                if (lane == 0 && warp != 5) {
                    cnt_wait(CNT_QKV + h / 12, (ep + 1) * 16);
                    cnt_wait(CNT_QKV + (32 + h) / 12, (ep + 1) * 16);
                    cnt_wait(CNT_QKV + (64 + h) / 12, (ep + 1) * 16);
                }
                __syncwarp();
                if (threadIdx.x == 64) TL(5, 0);
                if (warp == 1 || warp == 4 || warp >= 6) {
                    const int w = warp == 1 ? 0 : warp == 4 ? 1 : warp - 4, t = w * 32 + lane;
                    float kmax = 0.f, qmax = 0.f;
#pragma unroll
                    for (int i = 0; i < 4; i++) {
                        const float4 v = __ldcg(reinterpret_cast<const float4*>(g_nrm + (32 + h) * SEQ) + t + i * 128);
                        kmax = fmaxf(fmaxf(kmax, fmaxf(v.x, v.y)), fmaxf(v.z, v.w));
                    }
                    {
                        const float4 v = __ldcg(reinterpret_cast<const float4*>(g_nrm + h * SEQ + qb * 512) + t);
                        qmax = fmaxf(fmaxf(v.x, v.y), fmaxf(v.z, v.w));
                    }
#pragma unroll
                    for (int o = 16; o; o >>= 1) {
                        kmax = fmaxf(kmax, __shfl_xor_sync(~0u, kmax, o));
                        qmax = fmaxf(qmax, __shfl_xor_sync(~0u, qmax, o));
                    }
                    float* red = reinterpret_cast<float*>(smem + SM_RED);
                    if (lane == 0) { red[w] = kmax; red[8 + w] = qmax; }
                    asm volatile("bar.sync 8, 128;" ::: "memory");
                    if (warp == 1 && lane == 0) {
                        for (int u = 1; u < 4; u++) { kmax = fmaxf(kmax, red[u]); qmax = fmaxf(qmax, red[8 + u]); }
                        *reinterpret_cast<volatile uint32_t*>(smem + SM_SAFE) = kmax * qmax * 1.1f <= SAFE_BOUND * SAFE_BOUND;
                    }
                }
                const uint32_t barKV = bar + B_KV * 8;
                const uint8_t* gK = g_img + (size_t)(32 + h) * IMG_BYTES;
                const uint8_t* gV = g_img + (size_t)(64 + h) * IMG_BYTES;
                if (warp == 2) {
                    if (lane == 0) TL(5, 1);
                    mbar_wait(bar + B_DEAD * 8, 0);
                    if (lane == 0) TL(5, 2);
                    for (int i = lane; i < 192; i += 32) *reinterpret_cast<uint4*>(smem + SM_ZERO + i * 16) = make_uint4(0, 0, 0, 0);
                    fence_proxy_async();
                    __syncwarp();
                    if (elect_one()) {
                        asm volatile("fence.proxy.async.global;" ::: "memory");
                        const uint8_t* gQ = g_img + (size_t)h * IMG_BYTES + qb * 64 * 384;
                        mbar_expect_tx(barKV + 128, 6144);
                        bulk_load(sb + SM_K, gK, 6144, barKV + 128);
                        for (int p = 0; p < 2; p++) {
                            mbar_expect_tx(bar + (B_Q + p) * 8, 12288);
                            bulk_load(sb + SM_Q + p * 12288, gQ + p * 12288, 12288, bar + (B_Q + p) * 8);
                        }
                        for (int i = 0; i < 13; i++) {
                            mbar_expect_tx(barKV + i * 8, 12288);
                            bulk_load(sb + SM_K + (i + 1) * 6144, gK + (i + 1) * 6144, 6144, barKV + i * 8);
                        }
                    }
                    __syncwarp();
                    if (lane == 0) TL(5, 3);
                } else if (warp == 5) {
                    mbar_wait(bar + (B_ST + 1) * 8, 0);
                    if (lane == 0) {
                        for (int b = 0; b < 6; b++)
                            tma_store(&tm.h, sb + (7 + b % 3) * 16384 + (b / 3) * 8192, cg * 192 + (b % 3) * 64, rb * 128 + (b / 3) * 64);
                        bulk_commit();
                    }
                    __syncwarp();
                } else if (warp == 3) {
                    mbar_wait(bar + (B_DEAD + 1) * 8, 0);
                    if (elect_one()) {
                        asm volatile("fence.proxy.async.global;" ::: "memory");
                        for (int i = 0; i < 9; i++) bulk_load(sb + SM_V + (i + 7) * 6144, gV + i * 6144, 6144, barKV + i * 8);
                    }
                    __syncwarp();
                }
            }
            if (lane == 0) TL(6, warp);
            asm volatile("bar.sync %0, 128;" ::"r"(wgi + 3) : "memory");
            reg_alloc<128>();
        } else {
            reg_alloc<200>();
            const int wi = wgi - 2;
            const int row0 = rb * 128 + wi * 64 + w4 * 16 + g;
            const uint32_t sAw = sb + wi * 8192;
            const int rbk = row0 >> 3, hs0 = cg * 12;
            {
                const int srow = rb * 128 + cg * 16 + (warp - 8) * 2 + (lane >> 4);
                uint4 xv[5];
#pragma unroll
                for (int i = 0; i < 5; i++) xv[i] = __ldg(reinterpret_cast<const uint4*>(x + (size_t)srow * DM) + (lane & 15) + 16 * i);
                float sm = 0.f;
#pragma unroll
                for (int i = 0; i < 5; i++)
                    sm += ((bf_lo(xv[i].x) + bf_hi(xv[i].x)) + (bf_lo(xv[i].y) + bf_hi(xv[i].y))) +
                          ((bf_lo(xv[i].z) + bf_hi(xv[i].z)) + (bf_lo(xv[i].w) + bf_hi(xv[i].w)));
#pragma unroll
                for (int o = 8; o; o >>= 1) sm += __shfl_xor_sync(~0u, sm, o);
                const float mu = sm * (1.f / DM);
                float q0 = 0.f, q1 = 0.f;
#pragma unroll
                for (int i = 0; i < 5; i++) {
                    const uint32_t w[4] = {xv[i].x, xv[i].y, xv[i].z, xv[i].w};
#pragma unroll
                    for (int j = 0; j < 4; j++) {
                        const float d0 = bf_lo(w[j]) - mu, d1 = bf_hi(w[j]) - mu;
                        q0 = fmaf(d0, d0, q0); q1 = fmaf(d1, d1, q1);
                    }
                }
                float q = q0 + q1;
#pragma unroll
                for (int o = 8; o; o >>= 1) q += __shfl_xor_sync(~0u, q, o);
                const float var = q * (1.f / DM);
                const float r1 = rsqrtf(var + LN_EPS);
                const float r2 = rsqrtf(var * r1 * r1 + LN_EPS);
                if ((lane & 15) == 0) g_stat[srow] = make_float4(mu, r1, r1 * r2, 0.f);
                __syncwarp();
                if (lane == 0) mbar_arrive(bar + B_STAT * 8);
            }
            float accA[100], accB[20];
            const uint64_t dA0 = make_desc(sAw, 16, 1024, 1), dB0 = make_desc(sB, 4096, 1024, 1);
#pragma unroll 2
            for (int it = 0; it < 20; it++) {
                const int s = it & 3;
                if (!(it & 1)) mbar_wait(bar + (B_A + (it >> 1)) * 8, 0);
                if (threadIdx.x == 256 && it == 0) TL(0, 2);
                if (threadIdx.x == 256) IT(0, it);
                mbar_wait(bar + (B_F1 + s) * 8, (it >> 2) & 1);
                if (threadIdx.x == 256) IT(1, it);
                const uint64_t dA = dA0 + (it >> 1) * 1024 + (it & 1) * 4, dB = dB0 + s * 1024;
                wg_fence();
                wgmma_n40_ss_tb(accB, dA, dB + 769, it > 0);
                wgmma_n40_ss_tb(accB, dA + 2, dB + 769 + 128, 1);
                wgmma_n200_ss_tb(accA, dA, dB, it > 0);
                wgmma_n200_ss_tb(accA, dA + 2, dB + 128, 1);
                wg_commit();
                if (it > 0) { wg_wait<1>(); release_stage(bar + (B_E1 + ((it - 1) & 3)) * 8, peer, lane); }
            }
            if (threadIdx.x == 256) IT(2, 0);
            mbar_wait(bar + B_AUX * 8, 0);
            if (threadIdx.x == 256) IT(2, 1);
            const float4 st0 = __ldcg(g_stat + row0), st1 = __ldcg(g_stat + row0 + 8);
            wg_wait<0>();
            release_stage(bar + (B_E1 + 3) * 8, peer, lane);
            fence_regs(accA);
            fence_regs(accB);
            if (threadIdx.x == 256) TL(1, 1);
            const float2* cs = reinterpret_cast<const float2*>(smem + SM_CS) + c;
            uint8_t* img = g_img + (size_t)hs0 * IMG_BYTES + rbk * 384 + g * 16 + c * 4;
            const bool emu0 = (EMU_MASK >> (rbk & 15)) & 1, emu1 = (EMU_MASK >> ((rbk + 1) & 15)) & 1;
            const bool low = c < 2;
            uint32_t pk[60];
#pragma unroll
            for (int m = 0; m < 6; m++) {
                const int which = (hs0 + 2 * m) >> 5;
                const float m0 = st0.y * (which == 0 ? QSCALE : (which == 1 && emu0) ? 2.f : 1.f);
                const float m1 = st1.y * (which == 0 ? QSCALE : (which == 1 && emu1) ? 2.f : 1.f);
                const float d0 = -st0.x * m0, d1 = -st1.x * m1;
                const float* a = m < 5 ? &accA[20 * m] : accB;
#pragma unroll
                for (int b = 0; b < 5; b++) {
                    const float2 cv = cs[(5 * m + b) * 4];
                    pk[10 * m + 2 * b] = pack_bf16(fmaf(a[4 * b], m0, d0 * cv.x), fmaf(a[4 * b + 1], m0, d0 * cv.y));
                    pk[10 * m + 2 * b + 1] = pack_bf16(fmaf(a[4 * b + 2], m1, d1 * cv.x), fmaf(a[4 * b + 3], m1, d1 * cv.y));
                }
            }
            const float r20 = 0.5f * st0.z, r21 = 0.5f * st1.z, e20 = -st0.x * r20, e21 = -st1.x * r21;
            if (threadIdx.x == 256) IT(2, 2);
            float acc2[96];
#pragma unroll
            for (int it = 0; it < 20; it++) {
                const int s = it % 5;
                if (threadIdx.x == 256) IT(0, 20 + it);
                mbar_wait(bar + (B_F2 + s) * 8, (it / 5) & 1);
                if (threadIdx.x == 256) IT(1, 20 + it);
                wg_fence();
                const uint64_t dA = make_desc(sAw + (it >> 1) * 16384 + (it & 1) * 64, 16, 1024, 1);
                const uint64_t dB = make_desc(sB + s * 12288, 4096, 1024, 1);
                if (it == 0) wgmma_n192_ss_tb_z(acc2, dA, dB); else wgmma_n192_ss_tb(acc2, dA, dB, 1);
                wgmma_n192_ss_tb(acc2, dA + 2, dB + 128, 1);
                wg_commit();
                if (it > 0) {
                    wg_wait<1>();
                    if (it <= 15) release_stage(bar + (B_E2 + (it - 1) % 5) * 8, peer, lane);
                    if (it == 14 && lane == 0) mbar_arrive(bar + B_DEAD * 8);
                }
                if (it < 6) {
                    const int m = it;
                    const int hs = hs0 + 2 * m, which = hs >> 5;
                    const uint32_t* a = pk + 10 * m;
                    uint8_t* pe = img + (2 * m) * IMG_BYTES;
                    uint8_t* po = pe + IMG_BYTES;
                    const uint32_t padv = which == 0 ? 0x3F803F80u : which == 1 ? 0xBFFF4440u : 0x00003F80u;
                    const uint32_t p0 = ((c & 1) || (which == 1 && !emu0)) ? 0u : padv;
                    const uint32_t p1 = ((c & 1) || (which == 1 && !emu1)) ? 0u : padv;
                    *(uint32_t*)(pe) = a[0];
                    *(uint32_t*)(pe + 128) = a[2];
                    *(uint32_t*)(pe + 256) = low ? a[4] : p0;
                    *(uint32_t*)(pe + 384) = a[1];
                    *(uint32_t*)(pe + 512) = a[3];
                    *(uint32_t*)(pe + 640) = low ? a[5] : p1;
                    *(uint32_t*)(po) = a[6];
                    *(uint32_t*)(po + 128) = a[8];
                    *(uint32_t*)(po + 256) = low ? p0 : a[4];
                    *(uint32_t*)(po + 384) = a[7];
                    *(uint32_t*)(po + 512) = a[9];
                    *(uint32_t*)(po + 640) = low ? p1 : a[5];
                    if (which < 2) {
                        const uint32_t u0 = bf2_fma(a[4], a[4], 0u), u1 = bf2_fma(a[5], a[5], 0u);
                        const uint32_t pe0 = bf2_fma(a[0], a[0], bf2_fma(a[2], a[2], low ? u0 : 0u));
                        const uint32_t pe1 = bf2_fma(a[1], a[1], bf2_fma(a[3], a[3], low ? u1 : 0u));
                        const uint32_t po0 = bf2_fma(a[6], a[6], bf2_fma(a[8], a[8], low ? 0u : u0));
                        const uint32_t po1 = bf2_fma(a[7], a[7], bf2_fma(a[9], a[9], low ? 0u : u1));
                        const float e0 = bf_lo(pe0) + bf_hi(pe0), e1 = bf_lo(pe1) + bf_hi(pe1);
                        const float o0 = bf_lo(po0) + bf_hi(po0), o1 = bf_lo(po1) + bf_hi(po1);
                        const bool b0 = c & 1, b1_ = c & 2;
                        const float x0 = (b0 ? e1 : e0) + __shfl_xor_sync(~0u, b0 ? e0 : e1, 1);
                        const float x1 = (b0 ? o1 : o0) + __shfl_xor_sync(~0u, b0 ? o0 : o1, 1);
                        float y = (b1_ ? x1 : x0) + __shfl_xor_sync(~0u, b1_ ? x0 : x1, 2);
                        if (which == 1 && (b0 ? emu1 : emu0)) y *= 0.25f;
                        g_nrm[(hs + (c >> 1)) * SEQ + row0 + (c & 1) * 8] = y;
                    }
                    if (it == 5) { __syncwarp(); if (lane == 0) mbar_arrive(bar + B_ST * 8); }
                }
            }
            wg_wait<0>();
            fence_regs(acc2);
            if (lane == 0) mbar_arrive(bar + (B_DEAD + 1) * 8);
            if (threadIdx.x == 256) TL(1, 2);
            mbar_wait(bar + B_AUX2 * 8, 0);
            if (threadIdx.x == 256) TL(4, 0);
            const uint32_t* bias = reinterpret_cast<const uint32_t*>(smem + SM_BIAS) + c;
            const int mrow = w4 * 16 + (lane & 15);
            const uint32_t stage = sAw + 7 * 16384;
            const uint32_t st_row = stage + mrow * 128;
#pragma unroll
            for (int j = 0; j < 24; j += 2) {
                const uint32_t bA = bias[j * 4], bB = bias[j * 4 + 4];
                const float2 cA = cs[(30 + j) * 4], cB = cs[(31 + j) * 4];
                const float* a = acc2 + j * 4;
                const uint32_t r00 = pack_bf16(gelu_half(fmaf(a[0], r20, fmaf(e20, cA.x, bf_lo(bA)))), gelu_half(fmaf(a[1], r20, fmaf(e20, cA.y, bf_hi(bA)))));
                const uint32_t r10 = pack_bf16(gelu_half(fmaf(a[2], r21, fmaf(e21, cA.x, bf_lo(bA)))), gelu_half(fmaf(a[3], r21, fmaf(e21, cA.y, bf_hi(bA)))));
                const uint32_t r01 = pack_bf16(gelu_half(fmaf(a[4], r20, fmaf(e20, cB.x, bf_lo(bB)))), gelu_half(fmaf(a[5], r20, fmaf(e20, cB.y, bf_hi(bB)))));
                const uint32_t r11 = pack_bf16(gelu_half(fmaf(a[6], r21, fmaf(e21, cB.x, bf_lo(bB)))), gelu_half(fmaf(a[7], r21, fmaf(e21, cB.y, bf_hi(bB)))));
                const int chunk = (j & 7) + (lane >> 4);
                stmatrix_x4(st_row + (j >> 3) * 16384 + ((chunk ^ (mrow & 7)) << 4), r00, r10, r01, r11);
            }
            if (threadIdx.x == 256) TL(4, 1);
            fence_proxy_async();
            __syncwarp();
            if (lane == 0) mbar_arrive(bar + (B_ST + 1) * 8);
            asm volatile("bar.sync %0, 128;" ::"r"(wgi + 3) : "memory");
            reg_dealloc<128>();
            if (threadIdx.x == 256) TL(4, 3);
        }
        __syncthreads();
        if (threadIdx.x == 0) TL(1, 3);
    }

    {
        const int h = blockIdx.x >> 2, qb = blockIdx.x & 3;
        const uint32_t sK = sb + SM_K, sV = sb + SM_V, barKV = bar + B_KV * 8;
        if (threadIdx.x == 0) TL(2, 0);
        auto late_tiles = [&]() {
            if (warp == 5 && lane == 0) {
                bulk_wait_read();
                asm volatile("fence.proxy.async.global;" ::: "memory");
                const uint8_t* gK = g_img + (size_t)(32 + h) * IMG_BYTES;
                const uint8_t* gV = g_img + (size_t)(64 + h) * IMG_BYTES;
                for (int i = 9; i < 16; i++) {
                    if (i >= 13) mbar_expect_tx(barKV + i * 8, i < 15 ? 12288 : 6144);
                    bulk_load(sV + ((i + 7) & 15) * 6144, gV + i * 6144, 6144, barKV + i * 8);
                    if (i >= 13 && i < 15) bulk_load(sK + (i + 1) * 6144, gK + (i + 1) * 6144, 6144, barKV + i * 8);
                }
            }
            __syncwarp();
        };
        const bool safe = __all_sync(~0u, *reinterpret_cast<volatile uint32_t*>(smem + SM_SAFE) != 0);
        if (threadIdx.x == 0) TL(2, 1);
        const uint64_t dK0 = make_desc(sK, 128, 384, 0), dV0 = make_desc(sV, 384, 128, 0);
        auto publish_h = [&]() {
            if (warp == 5) {
                if (lane == 0) { bulk_wait_all(); cnt_signal(CNT_H + rb); }
                __syncwarp();
            }
        };
        auto g2_issue = [&](int kb) {
            const int ct = (blockIdx.x >> 1) & 3, rt = (blockIdx.x >> 3) * 2 + (blockIdx.x & 1);
            const uint32_t dst = sb + g2_slot(kb % 7), fb = bar + (B_F3 + kb % 7) * 8;
            const CUtensorMap* mA = kb < 24 ? &tm.h : &tm.o;
            const CUtensorMap* mB = kb < 24 ? &tm.w2 : &tm.wo;
            const int k0 = (kb < 24 ? kb : kb - 24) * 64;
            mbar_expect_tx(fb, G2_STAGE);
            tma_load(dst, mA, k0, rt * 64, fb);
            const int first = ((kb & 1) == (int)rank) ? 0 : 3, last = ((kb & 1) == (int)rank) ? 3 : 5;
            for (int b = first; b < last; b++) tma_load_mc(dst + 8192 + b * 4096, mB, ct * 160 + b * 32, k0, fb, 3);
        };
        auto pf_arrive = [&](int step) {
            if (lane == 0) { mbar_arrive(bar + (B_PF + step) * 8); mbar_arrive_cluster(bar + (B_PF + step) * 8, peer); }
        };
        auto pf_issue = [&](int step) {
            if (warp == 4) {
                mbar_wait(bar + (B_PF + step) * 8, 0);
                if (elect_one()) {
                    if (step == 0) {
                        cnt_wait(CNT_H + (blockIdx.x >> 3), (*reinterpret_cast<volatile uint32_t*>(smem + SM_EPOCH) + 1) * 8);
                        prefetch_map(&tm.o); prefetch_map(&tm.wo);
                    }
                    g2_issue(2 * step);
                    if (step < 2) g2_issue(2 * step + 1);
                }
                __syncwarp();
            }
        };
        if (!safe) {
            late_tiles();
#pragma unroll 1
            for (int pass = 0; pass < 2; pass++) {
                const uint32_t sQ = sb + SM_Q + pass * 12288 + wgi * 3072;
                mbar_wait(bar + (B_Q + pass) * 8, 0);
                attn_rows_maxshift(sK, barKV, make_desc(sQ, 128, 384, 0), make_desc(sQ + 256, sb + SM_ZERO - (sQ + 256), 384, 0), h,
                                   qb * 512 + pass * 256 + wgi * 64 + w4 * 16);
                if (pass == 0) publish_h();
            }
            pf_arrive(0); pf_arrive(1); pf_arrive(2);
            pf_issue(0); pf_issue(1);
        } else {
            const ExpConst kc = make_exp_const();
#pragma unroll 1
            for (int pass = 0; pass < 2; pass++) {
                const int rbase = qb * 512 + pass * 256 + wgi * 64 + w4 * 16;
                const uint32_t sQ = sb + SM_Q + pass * 12288 + wgi * 3072;
                const uint64_t dQ = make_desc(sQ, 128, 384, 0), dQ2 = make_desc(sQ + 256, sb + SM_ZERO - (sQ + 256), 384, 0);
                float o[12], sa[32], sc[32];
                uint32_t p[16];
#pragma unroll
                for (int i = 0; i < 12; i++) o[i] = 0.f;
                fence_regs(o);
                mbar_wait(bar + (B_Q + pass) * 8, 0);
                mbar_wait(barKV + 128, 0);
                qk_tile(sa, dQ, dQ2, dK0);
                wg_wait<0>();
                fence_regs(sa);
                uint64_t dK = dK0, dV = dV0 + 7 * 384;
                uint32_t bj = barKV;
#pragma unroll 1
                for (int j = 0; j < 16; j++) {
                    mbar_wait(bj, 0);
                    if (pass == 0 && j == 2) late_tiles();
                    qk_tile(sc, dQ, dQ2, dK + 192);
                    wg_wait<1>();
                    if (pass == 1) {
                        if (j == 6 || j == 10 || j == 14) pf_arrive((j - 6) >> 2);
                        if (j == 8 || j == 12) pf_issue((j - 8) >> 2);
                    }
                    exp_tile<0>(sa, p, kc);
                    pv_tile(o, p, dV);
                    wg_wait<1>();
                    fence_regs(sc);
                    mbar_wait(bj, 0);
                    qk_tile(sa, dQ, dQ2, dK + 384);
                    wg_wait<1>();
                    exp_tile<8>(sc, p, kc);
                    pv_tile(o, p, dV + 192);
                    wg_wait<1>();
                    fence_regs(sa);
                    dK += 384; dV = j == 8 ? dV0 : dV + 384; bj += 8;
                }
                wg_wait<0>();
                fence_regs(o);
                store_o(o, h, rbase, lane);
                if (threadIdx.x == 0) TL(2, 2 + pass);
                if (pass == 0) publish_h();
            }
        }
        pf_issue(2);
        __syncthreads();
        if (threadIdx.x == 64) cnt_signal(CNT_O + qb);
        cluster_arrive_relaxed();
    }

    {
        const uint32_t epoch = *reinterpret_cast<volatile uint32_t*>(smem + SM_EPOCH);
        const int ct = cl & 3, rt = (cl >> 2) * 2 + rank;
        if (threadIdx.x == 0) TL(3, 0);
        const int ot = threadIdx.x - 192, orow = ot / 5, oseg = ot - orow * 5;
        const size_t ooff = (size_t)(rt * 64 + orow) * DM + ct * 160 + oseg * 32;
        uint4 xr[4], br[4];
        if (ot >= 0) {
#pragma unroll
            for (int i = 0; i < 4; i++) {
                asm volatile("ld.global.nc.v4.u32 {%0, %1, %2, %3}, [%4];" : "=r"(xr[i].x), "=r"(xr[i].y), "=r"(xr[i].z), "=r"(xr[i].w)
                             : "l"(reinterpret_cast<const uint4*>(x + ooff) + i));
                asm volatile("ld.global.nc.v4.u32 {%0, %1, %2, %3}, [%4];" : "=r"(br[i].x), "=r"(br[i].y), "=r"(br[i].z), "=r"(br[i].w)
                             : "l"(reinterpret_cast<const uint4*>(b2 + ct * 160 + oseg * 32) + i));
            }
        }
        cluster_wait();
        float* stg = reinterpret_cast<float*>(smem);
        if (warp == 4) {
#pragma unroll 1
            for (int kb = 5; kb < 34; kb++) {
                const int s = kb % 7;
                if (kb >= 7) mbar_wait(bar + (B_E3 + s) * 8, ((kb / 7) - 1) & 1);
                if (elect_one()) {
                    if (kb == 24) { cnt_wait(CNT_O + (rt >> 3), (epoch + 1) * 32); TL(3, 1); }
                    const uint32_t dst = sb + g2_slot(s), fb = bar + (B_F3 + s) * 8;
                    const CUtensorMap* mA = kb < 24 ? &tm.h : &tm.o;
                    const CUtensorMap* mB = kb < 24 ? &tm.w2 : &tm.wo;
                    const int k0 = (kb < 24 ? kb : kb - 24) * 64;
                    mbar_expect_tx(fb, G2_STAGE);
                    tma_load(dst, mA, k0, rt * 64, fb);
                    const int first = ((kb & 1) == (int)rank) ? 0 : 3, last = ((kb & 1) == (int)rank) ? 3 : 5;
                    for (int b = first; b < last; b++) tma_load_mc(dst + 8192 + b * 4096, mB, ct * 160 + b * 32, k0, fb, 3);
                }
                __syncwarp();
            }
        } else if (wgi == 0) {
            float acc[80];
#pragma unroll 1
            for (int kb = 0; kb < 34; kb++) {
                const int s = kb % 7;
                mbar_wait(bar + (B_F3 + s) * 8, (kb / 7) & 1);
                const uint64_t dA = make_desc(sb + g2_slot(s), 16, 1024, 1);
                const uint64_t dB = make_desc(sb + g2_slot(s) + 8192, 4096, 512, 2);
                wg_fence();
#pragma unroll
                for (int kk = 0; kk < 4; kk++) wgmma_n160_ss_tb(acc, dA + kk * 2, dB + kk * 64, (kb | kk) != 0);
                wg_commit();
                if (kb > 0) {
                    wg_wait<1>();
                    if (kb <= 27) release_stage(bar + (B_E3 + (kb - 1) % 7) * 8, peer, lane);
                }
            }
            wg_wait<0>();
            fence_regs(acc);
            if (threadIdx.x == 0) TL(3, 2);
            const int r = w4 * 16 + g;
#pragma unroll
            for (int j = 0; j < 20; j++) {
                *reinterpret_cast<float2*>(stg + r * 184 + j * 8 + (j >> 2) * 4 + 2 * c) = make_float2(acc[4 * j], acc[4 * j + 1]);
                *reinterpret_cast<float2*>(stg + (r + 8) * 184 + j * 8 + (j >> 2) * 4 + 2 * c) = make_float2(acc[4 * j + 2], acc[4 * j + 3]);
            }
        }
        __syncthreads();
        if (ot >= 0) {
            const float4* sp = reinterpret_cast<const float4*>(stg + orow * 184 + oseg * 36);
#pragma unroll
            for (int i = 0; i < 4; i++) {
                const float4 a = sp[2 * i], b = sp[2 * i + 1];
                uint4 w;
                w.x = pack_bf16(a.x + bf_lo(br[i].x) + bf_lo(xr[i].x), a.y + bf_hi(br[i].x) + bf_hi(xr[i].x));
                w.y = pack_bf16(a.z + bf_lo(br[i].y) + bf_lo(xr[i].y), a.w + bf_hi(br[i].y) + bf_hi(xr[i].y));
                w.z = pack_bf16(b.x + bf_lo(br[i].z) + bf_lo(xr[i].z), b.y + bf_hi(br[i].z) + bf_hi(xr[i].z));
                w.w = pack_bf16(b.z + bf_lo(br[i].w) + bf_lo(xr[i].w), b.w + bf_hi(br[i].w) + bf_hi(xr[i].w));
                reinterpret_cast<uint4*>(out + ooff)[i] = w;
            }
        }
        if (blockIdx.x == 0 && threadIdx.x == 0) g_epoch = epoch + 1;
        if (threadIdx.x == 256) TL(3, 3);
    }
    cluster_arrive_relaxed();
    cluster_wait();
}

typedef CUresult (*EncodeTiledFn)(CUtensorMap*, CUtensorMapDataType, cuuint32_t, void*, const cuuint64_t*,
                                  const cuuint64_t*, const cuuint32_t*, const cuuint32_t*, CUtensorMapInterleave,
                                  CUtensorMapSwizzle, CUtensorMapL2promotion, CUtensorMapFloatOOBfill);

CUtensorMap make_map(EncodeTiledFn enc, const void* ptr, int rows, int cols, int box_rows, int box_cols,
                     CUtensorMapSwizzle swz) {
    CUtensorMap m;
    cuuint64_t gd[2] = {(cuuint64_t)cols, (cuuint64_t)rows};
    cuuint64_t gs[1] = {(cuuint64_t)cols * 2};
    cuuint32_t bd[2] = {(cuuint32_t)box_cols, (cuuint32_t)box_rows};
    cuuint32_t es[2] = {1, 1};
    enc(&m, CU_TENSOR_MAP_DATA_TYPE_BFLOAT16, 2, const_cast<void*>(ptr), gd, gs, bd, es, CU_TENSOR_MAP_INTERLEAVE_NONE,
        swz, CU_TENSOR_MAP_L2_PROMOTION_L2_128B, CU_TENSOR_MAP_FLOAT_OOB_FILL_NONE);
    return m;
}

}

extern "C" void kernel_launch(void* const* d_in, const int* in_sizes, int n_in, void* d_out, int out_size) {
    (void)in_sizes; (void)n_in; (void)out_size;
    const __nv_bfloat16* x = (const __nv_bfloat16*)d_in[0];
    const __nv_bfloat16* wqkv = (const __nv_bfloat16*)d_in[1];
    const __nv_bfloat16* wo = (const __nv_bfloat16*)d_in[2];
    const __nv_bfloat16* w1 = (const __nv_bfloat16*)d_in[4];
    const __nv_bfloat16* b1 = (const __nv_bfloat16*)d_in[5];
    const __nv_bfloat16* w2 = (const __nv_bfloat16*)d_in[6];
    const __nv_bfloat16* b2 = (const __nv_bfloat16*)d_in[7];
    __nv_bfloat16* out = (__nv_bfloat16*)d_out;

    static EncodeTiledFn enc = nullptr;
    static void *p_h, *p_o;
    if (!enc) {
        cudaDriverEntryPointQueryResult qr;
        cudaGetDriverEntryPoint("cuTensorMapEncodeTiled", (void**)&enc, cudaEnableDefault, &qr);
        cudaGetSymbolAddress(&p_h, g_h);
        cudaGetSymbolAddress(&p_o, g_o);
        cudaFuncSetAttribute(k_fused, cudaFuncAttributeMaxDynamicSharedMemorySize, SM_TOTAL);
    }
    Maps tm;
    tm.x = make_map(enc, x, SEQ, DM, 128, 64, CU_TENSOR_MAP_SWIZZLE_128B);
    tm.wqkv = make_map(enc, wqkv, DM, 3 * DM, 32, 64, CU_TENSOR_MAP_SWIZZLE_128B);
    tm.w1 = make_map(enc, w1, DM, FF, 32, 64, CU_TENSOR_MAP_SWIZZLE_128B);
    tm.h = make_map(enc, p_h, SEQ, FF, 64, 64, CU_TENSOR_MAP_SWIZZLE_128B);
    tm.o = make_map(enc, p_o, SEQ, DM, 64, 64, CU_TENSOR_MAP_SWIZZLE_128B);
    tm.wo = make_map(enc, wo, DM, DM, 64, 32, CU_TENSOR_MAP_SWIZZLE_64B);
    tm.w2 = make_map(enc, w2, FF, DM, 64, 32, CU_TENSOR_MAP_SWIZZLE_64B);
    k_fused<<<128, 512, SM_TOTAL, cudaStreamPerThread>>>(tm, x, (const uint8_t*)wqkv, (const uint8_t*)w1, (const uint8_t*)w2,
                                                         (const uint8_t*)wo, b1, b2, out);
}
```

```cpp
#include <cuda_runtime.h>
#include <cuda_bf16.h>
#include <cuda.h>
#include <stdint.h>

namespace {

constexpr int SEQ = 2048, DM = 640, FF = 1536;
constexpr float LN_EPS = 1e-5f;

constexpr int IMG_BYTES = 256 * 384;
constexpr uint32_t EMU_MASK = 0xD5D5u;
constexpr float SAFE_BOUND = 80.0f;
#define XV_IT 1
#define PACE_NS 200
constexpr float QSCALE = 0.22360679774997896f * 1.4426950408889634f;

__device__ float4 g_stat[SEQ];
__device__ float2 g_csp[16 * 1728];
__device__ __align__(1024) uint8_t g_img[96 * IMG_BYTES + 1024];
__device__ float g_nrm[64 * SEQ];
__device__ __align__(1024) __nv_bfloat16 g_h[SEQ * FF];
__device__ __align__(1024) __nv_bfloat16 g_o[SEQ * DM];
constexpr int CNT_ST = 0, CNT_QKV = 16, CNT_H = 24, CNT_O = 40, CNT_CS = 44, CNT_CS2 = 52;
__device__ uint32_t g_cnt[60 * 32];
__device__ uint32_t g_epoch;

#define TL(kern, slot) do { } while (0)
#define IT(row, i) do { } while (0)

__device__ __forceinline__ uint32_t smem_u32(const void* p) { return (uint32_t)__cvta_generic_to_shared(p); }
__device__ __forceinline__ void mbar_init(uint32_t bar, int cnt) {
    asm volatile("mbarrier.init.shared::cta.b64 [%0], %1;" ::"r"(bar), "r"(cnt));
}
__device__ __forceinline__ void mbar_expect_tx(uint32_t bar, uint32_t bytes) {
    asm volatile("mbarrier.arrive.expect_tx.shared::cta.b64 _, [%0], %1;" ::"r"(bar), "r"(bytes) : "memory");
}
__device__ __forceinline__ void mbar_wait(uint32_t bar, uint32_t parity) {
    asm volatile("{\n.reg .pred p;\n.reg .u32 n;\nmov.u32 n, 0;\n"
                 "WAIT_LOOP:\nmbarrier.try_wait.parity.shared::cta.b64 p, [%0], %1;\n@p bra WAIT_DONE;\n"
                 "add.u32 n, n, 1;\nsetp.lt.u32 p, n, 4194304;\n@p bra WAIT_LOOP;\nWAIT_DONE:\n}"
                 ::"r"(bar), "r"(parity) : "memory");
}
__device__ __forceinline__ void mbar_arrive(uint32_t bar) {
    asm volatile("mbarrier.arrive.shared::cta.b64 _, [%0];" ::"r"(bar) : "memory");
}
__device__ __forceinline__ void mbar_arrive_cluster(uint32_t bar, uint32_t cta) {
    asm volatile("{\n.reg .b32 ra;\nmapa.shared::cluster.u32 ra, %0, %1;\n"
                 "mbarrier.arrive.shared::cluster.b64 _, [ra];\n}" ::"r"(bar), "r"(cta) : "memory");
}
__device__ __forceinline__ void fence_barrier_init() { asm volatile("fence.mbarrier_init.release.cluster;" ::: "memory"); }
__device__ __forceinline__ void fence_proxy_async() { asm volatile("fence.proxy.async.shared::cta;" ::: "memory"); }
__device__ __forceinline__ void cluster_sync() {
    asm volatile("barrier.cluster.arrive.release.aligned;\nbarrier.cluster.wait.acquire.aligned;" ::: "memory");
}
__device__ __forceinline__ bool elect_one() {
    uint32_t pred;
    asm volatile("{\n.reg .pred p;\nelect.sync _|p, 0xFFFFFFFF;\nselp.b32 %0, 1, 0, p;\n}" : "=r"(pred));
    return pred != 0;
}
__device__ __forceinline__ void pdl_launch() { asm volatile("griddepcontrol.launch_dependents;" ::: "memory"); }
__device__ __forceinline__ void pdl_wait() { asm volatile("griddepcontrol.wait;" ::: "memory"); }
__device__ __forceinline__ void prefetch_map(const CUtensorMap* m) {
    asm volatile("prefetch.tensormap [%0];" ::"l"(m) : "memory");
}
__device__ __forceinline__ void tma_load(uint32_t dst, const CUtensorMap* m, int c0, int c1, uint32_t bar) {
    asm volatile("cp.async.bulk.tensor.2d.shared::cluster.global.mbarrier::complete_tx::bytes [%0], [%1, {%3, %4}], [%2];"
                 ::"r"(dst), "l"(m), "r"(bar), "r"(c0), "r"(c1) : "memory");
}
__device__ __forceinline__ void tma_load_mc(uint32_t dst, const CUtensorMap* m, int c0, int c1, uint32_t bar, uint16_t mask) {
    asm volatile("cp.async.bulk.tensor.2d.shared::cluster.global.mbarrier::complete_tx::bytes.multicast::cluster"
                 " [%0], [%1, {%3, %4}], [%2], %5;"
                 ::"r"(dst), "l"(m), "r"(bar), "r"(c0), "r"(c1), "h"(mask) : "memory");
}
__device__ __forceinline__ void tma_store(const CUtensorMap* m, uint32_t src, int c0, int c1) {
    asm volatile("cp.async.bulk.tensor.2d.global.shared::cta.bulk_group [%0, {%2, %3}], [%1];"
                 ::"l"(m), "r"(src), "r"(c0), "r"(c1) : "memory");
}
__device__ __forceinline__ void bulk_commit() { asm volatile("cp.async.bulk.commit_group;" ::: "memory"); }
__device__ __forceinline__ void bulk_wait_all() { asm volatile("cp.async.bulk.wait_group 0;" ::: "memory"); }
__device__ __forceinline__ void bulk_load(uint32_t dst, const void* src, uint32_t bytes, uint32_t bar) {
    asm volatile("cp.async.bulk.shared::cluster.global.mbarrier::complete_tx::bytes [%0], [%1], %2, [%3];"
                 ::"r"(dst), "l"(src), "r"(bytes), "r"(bar) : "memory");
}
__device__ __forceinline__ void prefetch_l2(const void* p, uint32_t bytes) {
    asm volatile("cp.async.bulk.prefetch.L2.global [%0], %1;" ::"l"(p), "r"(bytes) : "memory");
}
__device__ __forceinline__ void tma_prefetch_l2(const CUtensorMap* m, int c0, int c1) {
    asm volatile("cp.async.bulk.prefetch.tensor.2d.L2.global.tile [%0, {%1, %2}];" ::"l"(m), "r"(c0), "r"(c1) : "memory");
}
__device__ __forceinline__ void wg_fence() { asm volatile("wgmma.fence.sync.aligned;" ::: "memory"); }
__device__ __forceinline__ void wg_commit() { asm volatile("wgmma.commit_group.sync.aligned;" ::: "memory"); }
template <int N> __device__ __forceinline__ void wg_wait() {
    asm volatile("wgmma.wait_group.sync.aligned %0;" ::"n"(N) : "memory");
}
template <int N> __device__ __forceinline__ void reg_alloc() { asm volatile("setmaxnreg.inc.sync.aligned.u32 %0;" ::"n"(N)); }
template <int N> __device__ __forceinline__ void reg_dealloc() { asm volatile("setmaxnreg.dec.sync.aligned.u32 %0;" ::"n"(N)); }
template <int N> __device__ __forceinline__ void fence_regs(float (&d)[N]) {
#pragma unroll
    for (int i = 0; i < N; i++) asm volatile("" : "+f"(d[i])::"memory");
}
__device__ __forceinline__ uint64_t make_desc(uint32_t addr, uint32_t lbo, uint32_t sbo, uint32_t swz) {
    return (uint64_t)((addr & 0x3FFFF) >> 4) | ((uint64_t)(lbo >> 4) << 16) | ((uint64_t)(sbo >> 4) << 32) |
           ((uint64_t)swz << 62);
}
__device__ __forceinline__ uint32_t pack_bf16(float lo, float hi) {
    uint32_t r;
    asm("cvt.rn.bf16x2.f32 %0, %1, %2;" : "=r"(r) : "f"(hi), "f"(lo));
    return r;
}
__device__ __forceinline__ float ex2(float x) {
    float r;
    asm("ex2.approx.ftz.f32 %0, %1;" : "=f"(r) : "f"(x));
    return r;
}
__device__ __forceinline__ float bf_lo(uint32_t v) { return __uint_as_float(v << 16); }
__device__ __forceinline__ float bf_hi(uint32_t v) { return __uint_as_float(v & 0xFFFF0000u); }
__device__ __forceinline__ void stmatrix_x4(uint32_t addr, uint32_t r0, uint32_t r1, uint32_t r2, uint32_t r3) {
    asm volatile("stmatrix.sync.aligned.m8n8.x4.shared.b16 [%0], {%1, %2, %3, %4};"
                 ::"r"(addr), "r"(r0), "r"(r1), "r"(r2), "r"(r3) : "memory");
}

__device__ __forceinline__ void wgmma_n200_ss_tb(float (&d)[100], uint64_t descA, uint64_t descB, int scaleD) {
    asm volatile("{\n.reg .pred p;\nsetp.ne.b32 p, %102, 0;\n"
        "wgmma.mma_async.sync.aligned.m64n200k16.f32.bf16.bf16 {"
        "%0, %1, %2, %3, %4, %5, %6, %7, %8, %9, %10, %11, %12, %13, %14, %15, "
        "%16, %17, %18, %19, %20, %21, %22, %23, %24, %25, %26, %27, %28, %29, %30, %31, "
        "%32, %33, %34, %35, %36, %37, %38, %39, %40, %41, %42, %43, %44, %45, %46, %47, "
        "%48, %49, %50, %51, %52, %53, %54, %55, %56, %57, %58, %59, %60, %61, %62, %63, "
        "%64, %65, %66, %67, %68, %69, %70, %71, %72, %73, %74, %75, %76, %77, %78, %79, "
        "%80, %81, %82, %83, %84, %85, %86, %87, %88, %89, %90, %91, %92, %93, %94, %95, "
        "%96, %97, %98, %99}, "
        "%100, %101, p, 1, 1, 0, 1;\n}\n"
        : "+f"(d[0]), "+f"(d[1]), "+f"(d[2]), "+f"(d[3]), "+f"(d[4]), "+f"(d[5]), "+f"(d[6]), "+f"(d[7]),
          "+f"(d[8]), "+f"(d[9]), "+f"(d[10]), "+f"(d[11]), "+f"(d[12]), "+f"(d[13]), "+f"(d[14]), "+f"(d[15]),
          "+f"(d[16]), "+f"(d[17]), "+f"(d[18]), "+f"(d[19]), "+f"(d[20]), "+f"(d[21]), "+f"(d[22]), "+f"(d[23]),
          "+f"(d[24]), "+f"(d[25]), "+f"(d[26]), "+f"(d[27]), "+f"(d[28]), "+f"(d[29]), "+f"(d[30]), "+f"(d[31]),
          "+f"(d[32]), "+f"(d[33]), "+f"(d[34]), "+f"(d[35]), "+f"(d[36]), "+f"(d[37]), "+f"(d[38]), "+f"(d[39]),
          "+f"(d[40]), "+f"(d[41]), "+f"(d[42]), "+f"(d[43]), "+f"(d[44]), "+f"(d[45]), "+f"(d[46]), "+f"(d[47]),
          "+f"(d[48]), "+f"(d[49]), "+f"(d[50]), "+f"(d[51]), "+f"(d[52]), "+f"(d[53]), "+f"(d[54]), "+f"(d[55]),
          "+f"(d[56]), "+f"(d[57]), "+f"(d[58]), "+f"(d[59]), "+f"(d[60]), "+f"(d[61]), "+f"(d[62]), "+f"(d[63]),
          "+f"(d[64]), "+f"(d[65]), "+f"(d[66]), "+f"(d[67]), "+f"(d[68]), "+f"(d[69]), "+f"(d[70]), "+f"(d[71]),
          "+f"(d[72]), "+f"(d[73]), "+f"(d[74]), "+f"(d[75]), "+f"(d[76]), "+f"(d[77]), "+f"(d[78]), "+f"(d[79]),
          "+f"(d[80]), "+f"(d[81]), "+f"(d[82]), "+f"(d[83]), "+f"(d[84]), "+f"(d[85]), "+f"(d[86]), "+f"(d[87]),
          "+f"(d[88]), "+f"(d[89]), "+f"(d[90]), "+f"(d[91]), "+f"(d[92]), "+f"(d[93]), "+f"(d[94]), "+f"(d[95]),
          "+f"(d[96]), "+f"(d[97]), "+f"(d[98]), "+f"(d[99])
        : "l"(descA), "l"(descB), "r"(scaleD));
}

__device__ __forceinline__ void wgmma_n40_ss_tb(float (&d)[20], uint64_t descA, uint64_t descB, int scaleD) {
    asm volatile("{\n.reg .pred p;\nsetp.ne.b32 p, %22, 0;\n"
        "wgmma.mma_async.sync.aligned.m64n40k16.f32.bf16.bf16 {"
        "%0, %1, %2, %3, %4, %5, %6, %7, %8, %9, %10, %11, %12, %13, %14, %15, "
        "%16, %17, %18, %19}, "
        "%20, %21, p, 1, 1, 0, 1;\n}\n"
        : "+f"(d[0]), "+f"(d[1]), "+f"(d[2]), "+f"(d[3]), "+f"(d[4]), "+f"(d[5]), "+f"(d[6]), "+f"(d[7]),
          "+f"(d[8]), "+f"(d[9]), "+f"(d[10]), "+f"(d[11]), "+f"(d[12]), "+f"(d[13]), "+f"(d[14]), "+f"(d[15]),
          "+f"(d[16]), "+f"(d[17]), "+f"(d[18]), "+f"(d[19])
        : "l"(descA), "l"(descB), "r"(scaleD));
}

__device__ __forceinline__ void wgmma_n192_ss_tb(float (&d)[96], uint64_t descA, uint64_t descB, int scaleD) {
    asm volatile("{\n.reg .pred p;\nsetp.ne.b32 p, %98, 0;\n"
        "wgmma.mma_async.sync.aligned.m64n192k16.f32.bf16.bf16 {"
        "%0, %1, %2, %3, %4, %5, %6, %7, %8, %9, %10, %11, %12, %13, %14, %15, "
        "%16, %17, %18, %19, %20, %21, %22, %23, %24, %25, %26, %27, %28, %29, %30, %31, "
        "%32, %33, %34, %35, %36, %37, %38, %39, %40, %41, %42, %43, %44, %45, %46, %47, "
        "%48, %49, %50, %51, %52, %53, %54, %55, %56, %57, %58, %59, %60, %61, %62, %63, "
        "%64, %65, %66, %67, %68, %69, %70, %71, %72, %73, %74, %75, %76, %77, %78, %79, "
        "%80, %81, %82, %83, %84, %85, %86, %87, %88, %89, %90, %91, %92, %93, %94, %95}, "
        "%96, %97, p, 1, 1, 0, 1;\n}\n"
        : "+f"(d[0]), "+f"(d[1]), "+f"(d[2]), "+f"(d[3]), "+f"(d[4]), "+f"(d[5]), "+f"(d[6]), "+f"(d[7]),
          "+f"(d[8]), "+f"(d[9]), "+f"(d[10]), "+f"(d[11]), "+f"(d[12]), "+f"(d[13]), "+f"(d[14]), "+f"(d[15]),
          "+f"(d[16]), "+f"(d[17]), "+f"(d[18]), "+f"(d[19]), "+f"(d[20]), "+f"(d[21]), "+f"(d[22]), "+f"(d[23]),
          "+f"(d[24]), "+f"(d[25]), "+f"(d[26]), "+f"(d[27]), "+f"(d[28]), "+f"(d[29]), "+f"(d[30]), "+f"(d[31]),
          "+f"(d[32]), "+f"(d[33]), "+f"(d[34]), "+f"(d[35]), "+f"(d[36]), "+f"(d[37]), "+f"(d[38]), "+f"(d[39]),
          "+f"(d[40]), "+f"(d[41]), "+f"(d[42]), "+f"(d[43]), "+f"(d[44]), "+f"(d[45]), "+f"(d[46]), "+f"(d[47]),
          "+f"(d[48]), "+f"(d[49]), "+f"(d[50]), "+f"(d[51]), "+f"(d[52]), "+f"(d[53]), "+f"(d[54]), "+f"(d[55]),
          "+f"(d[56]), "+f"(d[57]), "+f"(d[58]), "+f"(d[59]), "+f"(d[60]), "+f"(d[61]), "+f"(d[62]), "+f"(d[63]),
          "+f"(d[64]), "+f"(d[65]), "+f"(d[66]), "+f"(d[67]), "+f"(d[68]), "+f"(d[69]), "+f"(d[70]), "+f"(d[71]),
          "+f"(d[72]), "+f"(d[73]), "+f"(d[74]), "+f"(d[75]), "+f"(d[76]), "+f"(d[77]), "+f"(d[78]), "+f"(d[79]),
          "+f"(d[80]), "+f"(d[81]), "+f"(d[82]), "+f"(d[83]), "+f"(d[84]), "+f"(d[85]), "+f"(d[86]), "+f"(d[87]),
          "+f"(d[88]), "+f"(d[89]), "+f"(d[90]), "+f"(d[91]), "+f"(d[92]), "+f"(d[93]), "+f"(d[94]), "+f"(d[95])
        : "l"(descA), "l"(descB), "r"(scaleD));
}

__device__ __forceinline__ void wgmma_n192_ss_tb_z(float (&d)[96], uint64_t descA, uint64_t descB) {
    asm volatile("{\n.reg .pred p;\nsetp.ne.b32 p, 0, 0;\n"
        "wgmma.mma_async.sync.aligned.m64n192k16.f32.bf16.bf16 {"
        "%0, %1, %2, %3, %4, %5, %6, %7, %8, %9, %10, %11, %12, %13, %14, %15, "
        "%16, %17, %18, %19, %20, %21, %22, %23, %24, %25, %26, %27, %28, %29, %30, %31, "
        "%32, %33, %34, %35, %36, %37, %38, %39, %40, %41, %42, %43, %44, %45, %46, %47, "
        "%48, %49, %50, %51, %52, %53, %54, %55, %56, %57, %58, %59, %60, %61, %62, %63, "
        "%64, %65, %66, %67, %68, %69, %70, %71, %72, %73, %74, %75, %76, %77, %78, %79, "
        "%80, %81, %82, %83, %84, %85, %86, %87, %88, %89, %90, %91, %92, %93, %94, %95}, "
        "%96, %97, p, 1, 1, 0, 1;\n}\n"
        : "=f"(d[0]), "=f"(d[1]), "=f"(d[2]), "=f"(d[3]), "=f"(d[4]), "=f"(d[5]), "=f"(d[6]), "=f"(d[7]),
          "=f"(d[8]), "=f"(d[9]), "=f"(d[10]), "=f"(d[11]), "=f"(d[12]), "=f"(d[13]), "=f"(d[14]), "=f"(d[15]),
          "=f"(d[16]), "=f"(d[17]), "=f"(d[18]), "=f"(d[19]), "=f"(d[20]), "=f"(d[21]), "=f"(d[22]), "=f"(d[23]),
          "=f"(d[24]), "=f"(d[25]), "=f"(d[26]), "=f"(d[27]), "=f"(d[28]), "=f"(d[29]), "=f"(d[30]), "=f"(d[31]),
          "=f"(d[32]), "=f"(d[33]), "=f"(d[34]), "=f"(d[35]), "=f"(d[36]), "=f"(d[37]), "=f"(d[38]), "=f"(d[39]),
          "=f"(d[40]), "=f"(d[41]), "=f"(d[42]), "=f"(d[43]), "=f"(d[44]), "=f"(d[45]), "=f"(d[46]), "=f"(d[47]),
          "=f"(d[48]), "=f"(d[49]), "=f"(d[50]), "=f"(d[51]), "=f"(d[52]), "=f"(d[53]), "=f"(d[54]), "=f"(d[55]),
          "=f"(d[56]), "=f"(d[57]), "=f"(d[58]), "=f"(d[59]), "=f"(d[60]), "=f"(d[61]), "=f"(d[62]), "=f"(d[63]),
          "=f"(d[64]), "=f"(d[65]), "=f"(d[66]), "=f"(d[67]), "=f"(d[68]), "=f"(d[69]), "=f"(d[70]), "=f"(d[71]),
          "=f"(d[72]), "=f"(d[73]), "=f"(d[74]), "=f"(d[75]), "=f"(d[76]), "=f"(d[77]), "=f"(d[78]), "=f"(d[79]),
          "=f"(d[80]), "=f"(d[81]), "=f"(d[82]), "=f"(d[83]), "=f"(d[84]), "=f"(d[85]), "=f"(d[86]), "=f"(d[87]),
          "=f"(d[88]), "=f"(d[89]), "=f"(d[90]), "=f"(d[91]), "=f"(d[92]), "=f"(d[93]), "=f"(d[94]), "=f"(d[95])
        : "l"(descA), "l"(descB));
}

__device__ __forceinline__ void wgmma_n160_ss_tb(float (&d)[80], uint64_t descA, uint64_t descB, int scaleD) {
    asm volatile("{\n.reg .pred p;\nsetp.ne.b32 p, %82, 0;\n"
        "wgmma.mma_async.sync.aligned.m64n160k16.f32.bf16.bf16 {"
        "%0, %1, %2, %3, %4, %5, %6, %7, %8, %9, %10, %11, %12, %13, %14, %15, "
        "%16, %17, %18, %19, %20, %21, %22, %23, %24, %25, %26, %27, %28, %29, %30, %31, "
        "%32, %33, %34, %35, %36, %37, %38, %39, %40, %41, %42, %43, %44, %45, %46, %47, "
        "%48, %49, %50, %51, %52, %53, %54, %55, %56, %57, %58, %59, %60, %61, %62, %63, "
        "%64, %65, %66, %67, %68, %69, %70, %71, %72, %73, %74, %75, %76, %77, %78, %79}, "
        "%80, %81, p, 1, 1, 0, 1;\n}\n"
        : "+f"(d[0]), "+f"(d[1]), "+f"(d[2]), "+f"(d[3]), "+f"(d[4]), "+f"(d[5]), "+f"(d[6]), "+f"(d[7]),
          "+f"(d[8]), "+f"(d[9]), "+f"(d[10]), "+f"(d[11]), "+f"(d[12]), "+f"(d[13]), "+f"(d[14]), "+f"(d[15]),
          "+f"(d[16]), "+f"(d[17]), "+f"(d[18]), "+f"(d[19]), "+f"(d[20]), "+f"(d[21]), "+f"(d[22]), "+f"(d[23]),
          "+f"(d[24]), "+f"(d[25]), "+f"(d[26]), "+f"(d[27]), "+f"(d[28]), "+f"(d[29]), "+f"(d[30]), "+f"(d[31]),
          "+f"(d[32]), "+f"(d[33]), "+f"(d[34]), "+f"(d[35]), "+f"(d[36]), "+f"(d[37]), "+f"(d[38]), "+f"(d[39]),
          "+f"(d[40]), "+f"(d[41]), "+f"(d[42]), "+f"(d[43]), "+f"(d[44]), "+f"(d[45]), "+f"(d[46]), "+f"(d[47]),
          "+f"(d[48]), "+f"(d[49]), "+f"(d[50]), "+f"(d[51]), "+f"(d[52]), "+f"(d[53]), "+f"(d[54]), "+f"(d[55]),
          "+f"(d[56]), "+f"(d[57]), "+f"(d[58]), "+f"(d[59]), "+f"(d[60]), "+f"(d[61]), "+f"(d[62]), "+f"(d[63]),
          "+f"(d[64]), "+f"(d[65]), "+f"(d[66]), "+f"(d[67]), "+f"(d[68]), "+f"(d[69]), "+f"(d[70]), "+f"(d[71]),
          "+f"(d[72]), "+f"(d[73]), "+f"(d[74]), "+f"(d[75]), "+f"(d[76]), "+f"(d[77]), "+f"(d[78]), "+f"(d[79])
        : "l"(descA), "l"(descB), "r"(scaleD));
}

__device__ __forceinline__ void wgmma_n64_ss(float (&d)[32], uint64_t descA, uint64_t descB, int scaleD) {
    asm volatile("{\n.reg .pred p;\nsetp.ne.b32 p, %34, 0;\n"
        "wgmma.mma_async.sync.aligned.m64n64k16.f32.bf16.bf16 {"
        "%0, %1, %2, %3, %4, %5, %6, %7, %8, %9, %10, %11, %12, %13, %14, %15, "
        "%16, %17, %18, %19, %20, %21, %22, %23, %24, %25, %26, %27, %28, %29, %30, %31}, "
        "%32, %33, p, 1, 1, 0, 0;\n}\n"
        : "+f"(d[0]), "+f"(d[1]), "+f"(d[2]), "+f"(d[3]), "+f"(d[4]), "+f"(d[5]), "+f"(d[6]), "+f"(d[7]),
          "+f"(d[8]), "+f"(d[9]), "+f"(d[10]), "+f"(d[11]), "+f"(d[12]), "+f"(d[13]), "+f"(d[14]), "+f"(d[15]),
          "+f"(d[16]), "+f"(d[17]), "+f"(d[18]), "+f"(d[19]), "+f"(d[20]), "+f"(d[21]), "+f"(d[22]), "+f"(d[23]),
          "+f"(d[24]), "+f"(d[25]), "+f"(d[26]), "+f"(d[27]), "+f"(d[28]), "+f"(d[29]), "+f"(d[30]), "+f"(d[31])
        : "l"(descA), "l"(descB), "r"(scaleD));
}

__device__ __forceinline__ void wgmma_n64_ss_z(float (&d)[32], uint64_t descA, uint64_t descB) {
    asm volatile("{\n.reg .pred p;\nsetp.ne.b32 p, 0, 0;\n"
        "wgmma.mma_async.sync.aligned.m64n64k16.f32.bf16.bf16 {"
        "%0, %1, %2, %3, %4, %5, %6, %7, %8, %9, %10, %11, %12, %13, %14, %15, "
        "%16, %17, %18, %19, %20, %21, %22, %23, %24, %25, %26, %27, %28, %29, %30, %31}, "
        "%32, %33, p, 1, 1, 0, 0;\n}\n"
        : "=f"(d[0]), "=f"(d[1]), "=f"(d[2]), "=f"(d[3]), "=f"(d[4]), "=f"(d[5]), "=f"(d[6]), "=f"(d[7]),
          "=f"(d[8]), "=f"(d[9]), "=f"(d[10]), "=f"(d[11]), "=f"(d[12]), "=f"(d[13]), "=f"(d[14]), "=f"(d[15]),
          "=f"(d[16]), "=f"(d[17]), "=f"(d[18]), "=f"(d[19]), "=f"(d[20]), "=f"(d[21]), "=f"(d[22]), "=f"(d[23]),
          "=f"(d[24]), "=f"(d[25]), "=f"(d[26]), "=f"(d[27]), "=f"(d[28]), "=f"(d[29]), "=f"(d[30]), "=f"(d[31])
        : "l"(descA), "l"(descB));
}

__device__ __forceinline__ void wgmma_n24_rs_tb(float (&d)[12], uint32_t a0, uint32_t a1, uint32_t a2, uint32_t a3, uint64_t descB, int scaleD) {
    asm volatile("{\n.reg .pred p;\nsetp.ne.b32 p, %17, 0;\n"
        "wgmma.mma_async.sync.aligned.m64n24k16.f32.bf16.bf16 {"
        "%0, %1, %2, %3, %4, %5, %6, %7, %8, %9, %10, %11}, "
        "{%12, %13, %14, %15}, %16, p, 1, 1, 1;\n}\n"
        : "+f"(d[0]), "+f"(d[1]), "+f"(d[2]), "+f"(d[3]), "+f"(d[4]), "+f"(d[5]), "+f"(d[6]), "+f"(d[7]),
          "+f"(d[8]), "+f"(d[9]), "+f"(d[10]), "+f"(d[11])
        : "r"(a0), "r"(a1), "r"(a2), "r"(a3), "l"(descB), "r"(scaleD));
}

__device__ __forceinline__ void cnt_signal(int idx) {
    asm volatile("fence.acq_rel.gpu;\nred.relaxed.gpu.global.add.u32 [%0], 1;"
                 ::"l"(g_cnt + idx * 32) : "memory");
}
__device__ __forceinline__ void cnt_wait(int idx, uint32_t target) {
    const uint32_t* p = g_cnt + idx * 32;
#pragma unroll 1
    for (uint32_t i = 0; i < (1u << 22); i++) {
        uint32_t v;
        asm volatile("ld.acquire.gpu.global.u32 %0, [%1];" : "=r"(v) : "l"(p) : "memory");
        if ((int32_t)(v - target) >= 0) break;
    }
    asm volatile("fence.proxy.async.global;" ::: "memory");
}
__device__ __forceinline__ void cluster_arrive() { asm volatile("barrier.cluster.arrive.release.aligned;" ::: "memory"); }
__device__ __forceinline__ void cluster_arrive_relaxed() { asm volatile("barrier.cluster.arrive.relaxed.aligned;" ::: "memory"); }
__device__ __forceinline__ void cluster_wait() { asm volatile("barrier.cluster.wait.acquire.aligned;" ::: "memory"); }
__device__ __forceinline__ void bulk_wait_read() { asm volatile("cp.async.bulk.wait_group.read 0;" ::: "memory"); }

__device__ __forceinline__ float gelu_half(float hx) {
    const float u = hx * fmaf(hx * hx, 8.f * 0.035677408136300125f, 2.f * 0.7978845608028654f);
    float t;
    asm("tanh.approx.f32 %0, %1;" : "=f"(t) : "f"(u));
    return fmaf(hx, t, hx);
}
__device__ __forceinline__ void release_stage(uint32_t bar, uint32_t peer, int lane) {
    if (lane == 0) { mbar_arrive(bar); mbar_arrive_cluster(bar, peer); }
}

constexpr int SM_RING = 163840;
constexpr int SM_Q = 0, SM_ZERO = 24576, SM_K = SM_ZERO + 3072, SM_V = SM_K + IMG_BYTES;
constexpr int G2_STAGE = 8192 + 20480;
__device__ __forceinline__ uint32_t g2_slot(int i) { return SM_K + ((0x4326150 >> (4 * i)) & 7) * G2_STAGE; }
constexpr int SM_MISC = 229376;
constexpr int SM_BIAS = SM_MISC, SM_RED = SM_BIAS + 384, SM_BAR = SM_RED + 128;
constexpr int B_A = 0, B_F1 = 10, B_E1 = 14, B_F2 = 18, B_E2 = 23, B_KV = 28, B_Q = 45, B_F3 = 47, B_E3 = 55, B_ST = 63, B_STAT = 65, B_AUX = 66, B_AUX2 = 67, B_DEAD = 68, B_PF = 70, B_COUNT = 73;
constexpr int SM_EPOCH = SM_BAR + 584, SM_SAFE = SM_EPOCH + 4;
constexpr int SM_CS = SM_EPOCH + 8;
constexpr int SM_TOTAL = SM_CS + 1728;
static_assert(SM_TOTAL <= 232448, "shared memory budget");

struct Maps { CUtensorMap x, wqkv, w1, h, o, wo, w2; };

__device__ __forceinline__ uint32_t bf2_fma(uint32_t a, uint32_t b, uint32_t c) {
    uint32_t r;
    asm("fma.rn.bf16x2 %0, %1, %2, %3;" : "=r"(r) : "r"(a), "r"(b), "r"(c));
    return r;
}
__device__ __forceinline__ uint32_t lop_and_or(uint32_t a, uint32_t m, uint32_t o) {
    uint32_t r;
    asm("lop3.b32 %0, %1, %2, %3, 0xEA;" : "=r"(r) : "r"(a), "r"(m), "r"(o));
    return r;
}
struct ExpConst { uint32_t mask, slope; };
__device__ __forceinline__ ExpConst make_exp_const() {
    ExpConst k;
    asm volatile("mov.b32 %0, 0x007F007F;" : "=r"(k.mask));
    asm volatile("mov.b32 %0, 0x3EF83EF8;" : "=r"(k.slope));
    return k;
}
__device__ __forceinline__ uint32_t exp2_pair_fma(float t0, float t1, const ExpConst& k) {
    const uint32_t L = __byte_perm(__float_as_uint(t0), __float_as_uint(t1), 0x6521);
    const uint32_t g = lop_and_or(L, k.mask, 0x3F803F80u);
    const uint32_t u = bf2_fma(g, k.slope, 0xBF37BF37u);
    const uint32_t e = bf2_fma(u, u, 0xBD71BD71u);
    return bf2_fma(L, e, L);
}
template <int SHIFT>
__device__ __forceinline__ void exp_tile(const float (&s)[32], uint32_t (&p)[16], const ExpConst& k) {
#pragma unroll
    for (int b = 0; b < 8; b++) {
        if ((EMU_MASK >> (b + SHIFT)) & 1) {
            p[2 * b] = exp2_pair_fma(s[4 * b], s[4 * b + 1], k);
            p[2 * b + 1] = exp2_pair_fma(s[4 * b + 2], s[4 * b + 3], k);
        } else {
            p[2 * b] = pack_bf16(ex2(s[4 * b]), ex2(s[4 * b + 1]));
            p[2 * b + 1] = pack_bf16(ex2(s[4 * b + 2]), ex2(s[4 * b + 3]));
        }
    }
}

__device__ __forceinline__ void qk_tile(float (&s)[32], uint64_t dQ, uint64_t dQ2, uint64_t dK) {
    wg_fence();
    wgmma_n64_ss_z(s, dQ, dK);
    wgmma_n64_ss(s, dQ2, dK + 16, 1);
    wg_commit();
}
__device__ __forceinline__ void pv_tile(float (&o)[12], const uint32_t (&p)[16], uint64_t dV) {
    wg_fence();
#pragma unroll
    for (int ks = 0; ks < 4; ks++)
        wgmma_n24_rs_tb(o, p[4 * ks], p[4 * ks + 1], p[4 * ks + 2], p[4 * ks + 3], dV + ks * 48, 1);
    wg_commit();
}
__device__ __forceinline__ void store_o(const float (&o)[12], int h, int rbase, int lane) {
    const int g = lane >> 2, c = lane & 3;
    const bool odd = h & 1;
    const int lsrc = (lane & ~3) | (odd ? 0 : 2);
    const float i0 = 1.f / __shfl_sync(~0u, o[8], lsrc), i1 = 1.f / __shfl_sync(~0u, o[10], lsrc);
    __nv_bfloat16* dst = g_o + (size_t)(rbase + g) * DM + h * 20;
    const int d0 = (odd ? 4 : 0) + 2 * c, d1 = d0 + 8, d2 = odd ? 2 * c - 4 : 16 + 2 * c;
    *(uint32_t*)(dst + d0) = pack_bf16(o[0] * i0, o[1] * i0);
    *(uint32_t*)(dst + d1) = pack_bf16(o[4] * i0, o[5] * i0);
    *(uint32_t*)(dst + 8 * DM + d0) = pack_bf16(o[2] * i1, o[3] * i1);
    *(uint32_t*)(dst + 8 * DM + d1) = pack_bf16(o[6] * i1, o[7] * i1);
    if (odd ? (c >= 2) : (c < 2)) {
        *(uint32_t*)(dst + d2) = pack_bf16(o[8] * i0, o[9] * i0);
        *(uint32_t*)(dst + 8 * DM + d2) = pack_bf16(o[10] * i1, o[11] * i1);
    }
}

__device__ __forceinline__ void attn_rows_maxshift(uint32_t sK, uint32_t barKV, uint64_t dQ, uint64_t dQ2, int h, int rbase) {
    const int lane = threadIdx.x & 31;
    const uint64_t dK0 = make_desc(sK, 128, 384, 0), dV0 = make_desc(sK + IMG_BYTES, 384, 128, 0);
    float o[12], s[32];
    uint32_t p[16];
#pragma unroll
    for (int i = 0; i < 12; i++) o[i] = 0.f;
    float m0 = -3.0e38f, m1 = -3.0e38f;
    mbar_wait(barKV + 128, 0);
#pragma unroll 1
    for (int t = 0; t < 32; t++) {
        mbar_wait(barKV + (t >> 1) * 8, 0);
        qk_tile(s, dQ, dQ2, dK0 + t * 192);
        wg_wait<0>();
        fence_regs(s);
        const uint32_t mask = EMU_MASK >> ((t & 1) * 8);
        float n0 = m0, n1 = m1;
#pragma unroll
        for (int b = 0; b < 8; b++) {
            const bool emu = (mask >> b) & 1;
            const float f = emu ? 0.5f : 1.f, off = emu ? -383.00390625f : 0.f;
#pragma unroll
            for (int i = 0; i < 4; i++) s[4 * b + i] = fmaf(s[4 * b + i], f, off);
            n0 = fmaxf(n0, fmaxf(s[4 * b], s[4 * b + 1]));
            n1 = fmaxf(n1, fmaxf(s[4 * b + 2], s[4 * b + 3]));
        }
        n0 = fmaxf(n0, __shfl_xor_sync(~0u, n0, 1)); n0 = fmaxf(n0, __shfl_xor_sync(~0u, n0, 2));
        n1 = fmaxf(n1, __shfl_xor_sync(~0u, n1, 1)); n1 = fmaxf(n1, __shfl_xor_sync(~0u, n1, 2));
        const float c0 = ex2(m0 - n0), c1 = ex2(m1 - n1);
        m0 = n0; m1 = n1;
#pragma unroll
        for (int b = 0; b < 3; b++) { o[4 * b] *= c0; o[4 * b + 1] *= c0; o[4 * b + 2] *= c1; o[4 * b + 3] *= c1; }
#pragma unroll
        for (int b = 0; b < 8; b++) {
            p[2 * b] = pack_bf16(ex2(s[4 * b] - m0), ex2(s[4 * b + 1] - m0));
            p[2 * b + 1] = pack_bf16(ex2(s[4 * b + 2] - m1), ex2(s[4 * b + 3] - m1));
        }
        pv_tile(o, p, dV0 + (((t >> 1) + 7) & 15) * 384 + (t & 1) * 192);
        wg_wait<0>();
        fence_regs(o);
    }
    store_o(o, h, rbase, lane);
}

__global__ void __launch_bounds__(512, 1) __cluster_dims__(2, 1, 1)
k_fused(const __grid_constant__ Maps tm, const __nv_bfloat16* __restrict__ x, const uint8_t* __restrict__ wqkv,
        const uint8_t* __restrict__ w1, const uint8_t* __restrict__ w2, const uint8_t* __restrict__ wo,
        const __nv_bfloat16* __restrict__ b1, const __nv_bfloat16* __restrict__ b2, __nv_bfloat16* __restrict__ out) {
    extern __shared__ __align__(1024) uint8_t smem[];
    const uint32_t sb = smem_u32(smem);
    const uint32_t bar = sb + SM_BAR;
    const int warp = __shfl_sync(~0u, threadIdx.x >> 5, 0), lane = threadIdx.x & 31;
    const int wgi = warp >> 2, w4 = warp & 3, g = lane >> 2, c = lane & 3;
    const uint32_t rank = blockIdx.x & 1, peer = rank ^ 1;
    const int cl = blockIdx.x >> 1;
    const int cg = cl >> 3, rb = (cl & 7) * 2 + rank;

    if (threadIdx.x == 0) TL(0, 0);
    if (warp == 15 && lane < 4) prefetch_map(lane == 0 ? &tm.x : lane == 1 ? &tm.wqkv : lane == 2 ? &tm.w1 : &tm.h);
    if (elect_one()) {
#pragma unroll
        for (int j = 0; j < 5; j++) {
            const int i = warp * 5 + j;
            const int cnt = i >= B_PF ? 32 : (i >= B_E1 && i < B_F2) || (i >= B_E2 && i < B_KV) ? 16
                          : (i >= B_E3 && i <= B_ST + 1) || i == B_STAT || i == B_DEAD || i == B_DEAD + 1 ? 8 : i == B_AUX ? 4 : i == B_AUX2 ? 3 : 1;
            if (i < B_COUNT) mbar_init(bar + i * 8, cnt);
        }
        fence_barrier_init();
    }
    __syncthreads();
    if (threadIdx.x == 0) TL(0, 1);
    cluster_arrive_relaxed();
    cluster_wait();
    if (threadIdx.x == 0) TL(0, 3);

    {
        const uint32_t sB = sb + SM_RING;
        if (threadIdx.x == 0) TL(1, 0);
        if (wgi < 2) {
            reg_dealloc<56>();
            if (warp == 0) {
#pragma unroll 1
                for (int it = 0; it < 20; it++) {
                    const int s = it & 3;
                    const int kb = it < 2 ? it : (it & 1) ? (it + 1) >> 1 : 10;
                    if (it >= 4) mbar_wait(bar + (B_E1 + s) * 8, ((it >> 2) - 1) & 1);
                    else if (it > 0) __nanosleep(PACE_NS);
                    if (elect_one()) {
                        if (kb < 10) {
                            mbar_expect_tx(bar + (B_A + kb) * 8, 16384);
                            tma_load(sb + kb * 16384, &tm.x, kb * 64, rb * 128, bar + (B_A + kb) * 8);
                        }
                        const uint32_t dst = sB + s * 16384 + rank * 8192, fb = bar + (B_F1 + s) * 8;
                        const int c0 = cg * 240 + rank * 128;
                        mbar_expect_tx(fb, 16384);
                        tma_load_mc(dst, &tm.wqkv, c0, it * 32, fb, 3);
                        tma_load_mc(dst + 4096, &tm.wqkv, c0 + 64, it * 32, fb, 3);
                    }
                    __syncwarp();
                }
#pragma unroll 1
                for (int it = 0; it < 20; it++) {
                    const int s = it % 5;
                    if (it < 5) { if (it != 3) mbar_wait(bar + (B_E1 + (it == 4 ? 3 : it)) * 8, 0); }
                    else mbar_wait(bar + (B_E2 + s) * 8, ((it / 5) - 1) & 1);
                    if (elect_one()) {
                        const uint32_t dst = sB + s * 12288, fb = bar + (B_F2 + s) * 8;
                        mbar_expect_tx(fb, 12288);
                        if ((it & 1) == (int)rank) {
                            tma_load_mc(dst, &tm.w1, cg * 192, it * 32, fb, 3);
                            tma_load_mc(dst + 4096, &tm.w1, cg * 192 + 64, it * 32, fb, 3);
                        } else {
                            tma_load_mc(dst + 8192, &tm.w1, cg * 192 + 128, it * 32, fb, 3);
                        }
                    }
                    __syncwarp();
                }
            } else {
                const int ht = threadIdx.x - 32;
                if (ht == 160) *reinterpret_cast<volatile uint32_t*>(smem + SM_EPOCH) = *(volatile uint32_t*)&g_epoch;
                auto slab_sum = [&](const uint32_t* src, int pitch) {
                    float s0 = 0.f, s1 = 0.f;
                    uint32_t v[40];
#pragma unroll
                    for (int k = 0; k < 40; k++) v[k] = __ldg(src + k * pitch);
#pragma unroll
                    for (int k = 0; k < 40; k++) { s0 += bf_lo(v[k]); s1 += bf_hi(v[k]); }
                    return make_float2(s0, s1);
                };
                auto gather = [&](int idx) {
                    float s0 = 0.f, s1 = 0.f;
#pragma unroll
                    for (int r = 0; r < 16; r++) {
                        const float2 v = __ldcg(g_csp + r * 1728 + cg * 216 + idx);
                        s0 += v.x; s1 += v.y;
                    }
                    reinterpret_cast<float2*>(smem + SM_CS)[idx] = make_float2(s0, s1);
                };
                if (warp == 7) {
                    mbar_wait(bar + B_STAT * 8, 0);
                    if (elect_one()) cnt_signal(CNT_ST + rb);
                    __syncwarp();
                }
                if (ht < 120)
                    g_csp[rb * 1728 + cg * 216 + ht] = slab_sum(reinterpret_cast<const uint32_t*>(wqkv) + rb * 40 * 960 + cg * 120 + ht, 960);
                if (threadIdx.x == 64) IT(3, 0);
                if (threadIdx.x == 192) IT(3, 1);
                if (warp != 7) asm volatile("bar.sync 8, 192;" ::: "memory");
                const uint32_t epoch = *reinterpret_cast<volatile uint32_t*>(smem + SM_EPOCH);
                if (warp == 6) { if (elect_one()) cnt_signal(CNT_CS + cg); __syncwarp(); }

                if (threadIdx.x == 64) IT(3, 2);
                if (warp <= 4) {
                    if (lane == 0) { cnt_wait(CNT_CS + cg, (epoch + 1) * 16); cnt_wait(CNT_ST + rb, (epoch + 1) * 8); }
                    __syncwarp();
                    if (threadIdx.x == 64) IT(3, 4);
                    if (ht < 120) gather(ht);
                    __syncwarp();
                    if (threadIdx.x == 64) IT(3, 5);
                    if (lane == 0) mbar_arrive(bar + B_AUX * 8);
                }
                if (ht >= 128) {
                    g_csp[rb * 1728 + cg * 216 + 120 + (ht - 128)] = slab_sum(reinterpret_cast<const uint32_t*>(w1) + rb * 40 * 768 + cg * 96 + (ht - 128), 768);
                    reinterpret_cast<uint32_t*>(smem + SM_BIAS)[ht - 128] =
                        bf2_fma(__ldg(reinterpret_cast<const uint32_t*>(b1 + cg * 192) + (ht - 128)), 0x3F003F00u, 0x80008000u);
                    asm volatile("bar.sync 9, 96;" ::: "memory");
                    const uint32_t epoch2 = *reinterpret_cast<volatile uint32_t*>(smem + SM_EPOCH);
                    if (warp == 5) { if (elect_one()) cnt_signal(CNT_CS2 + cg); __syncwarp(); }
                    if (warp == 6 && elect_one()) {
                        prefetch_l2(w2 + blockIdx.x * 15360, 15360);
                        prefetch_l2(wo + blockIdx.x * 6400, 6400);
                    }
                    if (lane == 0) cnt_wait(CNT_CS2 + cg, (epoch2 + 1) * 16);
                    __syncwarp();
                    gather(120 + (ht - 128));
                    __syncwarp();
                    if (lane == 0) mbar_arrive(bar + B_AUX2 * 8);
                }
                if (warp == 4) {
                    mbar_wait(bar + B_ST * 8, 0);
                    if (elect_one()) cnt_signal(CNT_QKV + cg);
                    __syncwarp();
                }
                const int h = blockIdx.x >> 2, qb = blockIdx.x & 3;
                const uint32_t ep = *reinterpret_cast<volatile uint32_t*>(smem + SM_EPOCH);
                if (lane == 0 && warp != 5) {
                    cnt_wait(CNT_QKV + h / 12, (ep + 1) * 16);
                    cnt_wait(CNT_QKV + (32 + h) / 12, (ep + 1) * 16);
                    cnt_wait(CNT_QKV + (64 + h) / 12, (ep + 1) * 16);
                }
                __syncwarp();
                if (threadIdx.x == 64) TL(5, 0);
                if (warp == 1 || warp == 4 || warp >= 6) {
                    const int w = warp == 1 ? 0 : warp == 4 ? 1 : warp - 4, t = w * 32 + lane;
                    float kmax = 0.f, qmax = 0.f;
#pragma unroll
                    for (int i = 0; i < 4; i++) {
                        const float4 v = __ldcg(reinterpret_cast<const float4*>(g_nrm + (32 + h) * SEQ) + t + i * 128);
                        kmax = fmaxf(fmaxf(kmax, fmaxf(v.x, v.y)), fmaxf(v.z, v.w));
                    }
                    {
                        const float4 v = __ldcg(reinterpret_cast<const float4*>(g_nrm + h * SEQ + qb * 512) + t);
                        qmax = fmaxf(fmaxf(v.x, v.y), fmaxf(v.z, v.w));
                    }
#pragma unroll
                    for (int o = 16; o; o >>= 1) {
                        kmax = fmaxf(kmax, __shfl_xor_sync(~0u, kmax, o));
                        qmax = fmaxf(qmax, __shfl_xor_sync(~0u, qmax, o));
                    }
                    float* red = reinterpret_cast<float*>(smem + SM_RED);
                    if (lane == 0) { red[w] = kmax; red[8 + w] = qmax; }
                    asm volatile("bar.sync 8, 128;" ::: "memory");
                    if (warp == 1 && lane == 0) {
                        for (int u = 1; u < 4; u++) { kmax = fmaxf(kmax, red[u]); qmax = fmaxf(qmax, red[8 + u]); }
                        *reinterpret_cast<volatile uint32_t*>(smem + SM_SAFE) = kmax * qmax * 1.1f <= SAFE_BOUND * SAFE_BOUND;
                    }
                }
                const uint32_t barKV = bar + B_KV * 8;
                const uint8_t* gK = g_img + (size_t)(32 + h) * IMG_BYTES;
                const uint8_t* gV = g_img + (size_t)(64 + h) * IMG_BYTES;
                if (warp == 2) {
                    if (lane == 0) TL(5, 1);
                    mbar_wait(bar + B_DEAD * 8, 0);
                    if (lane == 0) TL(5, 2);
                    for (int i = lane; i < 192; i += 32) *reinterpret_cast<uint4*>(smem + SM_ZERO + i * 16) = make_uint4(0, 0, 0, 0);
                    fence_proxy_async();
                    __syncwarp();
                    if (elect_one()) {
                        asm volatile("fence.proxy.async.global;" ::: "memory");
                        const uint8_t* gQ = g_img + (size_t)h * IMG_BYTES + qb * 64 * 384;
                        mbar_expect_tx(barKV + 128, 6144);
                        bulk_load(sb + SM_K, gK, 6144, barKV + 128);
                        for (int p = 0; p < 2; p++) {
                            mbar_expect_tx(bar + (B_Q + p) * 8, 12288);
                            bulk_load(sb + SM_Q + p * 12288, gQ + p * 12288, 12288, bar + (B_Q + p) * 8);
                        }
                        for (int i = 0; i < 13; i++) {
                            mbar_expect_tx(barKV + i * 8, 12288);
                            bulk_load(sb + SM_K + (i + 1) * 6144, gK + (i + 1) * 6144, 6144, barKV + i * 8);
                        }
                    }
                    __syncwarp();
                    if (lane == 0) TL(5, 3);
                } else if (warp == 5) {
                    mbar_wait(bar + (B_ST + 1) * 8, 0);
                    if (lane == 0) {
                        for (int b = 0; b < 6; b++)
                            tma_store(&tm.h, sb + (7 + b % 3) * 16384 + (b / 3) * 8192, cg * 192 + (b % 3) * 64, rb * 128 + (b / 3) * 64);
                        bulk_commit();
                    }
                    __syncwarp();
                } else if (warp == 3) {
                    mbar_wait(bar + (B_DEAD + 1) * 8, 0);
                    if (elect_one()) {
                        asm volatile("fence.proxy.async.global;" ::: "memory");
                        for (int i = 0; i < 9; i++) bulk_load(sb + SM_V + (i + 7) * 6144, gV + i * 6144, 6144, barKV + i * 8);
                    }
                    __syncwarp();
                }
            }
            if (lane == 0) TL(6, warp);
            asm volatile("bar.sync %0, 128;" ::"r"(wgi + 3) : "memory");
            reg_alloc<128>();
        } else {
            reg_alloc<200>();
            const int wi = wgi - 2;
            const int row0 = rb * 128 + wi * 64 + w4 * 16 + g;
            const uint32_t sAw = sb + wi * 8192;
            const int rbk = row0 >> 3, hs0 = cg * 12;
            {
                const int srow = rb * 128 + cg * 16 + (warp - 8) * 2 + (lane >> 4);
                uint4 xv[5];
#pragma unroll
                for (int i = 0; i < 5; i++) xv[i] = __ldg(reinterpret_cast<const uint4*>(x + (size_t)srow * DM) + (lane & 15) + 16 * i);
                float sm = 0.f;
#pragma unroll
                for (int i = 0; i < 5; i++)
                    sm += ((bf_lo(xv[i].x) + bf_hi(xv[i].x)) + (bf_lo(xv[i].y) + bf_hi(xv[i].y))) +
                          ((bf_lo(xv[i].z) + bf_hi(xv[i].z)) + (bf_lo(xv[i].w) + bf_hi(xv[i].w)));
#pragma unroll
                for (int o = 8; o; o >>= 1) sm += __shfl_xor_sync(~0u, sm, o);
                const float mu = sm * (1.f / DM);
                float q0 = 0.f, q1 = 0.f;
#pragma unroll
                for (int i = 0; i < 5; i++) {
                    const uint32_t w[4] = {xv[i].x, xv[i].y, xv[i].z, xv[i].w};
#pragma unroll
                    for (int j = 0; j < 4; j++) {
                        const float d0 = bf_lo(w[j]) - mu, d1 = bf_hi(w[j]) - mu;
                        q0 = fmaf(d0, d0, q0); q1 = fmaf(d1, d1, q1);
                    }
                }
                float q = q0 + q1;
#pragma unroll
                for (int o = 8; o; o >>= 1) q += __shfl_xor_sync(~0u, q, o);
                const float var = q * (1.f / DM);
                const float r1 = rsqrtf(var + LN_EPS);
                const float r2 = rsqrtf(var * r1 * r1 + LN_EPS);
                if ((lane & 15) == 0) g_stat[srow] = make_float4(mu, r1, r1 * r2, 0.f);
                __syncwarp();
                if (lane == 0) mbar_arrive(bar + B_STAT * 8);
            }
            float accA[100], accB[20];
            const uint64_t dA0 = make_desc(sAw, 16, 1024, 1), dB0 = make_desc(sB, 4096, 1024, 1);
#pragma unroll 2
            for (int it = 0; it < 20; it++) {
                const int s = it & 3;
                if (!(it & 1)) mbar_wait(bar + (B_A + (it >> 1)) * 8, 0);
                if (threadIdx.x == 256 && it == 0) TL(0, 2);
                if (threadIdx.x == 256) IT(0, it);
                mbar_wait(bar + (B_F1 + s) * 8, (it >> 2) & 1);
                if (threadIdx.x == 256) IT(1, it);
                const uint64_t dA = dA0 + (it >> 1) * 1024 + (it & 1) * 4, dB = dB0 + s * 1024;
                wg_fence();
                wgmma_n40_ss_tb(accB, dA, dB + 769, it > 0);
                wgmma_n40_ss_tb(accB, dA + 2, dB + 769 + 128, 1);
                wgmma_n200_ss_tb(accA, dA, dB, it > 0);
                wgmma_n200_ss_tb(accA, dA + 2, dB + 128, 1);
                wg_commit();
                if (it > 0) { wg_wait<1>(); release_stage(bar + (B_E1 + ((it - 1) & 3)) * 8, peer, lane); }
            }
            if (threadIdx.x == 256) IT(2, 0);
            mbar_wait(bar + B_AUX * 8, 0);
            if (threadIdx.x == 256) IT(2, 1);
            const float4 st0 = __ldcg(g_stat + row0), st1 = __ldcg(g_stat + row0 + 8);
            wg_wait<0>();
            release_stage(bar + (B_E1 + 3) * 8, peer, lane);
            fence_regs(accA);
            fence_regs(accB);
            if (threadIdx.x == 256) TL(1, 1);
            const float2* cs = reinterpret_cast<const float2*>(smem + SM_CS) + c;
            uint8_t* img = g_img + (size_t)hs0 * IMG_BYTES + rbk * 384 + g * 16 + c * 4;
            const bool emu0 = (EMU_MASK >> (rbk & 15)) & 1, emu1 = (EMU_MASK >> ((rbk + 1) & 15)) & 1;
            const bool low = c < 2;
            uint32_t pk[60];
#pragma unroll
            for (int m = 0; m < 6; m++) {
                const int which = (hs0 + 2 * m) >> 5;
                const float m0 = st0.y * (which == 0 ? QSCALE : (which == 1 && emu0) ? 2.f : 1.f);
                const float m1 = st1.y * (which == 0 ? QSCALE : (which == 1 && emu1) ? 2.f : 1.f);
                const float d0 = -st0.x * m0, d1 = -st1.x * m1;
                const float* a = m < 5 ? &accA[20 * m] : accB;
#pragma unroll
                for (int b = 0; b < 5; b++) {
                    const float2 cv = cs[(5 * m + b) * 4];
                    pk[10 * m + 2 * b] = pack_bf16(fmaf(a[4 * b], m0, d0 * cv.x), fmaf(a[4 * b + 1], m0, d0 * cv.y));
                    pk[10 * m + 2 * b + 1] = pack_bf16(fmaf(a[4 * b + 2], m1, d1 * cv.x), fmaf(a[4 * b + 3], m1, d1 * cv.y));
                }
            }
            const float r20 = 0.5f * st0.z, r21 = 0.5f * st1.z, e20 = -st0.x * r20, e21 = -st1.x * r21;
            if (threadIdx.x == 256) IT(2, 2);
            float acc2[96];
#pragma unroll
            for (int it = 0; it < 20; it++) {
                const int s = it % 5;
                if (threadIdx.x == 256) IT(0, 20 + it);
                mbar_wait(bar + (B_F2 + s) * 8, (it / 5) & 1);
                if (threadIdx.x == 256) IT(1, 20 + it);
                wg_fence();
                const uint64_t dA = make_desc(sAw + (it >> 1) * 16384 + (it & 1) * 64, 16, 1024, 1);
                const uint64_t dB = make_desc(sB + s * 12288, 4096, 1024, 1);
                if (it == 0) wgmma_n192_ss_tb_z(acc2, dA, dB); else wgmma_n192_ss_tb(acc2, dA, dB, 1);
                wgmma_n192_ss_tb(acc2, dA + 2, dB + 128, 1);
                wg_commit();
                if (it > 0) {
                    wg_wait<1>();
                    if (it <= 15) release_stage(bar + (B_E2 + (it - 1) % 5) * 8, peer, lane);
                    if (it == 14 && lane == 0) mbar_arrive(bar + B_DEAD * 8);
                }
                if (it < 6) {
                    const int m = it;
                    const int hs = hs0 + 2 * m, which = hs >> 5;
                    const uint32_t* a = pk + 10 * m;
                    uint8_t* pe = img + (2 * m) * IMG_BYTES;
                    uint8_t* po = pe + IMG_BYTES;
                    const uint32_t padv = which == 0 ? 0x3F803F80u : which == 1 ? 0xBFFF4440u : 0x00003F80u;
                    const uint32_t p0 = ((c & 1) || (which == 1 && !emu0)) ? 0u : padv;
                    const uint32_t p1 = ((c & 1) || (which == 1 && !emu1)) ? 0u : padv;
                    *(uint32_t*)(pe) = a[0];
                    *(uint32_t*)(pe + 128) = a[2];
                    *(uint32_t*)(pe + 256) = low ? a[4] : p0;
                    *(uint32_t*)(pe + 384) = a[1];
                    *(uint32_t*)(pe + 512) = a[3];
                    *(uint32_t*)(pe + 640) = low ? a[5] : p1;
                    *(uint32_t*)(po) = a[6];
                    *(uint32_t*)(po + 128) = a[8];
                    *(uint32_t*)(po + 256) = low ? p0 : a[4];
                    *(uint32_t*)(po + 384) = a[7];
                    *(uint32_t*)(po + 512) = a[9];
                    *(uint32_t*)(po + 640) = low ? p1 : a[5];
                    if (which < 2) {
                        const uint32_t u0 = bf2_fma(a[4], a[4], 0u), u1 = bf2_fma(a[5], a[5], 0u);
                        const uint32_t pe0 = bf2_fma(a[0], a[0], bf2_fma(a[2], a[2], low ? u0 : 0u));
                        const uint32_t pe1 = bf2_fma(a[1], a[1], bf2_fma(a[3], a[3], low ? u1 : 0u));
                        const uint32_t po0 = bf2_fma(a[6], a[6], bf2_fma(a[8], a[8], low ? 0u : u0));
                        const uint32_t po1 = bf2_fma(a[7], a[7], bf2_fma(a[9], a[9], low ? 0u : u1));
                        const float e0 = bf_lo(pe0) + bf_hi(pe0), e1 = bf_lo(pe1) + bf_hi(pe1);
                        const float o0 = bf_lo(po0) + bf_hi(po0), o1 = bf_lo(po1) + bf_hi(po1);
                        const bool b0 = c & 1, b1_ = c & 2;
                        const float x0 = (b0 ? e1 : e0) + __shfl_xor_sync(~0u, b0 ? e0 : e1, 1);
                        const float x1 = (b0 ? o1 : o0) + __shfl_xor_sync(~0u, b0 ? o0 : o1, 1);
                        float y = (b1_ ? x1 : x0) + __shfl_xor_sync(~0u, b1_ ? x0 : x1, 2);
                        if (which == 1 && (b0 ? emu1 : emu0)) y *= 0.25f;
                        g_nrm[(hs + (c >> 1)) * SEQ + row0 + (c & 1) * 8] = y;
                    }
                    if (it == 5) { __syncwarp(); if (lane == 0) mbar_arrive(bar + B_ST * 8); }
                }
            }
            wg_wait<0>();
            fence_regs(acc2);
            if (lane == 0) mbar_arrive(bar + (B_DEAD + 1) * 8);
            if (threadIdx.x == 256) TL(1, 2);
            mbar_wait(bar + B_AUX2 * 8, 0);
            if (threadIdx.x == 256) TL(4, 0);
            const uint32_t* bias = reinterpret_cast<const uint32_t*>(smem + SM_BIAS) + c;
            const int mrow = w4 * 16 + (lane & 15);
            const uint32_t stage = sAw + 7 * 16384;
            const uint32_t st_row = stage + mrow * 128;
#pragma unroll
            for (int j = 0; j < 24; j += 2) {
                const uint32_t bA = bias[j * 4], bB = bias[j * 4 + 4];
                const float2 cA = cs[(30 + j) * 4], cB = cs[(31 + j) * 4];
                const float* a = acc2 + j * 4;
                const uint32_t r00 = pack_bf16(gelu_half(fmaf(a[0], r20, fmaf(e20, cA.x, bf_lo(bA)))), gelu_half(fmaf(a[1], r20, fmaf(e20, cA.y, bf_hi(bA)))));
                const uint32_t r10 = pack_bf16(gelu_half(fmaf(a[2], r21, fmaf(e21, cA.x, bf_lo(bA)))), gelu_half(fmaf(a[3], r21, fmaf(e21, cA.y, bf_hi(bA)))));
                const uint32_t r01 = pack_bf16(gelu_half(fmaf(a[4], r20, fmaf(e20, cB.x, bf_lo(bB)))), gelu_half(fmaf(a[5], r20, fmaf(e20, cB.y, bf_hi(bB)))));
                const uint32_t r11 = pack_bf16(gelu_half(fmaf(a[6], r21, fmaf(e21, cB.x, bf_lo(bB)))), gelu_half(fmaf(a[7], r21, fmaf(e21, cB.y, bf_hi(bB)))));
                const int chunk = (j & 7) + (lane >> 4);
                stmatrix_x4(st_row + (j >> 3) * 16384 + ((chunk ^ (mrow & 7)) << 4), r00, r10, r01, r11);
            }
            if (threadIdx.x == 256) TL(4, 1);
            fence_proxy_async();
            __syncwarp();
            if (lane == 0) mbar_arrive(bar + (B_ST + 1) * 8);
            asm volatile("bar.sync %0, 128;" ::"r"(wgi + 3) : "memory");
            reg_dealloc<128>();
            if (threadIdx.x == 256) TL(4, 3);
        }
        __syncthreads();
        if (threadIdx.x == 0) TL(1, 3);
    }

    {
        const int h = blockIdx.x >> 2, qb = blockIdx.x & 3;
        const uint32_t sK = sb + SM_K, sV = sb + SM_V, barKV = bar + B_KV * 8;
        if (threadIdx.x == 0) TL(2, 0);
        auto late_tiles = [&]() {
            if (warp == 5 && lane == 0) {
                bulk_wait_read();
                asm volatile("fence.proxy.async.global;" ::: "memory");
                const uint8_t* gK = g_img + (size_t)(32 + h) * IMG_BYTES;
                const uint8_t* gV = g_img + (size_t)(64 + h) * IMG_BYTES;
                for (int i = 9; i < 16; i++) {
                    if (i >= 13) mbar_expect_tx(barKV + i * 8, i < 15 ? 12288 : 6144);
                    bulk_load(sV + ((i + 7) & 15) * 6144, gV + i * 6144, 6144, barKV + i * 8);
                    if (i >= 13 && i < 15) bulk_load(sK + (i + 1) * 6144, gK + (i + 1) * 6144, 6144, barKV + i * 8);
                }
            }
            __syncwarp();
        };
        const bool safe = __all_sync(~0u, *reinterpret_cast<volatile uint32_t*>(smem + SM_SAFE) != 0);
        if (threadIdx.x == 0) TL(2, 1);
        const uint64_t dK0 = make_desc(sK, 128, 384, 0), dV0 = make_desc(sV, 384, 128, 0);
        auto publish_h = [&]() {
            if (warp == 5) {
                if (lane == 0) { bulk_wait_all(); cnt_signal(CNT_H + rb); }
                __syncwarp();
            }
        };
        auto g2_issue = [&](int kb) {
            const int ct = (blockIdx.x >> 1) & 3, rt = (blockIdx.x >> 3) * 2 + (blockIdx.x & 1);
            const uint32_t dst = sb + g2_slot(kb % 7), fb = bar + (B_F3 + kb % 7) * 8;
            const CUtensorMap* mA = kb < 24 ? &tm.h : &tm.o;
            const CUtensorMap* mB = kb < 24 ? &tm.w2 : &tm.wo;
            const int k0 = (kb < 24 ? kb : kb - 24) * 64;
            mbar_expect_tx(fb, G2_STAGE);
            tma_load(dst, mA, k0, rt * 64, fb);
            const int first = ((kb & 1) == (int)rank) ? 0 : 3, last = ((kb & 1) == (int)rank) ? 3 : 5;
            for (int b = first; b < last; b++) tma_load_mc(dst + 8192 + b * 4096, mB, ct * 160 + b * 32, k0, fb, 3);
        };
        auto pf_arrive = [&](int step) {
            if (lane == 0) { mbar_arrive(bar + (B_PF + step) * 8); mbar_arrive_cluster(bar + (B_PF + step) * 8, peer); }
        };
        auto pf_issue = [&](int step) {
            if (warp == 4) {
                mbar_wait(bar + (B_PF + step) * 8, 0);
                if (elect_one()) {
                    if (step == 0) {
                        cnt_wait(CNT_H + (blockIdx.x >> 3), (*reinterpret_cast<volatile uint32_t*>(smem + SM_EPOCH) + 1) * 8);
                        prefetch_map(&tm.o); prefetch_map(&tm.wo);
                    }
                    g2_issue(2 * step);
                    if (step < 2) g2_issue(2 * step + 1);
                }
                __syncwarp();
            }
        };
        if (!safe) {
            late_tiles();
#pragma unroll 1
            for (int pass = 0; pass < 2; pass++) {
                const uint32_t sQ = sb + SM_Q + pass * 12288 + wgi * 3072;
                mbar_wait(bar + (B_Q + pass) * 8, 0);
                attn_rows_maxshift(sK, barKV, make_desc(sQ, 128, 384, 0), make_desc(sQ + 256, sb + SM_ZERO - (sQ + 256), 384, 0), h,
                                   qb * 512 + pass * 256 + wgi * 64 + w4 * 16);
                if (pass == 0) publish_h();
            }
            pf_arrive(0); pf_arrive(1); pf_arrive(2);
            pf_issue(0); pf_issue(1);
        } else {
            const ExpConst kc = make_exp_const();
#pragma unroll 1
            for (int pass = 0; pass < 2; pass++) {
                const int rbase = qb * 512 + pass * 256 + wgi * 64 + w4 * 16;
                const uint32_t sQ = sb + SM_Q + pass * 12288 + wgi * 3072;
                const uint64_t dQ = make_desc(sQ, 128, 384, 0), dQ2 = make_desc(sQ + 256, sb + SM_ZERO - (sQ + 256), 384, 0);
                float o[12], sa[32], sc[32];
                uint32_t p[16];
#pragma unroll
                for (int i = 0; i < 12; i++) o[i] = 0.f;
                fence_regs(o);
                mbar_wait(bar + (B_Q + pass) * 8, 0);
                mbar_wait(barKV + 128, 0);
                qk_tile(sa, dQ, dQ2, dK0);
                wg_wait<0>();
                fence_regs(sa);
                uint64_t dK = dK0, dV = dV0 + 7 * 384;
                uint32_t bj = barKV;
#pragma unroll 1
                for (int j = 0; j < 16; j++) {
                    mbar_wait(bj, 0);
                    if (pass == 0) {
                        if (j == 2) late_tiles();
                    } else if (j >= 6 && !(j & 1)) {
                        if ((j & 3) == 2) pf_arrive((j - 6) >> 2);
                        else pf_issue((j - 8) >> 2);
                    }
                    qk_tile(sc, dQ, dQ2, dK + 192);
                    wg_wait<1>();
                    exp_tile<0>(sa, p, kc);
                    pv_tile(o, p, dV);
                    wg_wait<1>();
                    fence_regs(sc);
                    mbar_wait(bj, 0);
                    qk_tile(sa, dQ, dQ2, dK + 384);
                    wg_wait<1>();
                    exp_tile<8>(sc, p, kc);
                    pv_tile(o, p, dV + 192);
                    wg_wait<1>();
                    fence_regs(sa);
                    dK += 384; dV = j == 8 ? dV0 : dV + 384; bj += 8;
                }
                wg_wait<0>();
                fence_regs(o);
                store_o(o, h, rbase, lane);
                if (threadIdx.x == 0) TL(2, 2 + pass);
                if (pass == 0) publish_h();
            }
        }
        pf_issue(2);
        __syncthreads();
        if (threadIdx.x == 64) cnt_signal(CNT_O + qb);
        cluster_arrive_relaxed();
    }

    {
        const uint32_t epoch = *reinterpret_cast<volatile uint32_t*>(smem + SM_EPOCH);
        const int ct = cl & 3, rt = (cl >> 2) * 2 + rank;
        if (threadIdx.x == 0) TL(3, 0);
        const int ot = threadIdx.x - 192, orow = ot / 5, oseg = ot - orow * 5;
        const size_t ooff = (size_t)(rt * 64 + orow) * DM + ct * 160 + oseg * 32;
        uint4 xr[4], br[4];
        if (ot >= 0) {
#pragma unroll
            for (int i = 0; i < 4; i++) {
                asm volatile("ld.global.nc.v4.u32 {%0, %1, %2, %3}, [%4];" : "=r"(xr[i].x), "=r"(xr[i].y), "=r"(xr[i].z), "=r"(xr[i].w)
                             : "l"(reinterpret_cast<const uint4*>(x + ooff) + i));
                asm volatile("ld.global.nc.v4.u32 {%0, %1, %2, %3}, [%4];" : "=r"(br[i].x), "=r"(br[i].y), "=r"(br[i].z), "=r"(br[i].w)
                             : "l"(reinterpret_cast<const uint4*>(b2 + ct * 160 + oseg * 32) + i));
            }
        }
        cluster_wait();
        float* stg = reinterpret_cast<float*>(smem);
        if (warp == 4) {
#pragma unroll 1
            for (int kb = 5; kb < 34; kb++) {
                const int s = kb % 7;
                if (kb >= 7) mbar_wait(bar + (B_E3 + s) * 8, ((kb / 7) - 1) & 1);
                if (elect_one()) {
                    if (kb == 24) { cnt_wait(CNT_O + (rt >> 3), (epoch + 1) * 32); TL(3, 1); }
                    const uint32_t dst = sb + g2_slot(s), fb = bar + (B_F3 + s) * 8;
                    const CUtensorMap* mA = kb < 24 ? &tm.h : &tm.o;
                    const CUtensorMap* mB = kb < 24 ? &tm.w2 : &tm.wo;
                    const int k0 = (kb < 24 ? kb : kb - 24) * 64;
                    mbar_expect_tx(fb, G2_STAGE);
                    tma_load(dst, mA, k0, rt * 64, fb);
                    const int first = ((kb & 1) == (int)rank) ? 0 : 3, last = ((kb & 1) == (int)rank) ? 3 : 5;
                    for (int b = first; b < last; b++) tma_load_mc(dst + 8192 + b * 4096, mB, ct * 160 + b * 32, k0, fb, 3);
                }
                __syncwarp();
            }
        } else if (wgi == 0) {
            float acc[80];
#pragma unroll 1
            for (int kb = 0; kb < 34; kb++) {
                const int s = kb % 7;
                mbar_wait(bar + (B_F3 + s) * 8, (kb / 7) & 1);
                const uint64_t dA = make_desc(sb + g2_slot(s), 16, 1024, 1);
                const uint64_t dB = make_desc(sb + g2_slot(s) + 8192, 4096, 512, 2);
                wg_fence();
#pragma unroll
                for (int kk = 0; kk < 4; kk++) wgmma_n160_ss_tb(acc, dA + kk * 2, dB + kk * 64, (kb | kk) != 0);
                wg_commit();
                if (kb > 0) {
                    wg_wait<1>();
                    if (kb <= 27) release_stage(bar + (B_E3 + (kb - 1) % 7) * 8, peer, lane);
                }
            }
            wg_wait<0>();
            fence_regs(acc);
            if (threadIdx.x == 0) TL(3, 2);
            const int r = w4 * 16 + g;
#pragma unroll
            for (int j = 0; j < 20; j++) {
                *reinterpret_cast<float2*>(stg + r * 184 + j * 8 + (j >> 2) * 4 + 2 * c) = make_float2(acc[4 * j], acc[4 * j + 1]);
                *reinterpret_cast<float2*>(stg + (r + 8) * 184 + j * 8 + (j >> 2) * 4 + 2 * c) = make_float2(acc[4 * j + 2], acc[4 * j + 3]);
            }
        }
        __syncthreads();
        if (ot >= 0) {
            const float4* sp = reinterpret_cast<const float4*>(stg + orow * 184 + oseg * 36);
#pragma unroll
            for (int i = 0; i < 4; i++) {
                const float4 a = sp[2 * i], b = sp[2 * i + 1];
                uint4 w;
                w.x = pack_bf16(a.x + bf_lo(br[i].x) + bf_lo(xr[i].x), a.y + bf_hi(br[i].x) + bf_hi(xr[i].x));
                w.y = pack_bf16(a.z + bf_lo(br[i].y) + bf_lo(xr[i].y), a.w + bf_hi(br[i].y) + bf_hi(xr[i].y));
                w.z = pack_bf16(b.x + bf_lo(br[i].z) + bf_lo(xr[i].z), b.y + bf_hi(br[i].z) + bf_hi(xr[i].z));
                w.w = pack_bf16(b.z + bf_lo(br[i].w) + bf_lo(xr[i].w), b.w + bf_hi(br[i].w) + bf_hi(xr[i].w));
                reinterpret_cast<uint4*>(out + ooff)[i] = w;
            }
        }
        if (blockIdx.x == 0 && threadIdx.x == 0) g_epoch = epoch + 1;
        if (threadIdx.x == 256) TL(3, 3);
    }
    cluster_arrive_relaxed();
    cluster_wait();
}

typedef CUresult (*EncodeTiledFn)(CUtensorMap*, CUtensorMapDataType, cuuint32_t, void*, const cuuint64_t*,
                                  const cuuint64_t*, const cuuint32_t*, const cuuint32_t*, CUtensorMapInterleave,
                                  CUtensorMapSwizzle, CUtensorMapL2promotion, CUtensorMapFloatOOBfill);

CUtensorMap make_map(EncodeTiledFn enc, const void* ptr, int rows, int cols, int box_rows, int box_cols,
                     CUtensorMapSwizzle swz) {
    CUtensorMap m;
    cuuint64_t gd[2] = {(cuuint64_t)cols, (cuuint64_t)rows};
    cuuint64_t gs[1] = {(cuuint64_t)cols * 2};
    cuuint32_t bd[2] = {(cuuint32_t)box_cols, (cuuint32_t)box_rows};
    cuuint32_t es[2] = {1, 1};
    enc(&m, CU_TENSOR_MAP_DATA_TYPE_BFLOAT16, 2, const_cast<void*>(ptr), gd, gs, bd, es, CU_TENSOR_MAP_INTERLEAVE_NONE,
        swz, CU_TENSOR_MAP_L2_PROMOTION_L2_128B, CU_TENSOR_MAP_FLOAT_OOB_FILL_NONE);
    return m;
}

}

extern "C" void kernel_launch(void* const* d_in, const int* in_sizes, int n_in, void* d_out, int out_size) {
    (void)in_sizes; (void)n_in; (void)out_size;
    const __nv_bfloat16* x = (const __nv_bfloat16*)d_in[0];
    const __nv_bfloat16* wqkv = (const __nv_bfloat16*)d_in[1];
    const __nv_bfloat16* wo = (const __nv_bfloat16*)d_in[2];
    const __nv_bfloat16* w1 = (const __nv_bfloat16*)d_in[4];
    const __nv_bfloat16* b1 = (const __nv_bfloat16*)d_in[5];
    const __nv_bfloat16* w2 = (const __nv_bfloat16*)d_in[6];
    const __nv_bfloat16* b2 = (const __nv_bfloat16*)d_in[7];
    __nv_bfloat16* out = (__nv_bfloat16*)d_out;

    static EncodeTiledFn enc = nullptr;
    static void *p_h, *p_o;
    if (!enc) {
        cudaDriverEntryPointQueryResult qr;
        cudaGetDriverEntryPoint("cuTensorMapEncodeTiled", (void**)&enc, cudaEnableDefault, &qr);
        cudaGetSymbolAddress(&p_h, g_h);
        cudaGetSymbolAddress(&p_o, g_o);
        cudaFuncSetAttribute(k_fused, cudaFuncAttributeMaxDynamicSharedMemorySize, SM_TOTAL);
    }
    Maps tm;
    tm.x = make_map(enc, x, SEQ, DM, 128, 64, CU_TENSOR_MAP_SWIZZLE_128B);
    tm.wqkv = make_map(enc, wqkv, DM, 3 * DM, 32, 64, CU_TENSOR_MAP_SWIZZLE_128B);
    tm.w1 = make_map(enc, w1, DM, FF, 32, 64, CU_TENSOR_MAP_SWIZZLE_128B);
    tm.h = make_map(enc, p_h, SEQ, FF, 64, 64, CU_TENSOR_MAP_SWIZZLE_128B);
    tm.o = make_map(enc, p_o, SEQ, DM, 64, 64, CU_TENSOR_MAP_SWIZZLE_128B);
    tm.wo = make_map(enc, wo, DM, DM, 64, 32, CU_TENSOR_MAP_SWIZZLE_64B);
    tm.w2 = make_map(enc, w2, FF, DM, 64, 32, CU_TENSOR_MAP_SWIZZLE_64B);
    k_fused<<<128, 512, SM_TOTAL, cudaStreamPerThread>>>(tm, x, (const uint8_t*)wqkv, (const uint8_t*)w1, (const uint8_t*)w2,
                                                         (const uint8_t*)wo, b1, b2, out);
}
```

```cpp
#include <cuda_runtime.h>
#include <cuda_bf16.h>
#include <cuda.h>
#include <stdint.h>

namespace {

constexpr int SEQ = 2048, DM = 640, FF = 1536;
constexpr float LN_EPS = 1e-5f;

constexpr int IMG_BYTES = 256 * 384;
#define EMUM 0xD5D5u
constexpr uint32_t EMU_MASK = EMUM;
constexpr float SAFE_BOUND = 80.0f;
#define XV_IT 1
#define PACE_NS 200
#define NPROD 1
#define SPREAD 2
#define STAT_IT 2
constexpr float QSCALE = 0.22360679774997896f * 1.4426950408889634f;

__device__ float4 g_stat[SEQ];
__device__ float2 g_csp[16 * 1728];
__device__ __align__(1024) uint8_t g_img[96 * IMG_BYTES + 1024];
__device__ float g_nrm[64 * SEQ];
__device__ __align__(1024) __nv_bfloat16 g_h[SEQ * FF];
__device__ __align__(1024) __nv_bfloat16 g_o[SEQ * DM];
constexpr int CNT_ST = 0, CNT_QKV = 16, CNT_H = 24, CNT_O = 40, CNT_CS = 44, CNT_CS2 = 52;
__device__ uint32_t g_cnt[60 * 32];
__device__ uint32_t g_epoch;

#define TL(kern, slot) do { } while (0)
#define IT(row, i) do { } while (0)

__device__ __forceinline__ uint32_t smem_u32(const void* p) { return (uint32_t)__cvta_generic_to_shared(p); }
__device__ __forceinline__ void mbar_init(uint32_t bar, int cnt) {
    asm volatile("mbarrier.init.shared::cta.b64 [%0], %1;" ::"r"(bar), "r"(cnt));
}
__device__ __forceinline__ void mbar_expect_tx(uint32_t bar, uint32_t bytes) {
    asm volatile("mbarrier.arrive.expect_tx.shared::cta.b64 _, [%0], %1;" ::"r"(bar), "r"(bytes) : "memory");
}
__device__ __forceinline__ void mbar_wait(uint32_t bar, uint32_t parity) {
    asm volatile("{\n.reg .pred p;\n.reg .u32 n;\nmov.u32 n, 0;\n"
                 "WAIT_LOOP:\nmbarrier.try_wait.parity.shared::cta.b64 p, [%0], %1;\n@p bra WAIT_DONE;\n"
                 "add.u32 n, n, 1;\nsetp.lt.u32 p, n, 4194304;\n@p bra WAIT_LOOP;\nWAIT_DONE:\n}"
                 ::"r"(bar), "r"(parity) : "memory");
}
__device__ __forceinline__ void mbar_arrive(uint32_t bar) {
    asm volatile("mbarrier.arrive.shared::cta.b64 _, [%0];" ::"r"(bar) : "memory");
}
__device__ __forceinline__ void mbar_arrive_cluster(uint32_t bar, uint32_t cta) {
    asm volatile("{\n.reg .b32 ra;\nmapa.shared::cluster.u32 ra, %0, %1;\n"
                 "mbarrier.arrive.shared::cluster.b64 _, [ra];\n}" ::"r"(bar), "r"(cta) : "memory");
}
__device__ __forceinline__ void fence_barrier_init() { asm volatile("fence.mbarrier_init.release.cluster;" ::: "memory"); }
__device__ __forceinline__ void fence_proxy_async() { asm volatile("fence.proxy.async.shared::cta;" ::: "memory"); }
__device__ __forceinline__ void cluster_sync() {
    asm volatile("barrier.cluster.arrive.release.aligned;\nbarrier.cluster.wait.acquire.aligned;" ::: "memory");
}
__device__ __forceinline__ bool elect_one() {
    uint32_t pred;
    asm volatile("{\n.reg .pred p;\nelect.sync _|p, 0xFFFFFFFF;\nselp.b32 %0, 1, 0, p;\n}" : "=r"(pred));
    return pred != 0;
}
__device__ __forceinline__ void pdl_launch() { asm volatile("griddepcontrol.launch_dependents;" ::: "memory"); }
__device__ __forceinline__ void pdl_wait() { asm volatile("griddepcontrol.wait;" ::: "memory"); }
__device__ __forceinline__ void prefetch_map(const CUtensorMap* m) {
    asm volatile("prefetch.tensormap [%0];" ::"l"(m) : "memory");
}
__device__ __forceinline__ void tma_load(uint32_t dst, const CUtensorMap* m, int c0, int c1, uint32_t bar) {
    asm volatile("cp.async.bulk.tensor.2d.shared::cluster.global.mbarrier::complete_tx::bytes [%0], [%1, {%3, %4}], [%2];"
                 ::"r"(dst), "l"(m), "r"(bar), "r"(c0), "r"(c1) : "memory");
}
__device__ __forceinline__ void tma_load_mc(uint32_t dst, const CUtensorMap* m, int c0, int c1, uint32_t bar, uint16_t mask) {
    asm volatile("cp.async.bulk.tensor.2d.shared::cluster.global.mbarrier::complete_tx::bytes.multicast::cluster"
                 " [%0], [%1, {%3, %4}], [%2], %5;"
                 ::"r"(dst), "l"(m), "r"(bar), "r"(c0), "r"(c1), "h"(mask) : "memory");
}
__device__ __forceinline__ void tma_store(const CUtensorMap* m, uint32_t src, int c0, int c1) {
    asm volatile("cp.async.bulk.tensor.2d.global.shared::cta.bulk_group [%0, {%2, %3}], [%1];"
                 ::"l"(m), "r"(src), "r"(c0), "r"(c1) : "memory");
}
__device__ __forceinline__ void bulk_commit() { asm volatile("cp.async.bulk.commit_group;" ::: "memory"); }
__device__ __forceinline__ void bulk_wait_all() { asm volatile("cp.async.bulk.wait_group 0;" ::: "memory"); }
__device__ __forceinline__ void bulk_load(uint32_t dst, const void* src, uint32_t bytes, uint32_t bar) {
    asm volatile("cp.async.bulk.shared::cluster.global.mbarrier::complete_tx::bytes [%0], [%1], %2, [%3];"
                 ::"r"(dst), "l"(src), "r"(bytes), "r"(bar) : "memory");
}
__device__ __forceinline__ void prefetch_l2(const void* p, uint32_t bytes) {
    asm volatile("cp.async.bulk.prefetch.L2.global [%0], %1;" ::"l"(p), "r"(bytes) : "memory");
}
__device__ __forceinline__ void tma_prefetch_l2(const CUtensorMap* m, int c0, int c1) {
    asm volatile("cp.async.bulk.prefetch.tensor.2d.L2.global.tile [%0, {%1, %2}];" ::"l"(m), "r"(c0), "r"(c1) : "memory");
}
__device__ __forceinline__ void wg_fence() { asm volatile("wgmma.fence.sync.aligned;" ::: "memory"); }
__device__ __forceinline__ void wg_commit() { asm volatile("wgmma.commit_group.sync.aligned;" ::: "memory"); }
template <int N> __device__ __forceinline__ void wg_wait() {
    asm volatile("wgmma.wait_group.sync.aligned %0;" ::"n"(N) : "memory");
}
template <int N> __device__ __forceinline__ void reg_alloc() { asm volatile("setmaxnreg.inc.sync.aligned.u32 %0;" ::"n"(N)); }
template <int N> __device__ __forceinline__ void reg_dealloc() { asm volatile("setmaxnreg.dec.sync.aligned.u32 %0;" ::"n"(N)); }
template <int N> __device__ __forceinline__ void fence_regs(float (&d)[N]) {
#pragma unroll
    for (int i = 0; i < N; i++) asm volatile("" : "+f"(d[i])::"memory");
}
__device__ __forceinline__ uint64_t make_desc(uint32_t addr, uint32_t lbo, uint32_t sbo, uint32_t swz) {
    return (uint64_t)((addr & 0x3FFFF) >> 4) | ((uint64_t)(lbo >> 4) << 16) | ((uint64_t)(sbo >> 4) << 32) |
           ((uint64_t)swz << 62);
}
__device__ __forceinline__ uint32_t pack_bf16(float lo, float hi) {
    uint32_t r;
    asm("cvt.rn.bf16x2.f32 %0, %1, %2;" : "=r"(r) : "f"(hi), "f"(lo));
    return r;
}
__device__ __forceinline__ float ex2(float x) {
    float r;
    asm("ex2.approx.ftz.f32 %0, %1;" : "=f"(r) : "f"(x));
    return r;
}
__device__ __forceinline__ float bf_lo(uint32_t v) { return __uint_as_float(v << 16); }
__device__ __forceinline__ float bf_hi(uint32_t v) { return __uint_as_float(v & 0xFFFF0000u); }
__device__ __forceinline__ void stmatrix_x4(uint32_t addr, uint32_t r0, uint32_t r1, uint32_t r2, uint32_t r3) {
    asm volatile("stmatrix.sync.aligned.m8n8.x4.shared.b16 [%0], {%1, %2, %3, %4};"
                 ::"r"(addr), "r"(r0), "r"(r1), "r"(r2), "r"(r3));
}

__device__ __forceinline__ void wgmma_n200_ss_tb(float (&d)[100], uint64_t descA, uint64_t descB, int scaleD) {
    asm volatile("{\n.reg .pred p;\nsetp.ne.b32 p, %102, 0;\n"
        "wgmma.mma_async.sync.aligned.m64n200k16.f32.bf16.bf16 {"
        "%0, %1, %2, %3, %4, %5, %6, %7, %8, %9, %10, %11, %12, %13, %14, %15, "
        "%16, %17, %18, %19, %20, %21, %22, %23, %24, %25, %26, %27, %28, %29, %30, %31, "
        "%32, %33, %34, %35, %36, %37, %38, %39, %40, %41, %42, %43, %44, %45, %46, %47, "
        "%48, %49, %50, %51, %52, %53, %54, %55, %56, %57, %58, %59, %60, %61, %62, %63, "
        "%64, %65, %66, %67, %68, %69, %70, %71, %72, %73, %74, %75, %76, %77, %78, %79, "
        "%80, %81, %82, %83, %84, %85, %86, %87, %88, %89, %90, %91, %92, %93, %94, %95, "
        "%96, %97, %98, %99}, "
        "%100, %101, p, 1, 1, 0, 1;\n}\n"
        : "+f"(d[0]), "+f"(d[1]), "+f"(d[2]), "+f"(d[3]), "+f"(d[4]), "+f"(d[5]), "+f"(d[6]), "+f"(d[7]),
          "+f"(d[8]), "+f"(d[9]), "+f"(d[10]), "+f"(d[11]), "+f"(d[12]), "+f"(d[13]), "+f"(d[14]), "+f"(d[15]),
          "+f"(d[16]), "+f"(d[17]), "+f"(d[18]), "+f"(d[19]), "+f"(d[20]), "+f"(d[21]), "+f"(d[22]), "+f"(d[23]),
          "+f"(d[24]), "+f"(d[25]), "+f"(d[26]), "+f"(d[27]), "+f"(d[28]), "+f"(d[29]), "+f"(d[30]), "+f"(d[31]),
          "+f"(d[32]), "+f"(d[33]), "+f"(d[34]), "+f"(d[35]), "+f"(d[36]), "+f"(d[37]), "+f"(d[38]), "+f"(d[39]),
          "+f"(d[40]), "+f"(d[41]), "+f"(d[42]), "+f"(d[43]), "+f"(d[44]), "+f"(d[45]), "+f"(d[46]), "+f"(d[47]),
          "+f"(d[48]), "+f"(d[49]), "+f"(d[50]), "+f"(d[51]), "+f"(d[52]), "+f"(d[53]), "+f"(d[54]), "+f"(d[55]),
          "+f"(d[56]), "+f"(d[57]), "+f"(d[58]), "+f"(d[59]), "+f"(d[60]), "+f"(d[61]), "+f"(d[62]), "+f"(d[63]),
          "+f"(d[64]), "+f"(d[65]), "+f"(d[66]), "+f"(d[67]), "+f"(d[68]), "+f"(d[69]), "+f"(d[70]), "+f"(d[71]),
          "+f"(d[72]), "+f"(d[73]), "+f"(d[74]), "+f"(d[75]), "+f"(d[76]), "+f"(d[77]), "+f"(d[78]), "+f"(d[79]),
          "+f"(d[80]), "+f"(d[81]), "+f"(d[82]), "+f"(d[83]), "+f"(d[84]), "+f"(d[85]), "+f"(d[86]), "+f"(d[87]),
          "+f"(d[88]), "+f"(d[89]), "+f"(d[90]), "+f"(d[91]), "+f"(d[92]), "+f"(d[93]), "+f"(d[94]), "+f"(d[95]),
          "+f"(d[96]), "+f"(d[97]), "+f"(d[98]), "+f"(d[99])
        : "l"(descA), "l"(descB), "r"(scaleD));
}

__device__ __forceinline__ void wgmma_n40_ss_tb(float (&d)[20], uint64_t descA, uint64_t descB, int scaleD) {
    asm volatile("{\n.reg .pred p;\nsetp.ne.b32 p, %22, 0;\n"
        "wgmma.mma_async.sync.aligned.m64n40k16.f32.bf16.bf16 {"
        "%0, %1, %2, %3, %4, %5, %6, %7, %8, %9, %10, %11, %12, %13, %14, %15, "
        "%16, %17, %18, %19}, "
        "%20, %21, p, 1, 1, 0, 1;\n}\n"
        : "+f"(d[0]), "+f"(d[1]), "+f"(d[2]), "+f"(d[3]), "+f"(d[4]), "+f"(d[5]), "+f"(d[6]), "+f"(d[7]),
          "+f"(d[8]), "+f"(d[9]), "+f"(d[10]), "+f"(d[11]), "+f"(d[12]), "+f"(d[13]), "+f"(d[14]), "+f"(d[15]),
          "+f"(d[16]), "+f"(d[17]), "+f"(d[18]), "+f"(d[19])
        : "l"(descA), "l"(descB), "r"(scaleD));
}

__device__ __forceinline__ void wgmma_n192_ss_tb(float (&d)[96], uint64_t descA, uint64_t descB, int scaleD) {
    asm volatile("{\n.reg .pred p;\nsetp.ne.b32 p, %98, 0;\n"
        "wgmma.mma_async.sync.aligned.m64n192k16.f32.bf16.bf16 {"
        "%0, %1, %2, %3, %4, %5, %6, %7, %8, %9, %10, %11, %12, %13, %14, %15, "
        "%16, %17, %18, %19, %20, %21, %22, %23, %24, %25, %26, %27, %28, %29, %30, %31, "
        "%32, %33, %34, %35, %36, %37, %38, %39, %40, %41, %42, %43, %44, %45, %46, %47, "
        "%48, %49, %50, %51, %52, %53, %54, %55, %56, %57, %58, %59, %60, %61, %62, %63, "
        "%64, %65, %66, %67, %68, %69, %70, %71, %72, %73, %74, %75, %76, %77, %78, %79, "
        "%80, %81, %82, %83, %84, %85, %86, %87, %88, %89, %90, %91, %92, %93, %94, %95}, "
        "%96, %97, p, 1, 1, 0, 1;\n}\n"
        : "+f"(d[0]), "+f"(d[1]), "+f"(d[2]), "+f"(d[3]), "+f"(d[4]), "+f"(d[5]), "+f"(d[6]), "+f"(d[7]),
          "+f"(d[8]), "+f"(d[9]), "+f"(d[10]), "+f"(d[11]), "+f"(d[12]), "+f"(d[13]), "+f"(d[14]), "+f"(d[15]),
          "+f"(d[16]), "+f"(d[17]), "+f"(d[18]), "+f"(d[19]), "+f"(d[20]), "+f"(d[21]), "+f"(d[22]), "+f"(d[23]),
          "+f"(d[24]), "+f"(d[25]), "+f"(d[26]), "+f"(d[27]), "+f"(d[28]), "+f"(d[29]), "+f"(d[30]), "+f"(d[31]),
          "+f"(d[32]), "+f"(d[33]), "+f"(d[34]), "+f"(d[35]), "+f"(d[36]), "+f"(d[37]), "+f"(d[38]), "+f"(d[39]),
          "+f"(d[40]), "+f"(d[41]), "+f"(d[42]), "+f"(d[43]), "+f"(d[44]), "+f"(d[45]), "+f"(d[46]), "+f"(d[47]),
          "+f"(d[48]), "+f"(d[49]), "+f"(d[50]), "+f"(d[51]), "+f"(d[52]), "+f"(d[53]), "+f"(d[54]), "+f"(d[55]),
          "+f"(d[56]), "+f"(d[57]), "+f"(d[58]), "+f"(d[59]), "+f"(d[60]), "+f"(d[61]), "+f"(d[62]), "+f"(d[63]),
          "+f"(d[64]), "+f"(d[65]), "+f"(d[66]), "+f"(d[67]), "+f"(d[68]), "+f"(d[69]), "+f"(d[70]), "+f"(d[71]),
          "+f"(d[72]), "+f"(d[73]), "+f"(d[74]), "+f"(d[75]), "+f"(d[76]), "+f"(d[77]), "+f"(d[78]), "+f"(d[79]),
          "+f"(d[80]), "+f"(d[81]), "+f"(d[82]), "+f"(d[83]), "+f"(d[84]), "+f"(d[85]), "+f"(d[86]), "+f"(d[87]),
          "+f"(d[88]), "+f"(d[89]), "+f"(d[90]), "+f"(d[91]), "+f"(d[92]), "+f"(d[93]), "+f"(d[94]), "+f"(d[95])
        : "l"(descA), "l"(descB), "r"(scaleD));
}

__device__ __forceinline__ void wgmma_n192_ss_tb_z(float (&d)[96], uint64_t descA, uint64_t descB) {
    asm volatile("{\n.reg .pred p;\nsetp.ne.b32 p, 0, 0;\n"
        "wgmma.mma_async.sync.aligned.m64n192k16.f32.bf16.bf16 {"
        "%0, %1, %2, %3, %4, %5, %6, %7, %8, %9, %10, %11, %12, %13, %14, %15, "
        "%16, %17, %18, %19, %20, %21, %22, %23, %24, %25, %26, %27, %28, %29, %30, %31, "
        "%32, %33, %34, %35, %36, %37, %38, %39, %40, %41, %42, %43, %44, %45, %46, %47, "
        "%48, %49, %50, %51, %52, %53, %54, %55, %56, %57, %58, %59, %60, %61, %62, %63, "
        "%64, %65, %66, %67, %68, %69, %70, %71, %72, %73, %74, %75, %76, %77, %78, %79, "
        "%80, %81, %82, %83, %84, %85, %86, %87, %88, %89, %90, %91, %92, %93, %94, %95}, "
        "%96, %97, p, 1, 1, 0, 1;\n}\n"
        : "=f"(d[0]), "=f"(d[1]), "=f"(d[2]), "=f"(d[3]), "=f"(d[4]), "=f"(d[5]), "=f"(d[6]), "=f"(d[7]),
          "=f"(d[8]), "=f"(d[9]), "=f"(d[10]), "=f"(d[11]), "=f"(d[12]), "=f"(d[13]), "=f"(d[14]), "=f"(d[15]),
          "=f"(d[16]), "=f"(d[17]), "=f"(d[18]), "=f"(d[19]), "=f"(d[20]), "=f"(d[21]), "=f"(d[22]), "=f"(d[23]),
          "=f"(d[24]), "=f"(d[25]), "=f"(d[26]), "=f"(d[27]), "=f"(d[28]), "=f"(d[29]), "=f"(d[30]), "=f"(d[31]),
          "=f"(d[32]), "=f"(d[33]), "=f"(d[34]), "=f"(d[35]), "=f"(d[36]), "=f"(d[37]), "=f"(d[38]), "=f"(d[39]),
          "=f"(d[40]), "=f"(d[41]), "=f"(d[42]), "=f"(d[43]), "=f"(d[44]), "=f"(d[45]), "=f"(d[46]), "=f"(d[47]),
          "=f"(d[48]), "=f"(d[49]), "=f"(d[50]), "=f"(d[51]), "=f"(d[52]), "=f"(d[53]), "=f"(d[54]), "=f"(d[55]),
          "=f"(d[56]), "=f"(d[57]), "=f"(d[58]), "=f"(d[59]), "=f"(d[60]), "=f"(d[61]), "=f"(d[62]), "=f"(d[63]),
          "=f"(d[64]), "=f"(d[65]), "=f"(d[66]), "=f"(d[67]), "=f"(d[68]), "=f"(d[69]), "=f"(d[70]), "=f"(d[71]),
          "=f"(d[72]), "=f"(d[73]), "=f"(d[74]), "=f"(d[75]), "=f"(d[76]), "=f"(d[77]), "=f"(d[78]), "=f"(d[79]),
          "=f"(d[80]), "=f"(d[81]), "=f"(d[82]), "=f"(d[83]), "=f"(d[84]), "=f"(d[85]), "=f"(d[86]), "=f"(d[87]),
          "=f"(d[88]), "=f"(d[89]), "=f"(d[90]), "=f"(d[91]), "=f"(d[92]), "=f"(d[93]), "=f"(d[94]), "=f"(d[95])
        : "l"(descA), "l"(descB));
}

__device__ __forceinline__ void wgmma_n160_ss_tb(float (&d)[80], uint64_t descA, uint64_t descB, int scaleD) {
    asm volatile("{\n.reg .pred p;\nsetp.ne.b32 p, %82, 0;\n"
        "wgmma.mma_async.sync.aligned.m64n160k16.f32.bf16.bf16 {"
        "%0, %1, %2, %3, %4, %5, %6, %7, %8, %9, %10, %11, %12, %13, %14, %15, "
        "%16, %17, %18, %19, %20, %21, %22, %23, %24, %25, %26, %27, %28, %29, %30, %31, "
        "%32, %33, %34, %35, %36, %37, %38, %39, %40, %41, %42, %43, %44, %45, %46, %47, "
        "%48, %49, %50, %51, %52, %53, %54, %55, %56, %57, %58, %59, %60, %61, %62, %63, "
        "%64, %65, %66, %67, %68, %69, %70, %71, %72, %73, %74, %75, %76, %77, %78, %79}, "
        "%80, %81, p, 1, 1, 0, 1;\n}\n"
        : "+f"(d[0]), "+f"(d[1]), "+f"(d[2]), "+f"(d[3]), "+f"(d[4]), "+f"(d[5]), "+f"(d[6]), "+f"(d[7]),
          "+f"(d[8]), "+f"(d[9]), "+f"(d[10]), "+f"(d[11]), "+f"(d[12]), "+f"(d[13]), "+f"(d[14]), "+f"(d[15]),
          "+f"(d[16]), "+f"(d[17]), "+f"(d[18]), "+f"(d[19]), "+f"(d[20]), "+f"(d[21]), "+f"(d[22]), "+f"(d[23]),
          "+f"(d[24]), "+f"(d[25]), "+f"(d[26]), "+f"(d[27]), "+f"(d[28]), "+f"(d[29]), "+f"(d[30]), "+f"(d[31]),
          "+f"(d[32]), "+f"(d[33]), "+f"(d[34]), "+f"(d[35]), "+f"(d[36]), "+f"(d[37]), "+f"(d[38]), "+f"(d[39]),
          "+f"(d[40]), "+f"(d[41]), "+f"(d[42]), "+f"(d[43]), "+f"(d[44]), "+f"(d[45]), "+f"(d[46]), "+f"(d[47]),
          "+f"(d[48]), "+f"(d[49]), "+f"(d[50]), "+f"(d[51]), "+f"(d[52]), "+f"(d[53]), "+f"(d[54]), "+f"(d[55]),
          "+f"(d[56]), "+f"(d[57]), "+f"(d[58]), "+f"(d[59]), "+f"(d[60]), "+f"(d[61]), "+f"(d[62]), "+f"(d[63]),
          "+f"(d[64]), "+f"(d[65]), "+f"(d[66]), "+f"(d[67]), "+f"(d[68]), "+f"(d[69]), "+f"(d[70]), "+f"(d[71]),
          "+f"(d[72]), "+f"(d[73]), "+f"(d[74]), "+f"(d[75]), "+f"(d[76]), "+f"(d[77]), "+f"(d[78]), "+f"(d[79])
        : "l"(descA), "l"(descB), "r"(scaleD));
}

__device__ __forceinline__ void wgmma_n64_ss(float (&d)[32], uint64_t descA, uint64_t descB, int scaleD) {
    asm volatile("{\n.reg .pred p;\nsetp.ne.b32 p, %34, 0;\n"
        "wgmma.mma_async.sync.aligned.m64n64k16.f32.bf16.bf16 {"
        "%0, %1, %2, %3, %4, %5, %6, %7, %8, %9, %10, %11, %12, %13, %14, %15, "
        "%16, %17, %18, %19, %20, %21, %22, %23, %24, %25, %26, %27, %28, %29, %30, %31}, "
        "%32, %33, p, 1, 1, 0, 0;\n}\n"
        : "+f"(d[0]), "+f"(d[1]), "+f"(d[2]), "+f"(d[3]), "+f"(d[4]), "+f"(d[5]), "+f"(d[6]), "+f"(d[7]),
          "+f"(d[8]), "+f"(d[9]), "+f"(d[10]), "+f"(d[11]), "+f"(d[12]), "+f"(d[13]), "+f"(d[14]), "+f"(d[15]),
          "+f"(d[16]), "+f"(d[17]), "+f"(d[18]), "+f"(d[19]), "+f"(d[20]), "+f"(d[21]), "+f"(d[22]), "+f"(d[23]),
          "+f"(d[24]), "+f"(d[25]), "+f"(d[26]), "+f"(d[27]), "+f"(d[28]), "+f"(d[29]), "+f"(d[30]), "+f"(d[31])
        : "l"(descA), "l"(descB), "r"(scaleD));
}

__device__ __forceinline__ void wgmma_n64_ss_z(float (&d)[32], uint64_t descA, uint64_t descB) {
    asm volatile("{\n.reg .pred p;\nsetp.ne.b32 p, 0, 0;\n"
        "wgmma.mma_async.sync.aligned.m64n64k16.f32.bf16.bf16 {"
        "%0, %1, %2, %3, %4, %5, %6, %7, %8, %9, %10, %11, %12, %13, %14, %15, "
        "%16, %17, %18, %19, %20, %21, %22, %23, %24, %25, %26, %27, %28, %29, %30, %31}, "
        "%32, %33, p, 1, 1, 0, 0;\n}\n"
        : "=f"(d[0]), "=f"(d[1]), "=f"(d[2]), "=f"(d[3]), "=f"(d[4]), "=f"(d[5]), "=f"(d[6]), "=f"(d[7]),
          "=f"(d[8]), "=f"(d[9]), "=f"(d[10]), "=f"(d[11]), "=f"(d[12]), "=f"(d[13]), "=f"(d[14]), "=f"(d[15]),
          "=f"(d[16]), "=f"(d[17]), "=f"(d[18]), "=f"(d[19]), "=f"(d[20]), "=f"(d[21]), "=f"(d[22]), "=f"(d[23]),
          "=f"(d[24]), "=f"(d[25]), "=f"(d[26]), "=f"(d[27]), "=f"(d[28]), "=f"(d[29]), "=f"(d[30]), "=f"(d[31])
        : "l"(descA), "l"(descB));
}

__device__ __forceinline__ void wgmma_n24_rs_tb(float (&d)[12], uint32_t a0, uint32_t a1, uint32_t a2, uint32_t a3, uint64_t descB, int scaleD) {
    asm volatile("{\n.reg .pred p;\nsetp.ne.b32 p, %17, 0;\n"
        "wgmma.mma_async.sync.aligned.m64n24k16.f32.bf16.bf16 {"
        "%0, %1, %2, %3, %4, %5, %6, %7, %8, %9, %10, %11}, "
        "{%12, %13, %14, %15}, %16, p, 1, 1, 1;\n}\n"
        : "+f"(d[0]), "+f"(d[1]), "+f"(d[2]), "+f"(d[3]), "+f"(d[4]), "+f"(d[5]), "+f"(d[6]), "+f"(d[7]),
          "+f"(d[8]), "+f"(d[9]), "+f"(d[10]), "+f"(d[11])
        : "r"(a0), "r"(a1), "r"(a2), "r"(a3), "l"(descB), "r"(scaleD));
}

__device__ __forceinline__ void cnt_signal(int idx) {
    asm volatile("fence.acq_rel.gpu;\nred.relaxed.gpu.global.add.u32 [%0], 1;"
                 ::"l"(g_cnt + idx * 32) : "memory");
}
__device__ __forceinline__ void cnt_wait(int idx, uint32_t target) {
    asm volatile("{\n.reg .pred p;\n.reg .u32 n, v;\nmov.u32 n, 0;\n"
                 "CNT_LOOP:\nld.acquire.gpu.global.u32 v, [%0];\nsub.u32 v, v, %1;\nsetp.ge.s32 p, v, 0;\n@p bra CNT_DONE;\n"
                 "add.u32 n, n, 1;\nsetp.lt.u32 p, n, 4194304;\n@p bra CNT_LOOP;\nCNT_DONE:\n"
                 "fence.proxy.async.global;\n}"
                 ::"l"(g_cnt + idx * 32), "r"(target) : "memory");
}
__device__ __forceinline__ void cluster_arrive() { asm volatile("barrier.cluster.arrive.release.aligned;" ::: "memory"); }
__device__ __forceinline__ void cluster_arrive_relaxed() { asm volatile("barrier.cluster.arrive.relaxed.aligned;" ::: "memory"); }
__device__ __forceinline__ void cluster_wait() { asm volatile("barrier.cluster.wait.acquire.aligned;" ::: "memory"); }
__device__ __forceinline__ void bulk_wait_read() { asm volatile("cp.async.bulk.wait_group.read 0;" ::: "memory"); }

__device__ __forceinline__ uint32_t gelu_half2(float h0, float h1) {
    const uint32_t hx = pack_bf16(h0, h1);
    uint32_t y, p, u, t, r;
    asm("mul.rn.bf16x2 %0, %1, %1;" : "=r"(y) : "r"(hx));
    asm("fma.rn.bf16x2 %0, %1, %2, %3;" : "=r"(p) : "r"(y), "r"(0x3E923E92u), "r"(0x3FCC3FCCu));
    asm("mul.rn.bf16x2 %0, %1, %2;" : "=r"(u) : "r"(hx), "r"(p));
    asm("tanh.approx.bf16x2 %0, %1;" : "=r"(t) : "r"(u));
    asm("fma.rn.bf16x2 %0, %1, %2, %1;" : "=r"(r) : "r"(hx), "r"(t));
    return r;
}
__device__ __forceinline__ void release_stage(uint32_t bar, uint32_t peer, int lane) {
    if (lane == 0) { mbar_arrive(bar); mbar_arrive_cluster(bar, peer); }
}

constexpr int SM_RING = 163840;
constexpr int SM_Q = 0, SM_ZERO = 24576, SM_K = SM_ZERO + 3072, SM_V = SM_K + IMG_BYTES;
constexpr int G2_STAGE = 8192 + 20480;
__device__ __forceinline__ uint32_t g2_slot(int i) { return SM_K + ((0x4326150 >> (4 * i)) & 7) * G2_STAGE; }
constexpr int SM_MISC = 229376;
constexpr int SM_BIAS = SM_MISC, SM_RED = SM_BIAS + 384, SM_BAR = SM_RED + 128;
constexpr int B_A = 0, B_F1 = 10, B_E1 = 14, B_F2 = 18, B_E2 = 23, B_KV = 28, B_Q = 45, B_F3 = 47, B_E3 = 55, B_ST = 63, B_STAT = 65, B_AUX = 66, B_AUX2 = 67, B_DEAD = 68, B_PF = 70, B_COUNT = 73;
constexpr int SM_EPOCH = SM_BAR + 584, SM_SAFE = SM_EPOCH + 4;
constexpr int SM_CS = SM_EPOCH + 8;
constexpr int SM_TOTAL = SM_CS + 1728;
static_assert(SM_TOTAL <= 232448, "shared memory budget");

template <int V> struct IntC { static constexpr int value = V; };
struct Maps { CUtensorMap x, wqkv, w1, h, o, wo, w2; };

__device__ __forceinline__ uint32_t bf2_fma(uint32_t a, uint32_t b, uint32_t c) {
    uint32_t r;
    asm("fma.rn.bf16x2 %0, %1, %2, %3;" : "=r"(r) : "r"(a), "r"(b), "r"(c));
    return r;
}
__device__ __forceinline__ uint32_t lop_and_or(uint32_t a, uint32_t m, uint32_t o) {
    uint32_t r;
    asm("lop3.b32 %0, %1, %2, %3, 0xEA;" : "=r"(r) : "r"(a), "r"(m), "r"(o));
    return r;
}
struct ExpConst { uint32_t mask, slope; };
__device__ __forceinline__ ExpConst make_exp_const() {
    ExpConst k;
    asm volatile("mov.b32 %0, 0x007F007F;" : "=r"(k.mask));
    asm volatile("mov.b32 %0, 0x3EF83EF8;" : "=r"(k.slope));
    return k;
}
__device__ __forceinline__ uint32_t exp2_pair_fma(float t0, float t1, const ExpConst& k) {
    const uint32_t L = __byte_perm(__float_as_uint(t0), __float_as_uint(t1), 0x6521);
    const uint32_t g = lop_and_or(L, k.mask, 0x3F803F80u);
    const uint32_t u = bf2_fma(g, k.slope, 0xBF37BF37u);
    const uint32_t e = bf2_fma(u, u, 0xBD71BD71u);
    return bf2_fma(L, e, L);
}
template <int SHIFT>
__device__ __forceinline__ void exp_tile(const float (&s)[32], uint32_t (&p)[16], const ExpConst& k) {
#pragma unroll
    for (int b = 0; b < 8; b++) {
        if ((EMU_MASK >> (b + SHIFT)) & 1) {
            p[2 * b] = exp2_pair_fma(s[4 * b], s[4 * b + 1], k);
            p[2 * b + 1] = exp2_pair_fma(s[4 * b + 2], s[4 * b + 3], k);
        } else {
            p[2 * b] = pack_bf16(ex2(s[4 * b]), ex2(s[4 * b + 1]));
            p[2 * b + 1] = pack_bf16(ex2(s[4 * b + 2]), ex2(s[4 * b + 3]));
        }
    }
}

__device__ __forceinline__ void qk_tile(float (&s)[32], uint64_t dQ, uint64_t dQ2, uint64_t dK) {
    wg_fence();
    wgmma_n64_ss_z(s, dQ, dK);
    wgmma_n64_ss(s, dQ2, dK + 16, 1);
    wg_commit();
}
__device__ __forceinline__ void pv_tile(float (&o)[12], const uint32_t (&p)[16], uint64_t dV) {
    wg_fence();
#pragma unroll
    for (int ks = 0; ks < 4; ks++)
        wgmma_n24_rs_tb(o, p[4 * ks], p[4 * ks + 1], p[4 * ks + 2], p[4 * ks + 3], dV + ks * 48, 1);
    wg_commit();
}
__device__ __forceinline__ void store_o(const float (&o)[12], int h, int rbase, int lane) {
    const int g = lane >> 2, c = lane & 3;
    const bool odd = h & 1;
    const int lsrc = (lane & ~3) | (odd ? 0 : 2);
    float i0, i1;
    asm("rcp.approx.ftz.f32 %0, %1;" : "=f"(i0) : "f"(__shfl_sync(~0u, o[8], lsrc)));
    asm("rcp.approx.ftz.f32 %0, %1;" : "=f"(i1) : "f"(__shfl_sync(~0u, o[10], lsrc)));
    __nv_bfloat16* dst = g_o + (size_t)(rbase + g) * DM + h * 20;
    const int d0 = (odd ? 4 : 0) + 2 * c, d1 = d0 + 8, d2 = odd ? 2 * c - 4 : 16 + 2 * c;
    *(uint32_t*)(dst + d0) = pack_bf16(o[0] * i0, o[1] * i0);
    *(uint32_t*)(dst + d1) = pack_bf16(o[4] * i0, o[5] * i0);
    *(uint32_t*)(dst + 8 * DM + d0) = pack_bf16(o[2] * i1, o[3] * i1);
    *(uint32_t*)(dst + 8 * DM + d1) = pack_bf16(o[6] * i1, o[7] * i1);
    if (odd ? (c >= 2) : (c < 2)) {
        *(uint32_t*)(dst + d2) = pack_bf16(o[8] * i0, o[9] * i0);
        *(uint32_t*)(dst + 8 * DM + d2) = pack_bf16(o[10] * i1, o[11] * i1);
    }
}

__device__ __forceinline__ void attn_rows_maxshift(uint32_t sK, uint32_t barKV, uint64_t dQ, uint64_t dQ2, int h, int rbase) {
    const int lane = threadIdx.x & 31;
    const uint64_t dK0 = make_desc(sK, 128, 384, 0), dV0 = make_desc(sK + IMG_BYTES, 384, 128, 0);
    float o[12], s[32];
    uint32_t p[16];
#pragma unroll
    for (int i = 0; i < 12; i++) o[i] = 0.f;
    float m0 = -3.0e38f, m1 = -3.0e38f;
    mbar_wait(barKV + 128, 0);
#pragma unroll 1
    for (int t = 0; t < 32; t++) {
        mbar_wait(barKV + (t >> 1) * 8, 0);
        qk_tile(s, dQ, dQ2, dK0 + t * 192);
        wg_wait<0>();
        fence_regs(s);
        const uint32_t mask = EMU_MASK >> ((t & 1) * 8);
        float n0 = m0, n1 = m1;
#pragma unroll
        for (int b = 0; b < 8; b++) {
            const bool emu = (mask >> b) & 1;
            const float f = emu ? 0.5f : 1.f, off = emu ? -383.00390625f : 0.f;
#pragma unroll
            for (int i = 0; i < 4; i++) s[4 * b + i] = fmaf(s[4 * b + i], f, off);
            n0 = fmaxf(n0, fmaxf(s[4 * b], s[4 * b + 1]));
            n1 = fmaxf(n1, fmaxf(s[4 * b + 2], s[4 * b + 3]));
        }
        n0 = fmaxf(n0, __shfl_xor_sync(~0u, n0, 1)); n0 = fmaxf(n0, __shfl_xor_sync(~0u, n0, 2));
        n1 = fmaxf(n1, __shfl_xor_sync(~0u, n1, 1)); n1 = fmaxf(n1, __shfl_xor_sync(~0u, n1, 2));
        const float c0 = ex2(m0 - n0), c1 = ex2(m1 - n1);
        m0 = n0; m1 = n1;
#pragma unroll
        for (int b = 0; b < 3; b++) { o[4 * b] *= c0; o[4 * b + 1] *= c0; o[4 * b + 2] *= c1; o[4 * b + 3] *= c1; }
#pragma unroll
        for (int b = 0; b < 8; b++) {
            p[2 * b] = pack_bf16(ex2(s[4 * b] - m0), ex2(s[4 * b + 1] - m0));
            p[2 * b + 1] = pack_bf16(ex2(s[4 * b + 2] - m1), ex2(s[4 * b + 3] - m1));
        }
        pv_tile(o, p, dV0 + (((t >> 1) + 7) & 15) * 384 + (t & 1) * 192);
        wg_wait<0>();
        fence_regs(o);
    }
    store_o(o, h, rbase, lane);
}

__global__ void __launch_bounds__(512, 1) __cluster_dims__(2, 1, 1)
k_fused(const __grid_constant__ Maps tm, const __nv_bfloat16* __restrict__ x, const uint8_t* __restrict__ wqkv,
        const uint8_t* __restrict__ w1, const uint8_t* __restrict__ w2, const uint8_t* __restrict__ wo,
        const __nv_bfloat16* __restrict__ b1, const __nv_bfloat16* __restrict__ b2, __nv_bfloat16* __restrict__ out) {
    extern __shared__ __align__(1024) uint8_t smem[];
    const uint32_t sb = smem_u32(smem);
    const uint32_t bar = sb + SM_BAR;
    const int warp = __shfl_sync(~0u, threadIdx.x >> 5, 0), lane = threadIdx.x & 31;
    const int wgi = warp >> 2, w4 = warp & 3, g = lane >> 2, c = lane & 3;
    const uint32_t rank = blockIdx.x & 1, peer = rank ^ 1;
    const int cl = blockIdx.x >> 1;
    const int cg = cl >> 3, rb = (cl & 7) * 2 + rank;

    if (threadIdx.x == 0) TL(0, 0);
    if (warp == 15 && lane < 4) prefetch_map(lane == 0 ? &tm.x : lane == 1 ? &tm.wqkv : lane == 2 ? &tm.w1 : &tm.h);
    if (elect_one()) {
#pragma unroll
        for (int j = 0; j < 5; j++) {
            const int i = warp * 5 + j;
            const int cnt = i >= B_PF ? 32 : (i >= B_E1 && i < B_F2) || (i >= B_E2 && i < B_KV) ? 16
                          : (i >= B_E3 && i <= B_ST + 1) || i == B_STAT || i == B_DEAD || i == B_DEAD + 1 ? 8 : i == B_AUX ? 4 : i == B_AUX2 ? 3 : 1;
            if (i < B_COUNT) mbar_init(bar + i * 8, cnt);
        }
        fence_barrier_init();
    }
    __syncthreads();
    if (threadIdx.x == 0) TL(0, 1);
    cluster_arrive_relaxed();
    if (warp == 0 && elect_one()) {
        for (int kb = 0; kb < 2; kb++) {
            mbar_expect_tx(bar + (B_A + kb) * 8, 16384);
            tma_load(sb + kb * 16384, &tm.x, kb * 64, rb * 128, bar + (B_A + kb) * 8);
        }
    }
    cluster_wait();
    if (warp == 0 && elect_one()) {
        const uint32_t dst = sb + SM_RING + rank * 8192, fb = bar + B_F1 * 8;
        mbar_expect_tx(fb, 16384);
        tma_load_mc(dst, &tm.wqkv, cg * 240 + rank * 128, 0, fb, 3);
        tma_load_mc(dst + 4096, &tm.wqkv, cg * 240 + rank * 128 + 64, 0, fb, 3);
    }
    __syncwarp();
    if (threadIdx.x == 0) TL(0, 3);

    {
        const uint32_t sB = sb + SM_RING;
        if (threadIdx.x == 0) TL(1, 0);
        if (wgi < 2) {
            reg_dealloc<56>();
            if (warp == 0) {
#pragma unroll 1
                for (int it = 1; it < 20; it++) {
                    const int s = it & 3;
                    const int kb = it > 1 && (it & 1) ? (it + 1) >> 1 : 10;
                    if (it >= 4) mbar_wait(bar + (B_E1 + s) * 8, ((it >> 2) - 1) & 1);
                    if (elect_one()) {
                        if (kb < 10) {
                            mbar_expect_tx(bar + (B_A + kb) * 8, 16384);
                            tma_load(sb + kb * 16384, &tm.x, kb * 64, rb * 128, bar + (B_A + kb) * 8);
                        }
                        const uint32_t dst = sB + s * 16384 + rank * 8192, fb = bar + (B_F1 + s) * 8;
                        const int c0 = cg * 240 + rank * 128;
                        mbar_expect_tx(fb, 16384);
                        tma_load_mc(dst, &tm.wqkv, c0, it * 32, fb, 3);
                        tma_load_mc(dst + 4096, &tm.wqkv, c0 + 64, it * 32, fb, 3);
                    }
                    __syncwarp();
                }
#pragma unroll 1
                for (int it = 0; it < 20; it++) {
                    const int s = it % 5;
                    if (it < 5) { if (it != 3) mbar_wait(bar + (B_E1 + (it == 4 ? 3 : it)) * 8, 0); }
                    else mbar_wait(bar + (B_E2 + s) * 8, ((it / 5) - 1) & 1);
                    if (elect_one()) {
                        const uint32_t dst = sB + s * 12288, fb = bar + (B_F2 + s) * 8;
                        mbar_expect_tx(fb, 12288);
                        if ((it & 1) == (int)rank) {
                            tma_load_mc(dst, &tm.w1, cg * 192, it * 32, fb, 3);
                            tma_load_mc(dst + 4096, &tm.w1, cg * 192 + 64, it * 32, fb, 3);
                        } else {
                            tma_load_mc(dst + 8192, &tm.w1, cg * 192 + 128, it * 32, fb, 3);
                        }
                    }
                    __syncwarp();
                }
                mbar_wait(bar + B_AUX * 8, 0);
                mbar_wait(bar + B_DEAD * 8, 0);
                if (elect_one()) {
                    const int h = blockIdx.x >> 2;
                    cnt_wait(CNT_QKV + (32 + h) / 12, (*reinterpret_cast<volatile uint32_t*>(smem + SM_EPOCH) + 1) * 16);
                    const uint8_t* gK = g_img + (size_t)(32 + h) * IMG_BYTES;
                    for (int i = 5; i < 13; i++) {
                        mbar_expect_tx(bar + (B_KV + i) * 8, 12288);
                        bulk_load(sb + SM_K + (i + 1) * 6144, gK + (i + 1) * 6144, 6144, bar + (B_KV + i) * 8);
                    }
                }
                __syncwarp();
            } else {
                const int ht = threadIdx.x - 32;
                if (ht == 160) *reinterpret_cast<volatile uint32_t*>(smem + SM_EPOCH) = *(volatile uint32_t*)&g_epoch;
                auto slab_sum = [&](const uint32_t* src, int pitch) {
                    float s0 = 0.f, s1 = 0.f;
                    uint32_t v[40];
#pragma unroll
                    for (int k = 0; k < 40; k++) v[k] = __ldg(src + k * pitch);
#pragma unroll
                    for (int k = 0; k < 40; k++) { s0 += bf_lo(v[k]); s1 += bf_hi(v[k]); }
                    return make_float2(s0, s1);
                };
                auto gather = [&](int idx) {
                    float s0 = 0.f, s1 = 0.f;
#pragma unroll
                    for (int r = 0; r < 16; r++) {
                        const float2 v = __ldcg(g_csp + r * 1728 + cg * 216 + idx);
                        s0 += v.x; s1 += v.y;
                    }
                    reinterpret_cast<float2*>(smem + SM_CS)[idx] = make_float2(s0, s1);
                };
                if (warp == 7) {
                    mbar_wait(bar + B_STAT * 8, 0);
                    if (elect_one()) cnt_signal(CNT_ST + rb);
                    __syncwarp();
                }
                if (ht < 120)
                    g_csp[rb * 1728 + cg * 216 + ht] = slab_sum(reinterpret_cast<const uint32_t*>(wqkv) + rb * 40 * 960 + cg * 120 + ht, 960);
                if (threadIdx.x == 64) IT(3, 0);
                if (threadIdx.x == 192) IT(3, 1);
                if (warp != 7) asm volatile("bar.sync 8, 192;" ::: "memory");
                const uint32_t epoch = *reinterpret_cast<volatile uint32_t*>(smem + SM_EPOCH);
                if (warp == 6) { if (elect_one()) cnt_signal(CNT_CS + cg); __syncwarp(); }

                if (threadIdx.x == 64) IT(3, 2);
                if (warp <= 4) {
                    if (lane == 0) { cnt_wait(CNT_CS + cg, (epoch + 1) * 16); cnt_wait(CNT_ST + rb, (epoch + 1) * 8); }
                    __syncwarp();
                    if (threadIdx.x == 64) IT(3, 4);
                    if (ht < 120) gather(ht);
                    __syncwarp();
                    if (threadIdx.x == 64) IT(3, 5);
                    if (lane == 0) mbar_arrive(bar + B_AUX * 8);
                }
                if (ht >= 128) {
                    g_csp[rb * 1728 + cg * 216 + 120 + (ht - 128)] = slab_sum(reinterpret_cast<const uint32_t*>(w1) + rb * 40 * 768 + cg * 96 + (ht - 128), 768);
                    reinterpret_cast<uint32_t*>(smem + SM_BIAS)[ht - 128] =
                        bf2_fma(__ldg(reinterpret_cast<const uint32_t*>(b1 + cg * 192) + (ht - 128)), 0x3F003F00u, 0x80008000u);
                    asm volatile("bar.sync 9, 96;" ::: "memory");
                    const uint32_t epoch2 = *reinterpret_cast<volatile uint32_t*>(smem + SM_EPOCH);
                    if (warp == 5) { if (elect_one()) cnt_signal(CNT_CS2 + cg); __syncwarp(); }
                    if (warp == 6 && elect_one()) {
                        prefetch_l2(w2 + blockIdx.x * 15360, 15360);
                        prefetch_l2(wo + blockIdx.x * 6400, 6400);
                        prefetch_map(&tm.o); prefetch_map(&tm.w2); prefetch_map(&tm.wo);
                    }
                    if (lane == 0) cnt_wait(CNT_CS2 + cg, (epoch2 + 1) * 16);
                    __syncwarp();
                    gather(120 + (ht - 128));
                    __syncwarp();
                    if (lane == 0) mbar_arrive(bar + B_AUX2 * 8);
                }
                if (warp == 4) {
                    mbar_wait(bar + B_ST * 8, 0);
                    if (elect_one()) cnt_signal(CNT_QKV + cg);
                    __syncwarp();
                }
                const int h = blockIdx.x >> 2, qb = blockIdx.x & 3;
                const uint32_t ep = *reinterpret_cast<volatile uint32_t*>(smem + SM_EPOCH);
                if (lane == 0 && warp != 5) {
                    cnt_wait(CNT_QKV + h / 12, (ep + 1) * 16);
                    cnt_wait(CNT_QKV + (32 + h) / 12, (ep + 1) * 16);
                    cnt_wait(CNT_QKV + (64 + h) / 12, (ep + 1) * 16);
                }
                __syncwarp();
                if (threadIdx.x == 64) TL(5, 0);
                if (warp == 1 || warp == 4 || warp >= 6) {
                    const int w = warp == 1 ? 0 : warp == 4 ? 1 : warp - 4, t = w * 32 + lane;
                    float kmax = 0.f, qmax = 0.f;
#pragma unroll
                    for (int i = 0; i < 4; i++) {
                        const float4 v = __ldcg(reinterpret_cast<const float4*>(g_nrm + (32 + h) * SEQ) + t + i * 128);
                        kmax = fmaxf(fmaxf(kmax, fmaxf(v.x, v.y)), fmaxf(v.z, v.w));
                    }
                    {
                        const float4 v = __ldcg(reinterpret_cast<const float4*>(g_nrm + h * SEQ + qb * 512) + t);
                        qmax = fmaxf(fmaxf(v.x, v.y), fmaxf(v.z, v.w));
                    }
#pragma unroll
                    for (int o = 16; o; o >>= 1) {
                        kmax = fmaxf(kmax, __shfl_xor_sync(~0u, kmax, o));
                        qmax = fmaxf(qmax, __shfl_xor_sync(~0u, qmax, o));
                    }
                    float* red = reinterpret_cast<float*>(smem + SM_RED);
                    if (lane == 0) { red[w] = kmax; red[8 + w] = qmax; }
                    asm volatile("bar.sync 8, 128;" ::: "memory");
                    if (warp == 1 && lane == 0) {
                        for (int u = 1; u < 4; u++) { kmax = fmaxf(kmax, red[u]); qmax = fmaxf(qmax, red[8 + u]); }
                        *reinterpret_cast<volatile uint32_t*>(smem + SM_SAFE) = kmax * qmax * 1.1f <= SAFE_BOUND * SAFE_BOUND;
                    }
                }
                const uint32_t barKV = bar + B_KV * 8;
                const uint8_t* gK = g_img + (size_t)(32 + h) * IMG_BYTES;
                const uint8_t* gV = g_img + (size_t)(64 + h) * IMG_BYTES;
                if (warp == 2) {
                    if (lane == 0) TL(5, 1);
                    mbar_wait(bar + B_DEAD * 8, 0);
                    if (lane == 0) TL(5, 2);
                    for (int i = lane; i < 192; i += 32) *reinterpret_cast<uint4*>(smem + SM_ZERO + i * 16) = make_uint4(0, 0, 0, 0);
                    fence_proxy_async();
                    __syncwarp();
                    if (elect_one()) {
                        asm volatile("fence.proxy.async.global;" ::: "memory");
                        const uint8_t* gQ = g_img + (size_t)h * IMG_BYTES + qb * 64 * 384;
                        mbar_expect_tx(barKV + 128, 6144);
                        bulk_load(sb + SM_K, gK, 6144, barKV + 128);
                        for (int p = 0; p < 2; p++) {
                            mbar_expect_tx(bar + (B_Q + p) * 8, 12288);
                            bulk_load(sb + SM_Q + p * 12288, gQ + p * 12288, 12288, bar + (B_Q + p) * 8);
                        }
                        for (int i = 0; i < 5; i++) {
                            mbar_expect_tx(barKV + i * 8, 12288);
                            bulk_load(sb + SM_K + (i + 1) * 6144, gK + (i + 1) * 6144, 6144, barKV + i * 8);
                        }
                    }
                    __syncwarp();
                    if (lane == 0) TL(5, 3);
                } else if (warp == 5) {
                    mbar_wait(bar + (B_ST + 1) * 8, 0);
                    if (lane == 0) {
                        for (int b = 0; b < 6; b++)
                            tma_store(&tm.h, sb + (7 + b % 3) * 16384 + (b / 3) * 8192, cg * 192 + (b % 3) * 64, rb * 128 + (b / 3) * 64);
                        bulk_commit();
                    }
                    __syncwarp();
                } else if (warp == 3) {
                    mbar_wait(bar + (B_DEAD + 1) * 8, 0);
                    if (elect_one()) {
                        asm volatile("fence.proxy.async.global;" ::: "memory");
                        for (int i = 0; i < 9; i++) bulk_load(sb + SM_V + (i + 7) * 6144, gV + i * 6144, 6144, barKV + i * 8);
                    }
                    __syncwarp();
                }
            }
            if (lane == 0) TL(6, warp);
            asm volatile("bar.sync %0, 128;" ::"r"(wgi + 3) : "memory");
            reg_alloc<128>();
        } else {
            reg_alloc<200>();
            const int wi = wgi - 2;
            const int row0 = rb * 128 + wi * 64 + w4 * 16 + g;
            const uint32_t sAw = sb + wi * 8192;
            const int rbk = row0 >> 3, hs0 = cg * 12;
            const int srow = rb * 128 + cg * 16 + (warp - 8) * 2 + (lane >> 4);
            uint4 xv[5];
#pragma unroll
            for (int i = 0; i < 5; i++) xv[i] = __ldg(reinterpret_cast<const uint4*>(x + (size_t)srow * DM) + (lane & 15) + 16 * i);
            float accA[100], accB[20];
            const uint64_t dA0 = make_desc(sAw, 16, 1024, 1), dB0 = make_desc(sB, 4096, 1024, 1);
#pragma unroll 2
            for (int it = 0; it < 20; it++) {
                const int s = it & 3;
                if (!(it & 1)) mbar_wait(bar + (B_A + (it >> 1)) * 8, 0);
                if (threadIdx.x == 256 && it == 0) TL(0, 2);
                if (threadIdx.x == 256) IT(0, it);
                mbar_wait(bar + (B_F1 + s) * 8, (it >> 2) & 1);
                if (threadIdx.x == 256) IT(1, it);
                const uint64_t dA = dA0 + (it >> 1) * 1024 + (it & 1) * 4, dB = dB0 + s * 1024;
                wg_fence();
                wgmma_n40_ss_tb(accB, dA, dB + 769, it > 0);
                wgmma_n40_ss_tb(accB, dA + 2, dB + 769 + 128, 1);
                wgmma_n200_ss_tb(accA, dA, dB, it > 0);
                wgmma_n200_ss_tb(accA, dA + 2, dB + 128, 1);
                wg_commit();
                if (it > 0) { wg_wait<1>(); release_stage(bar + (B_E1 + ((it - 1) & 3)) * 8, peer, lane); }
                if (it == STAT_IT) {
                float sm = 0.f;
#pragma unroll
                for (int i = 0; i < 5; i++)
                    sm += ((bf_lo(xv[i].x) + bf_hi(xv[i].x)) + (bf_lo(xv[i].y) + bf_hi(xv[i].y))) +
                          ((bf_lo(xv[i].z) + bf_hi(xv[i].z)) + (bf_lo(xv[i].w) + bf_hi(xv[i].w)));
#pragma unroll
                for (int o = 8; o; o >>= 1) sm += __shfl_xor_sync(~0u, sm, o);
                const float mu = sm * (1.f / DM);
                float q0 = 0.f, q1 = 0.f;
#pragma unroll
                for (int i = 0; i < 5; i++) {
                    const uint32_t w[4] = {xv[i].x, xv[i].y, xv[i].z, xv[i].w};
#pragma unroll
                    for (int j = 0; j < 4; j++) {
                        const float d0 = bf_lo(w[j]) - mu, d1 = bf_hi(w[j]) - mu;
                        q0 = fmaf(d0, d0, q0); q1 = fmaf(d1, d1, q1);
                    }
                }
                float q = q0 + q1;
#pragma unroll
                for (int o = 8; o; o >>= 1) q += __shfl_xor_sync(~0u, q, o);
                const float var = q * (1.f / DM);
                const float r1 = rsqrtf(var + LN_EPS);
                const float r2 = rsqrtf(var * r1 * r1 + LN_EPS);
                if ((lane & 15) == 0) g_stat[srow] = make_float4(mu, r1, r1 * r2, 0.f);
                __syncwarp();
                if (lane == 0) mbar_arrive(bar + B_STAT * 8);
                }
            }
            if (threadIdx.x == 256) IT(2, 0);
            mbar_wait(bar + B_AUX * 8, 0);
            if (threadIdx.x == 256) IT(2, 1);
            const float4 st0 = __ldcg(g_stat + row0), st1 = __ldcg(g_stat + row0 + 8);
            wg_wait<0>();
            release_stage(bar + (B_E1 + 3) * 8, peer, lane);
            fence_regs(accA);
            fence_regs(accB);
            if (threadIdx.x == 256) TL(1, 1);
            const float2* cs = reinterpret_cast<const float2*>(smem + SM_CS) + c;
            uint8_t* img = g_img + (size_t)hs0 * IMG_BYTES + rbk * 384 + g * 16 + c * 4;
            const bool emu0 = (EMU_MASK >> (rbk & 15)) & 1, emu1 = (EMU_MASK >> ((rbk + 1) & 15)) & 1;
            const bool low = c < 2;
            uint32_t pk[60];
#pragma unroll
            for (int m = 0; m < 6; m++) {
                const int which = (hs0 + 2 * m) >> 5;
                const float m0 = st0.y * (which == 0 ? QSCALE : (which == 1 && emu0) ? 2.f : 1.f);
                const float m1 = st1.y * (which == 0 ? QSCALE : (which == 1 && emu1) ? 2.f : 1.f);
                const float d0 = -st0.x * m0, d1 = -st1.x * m1;
                const float* a = m < 5 ? &accA[20 * m] : accB;
#pragma unroll
                for (int b = 0; b < 5; b++) {
                    const float2 cv = cs[(5 * m + b) * 4];
                    pk[10 * m + 2 * b] = pack_bf16(fmaf(a[4 * b], m0, d0 * cv.x), fmaf(a[4 * b + 1], m0, d0 * cv.y));
                    pk[10 * m + 2 * b + 1] = pack_bf16(fmaf(a[4 * b + 2], m1, d1 * cv.x), fmaf(a[4 * b + 3], m1, d1 * cv.y));
                }
            }
            const float r20 = 0.5f * st0.z, r21 = 0.5f * st1.z, e20 = -st0.x * r20, e21 = -st1.x * r21;
            if (threadIdx.x == 256) IT(2, 2);
            float acc2[96];
#pragma unroll
            for (int it = 0; it < 20; it++) {
                const int s = it % 5;
                if (threadIdx.x == 256) IT(0, 20 + it);
                mbar_wait(bar + (B_F2 + s) * 8, (it / 5) & 1);
                if (threadIdx.x == 256) IT(1, 20 + it);
                wg_fence();
                const uint64_t dA = make_desc(sAw + (it >> 1) * 16384 + (it & 1) * 64, 16, 1024, 1);
                const uint64_t dB = make_desc(sB + s * 12288, 4096, 1024, 1);
                if (it == 0) wgmma_n192_ss_tb_z(acc2, dA, dB); else wgmma_n192_ss_tb(acc2, dA, dB, 1);
                wgmma_n192_ss_tb(acc2, dA + 2, dB + 128, 1);
                wg_commit();
                if (it > 0) {
                    wg_wait<1>();
                    if (it <= 15) release_stage(bar + (B_E2 + (it - 1) % 5) * 8, peer, lane);
                    if (it == 14 && lane == 0) mbar_arrive(bar + B_DEAD * 8);
                }
                if (it < 6 * SPREAD) {
                    const int m = it / SPREAD, part = it % SPREAD;
                    const int hs = hs0 + 2 * m, which = hs >> 5;
                    const uint32_t* a = pk + 10 * m;
                    uint8_t* pe = img + (2 * m) * IMG_BYTES;
                    uint8_t* po = pe + IMG_BYTES;
                    if (part == 0) {
                        *(uint32_t*)(pe) = a[0];
                        *(uint32_t*)(pe + 128) = a[2];
                        *(uint32_t*)(pe + 384) = a[1];
                        *(uint32_t*)(pe + 512) = a[3];
                    }
                    if (part == (SPREAD == 3 ? 1 : 0)) {
                        const uint32_t padv = which == 0 ? 0x3F803F80u : which == 1 ? 0xBFFF4440u : 0x00003F80u;
                        const uint32_t p0 = ((c & 1) || (which == 1 && !emu0)) ? 0u : padv;
                        const uint32_t p1 = ((c & 1) || (which == 1 && !emu1)) ? 0u : padv;
                        *(uint32_t*)(pe + 256) = low ? a[4] : p0;
                        *(uint32_t*)(pe + 640) = low ? a[5] : p1;
                        *(uint32_t*)(po + 256) = low ? p0 : a[4];
                        *(uint32_t*)(po + 640) = low ? p1 : a[5];
                    }
                    if (part == SPREAD - 1) {
                        *(uint32_t*)(po) = a[6];
                        *(uint32_t*)(po + 128) = a[8];
                        *(uint32_t*)(po + 384) = a[7];
                        *(uint32_t*)(po + 512) = a[9];
                        if (which < 2) {
                            const uint32_t u0 = bf2_fma(a[4], a[4], 0u), u1 = bf2_fma(a[5], a[5], 0u);
                            const uint32_t pe0 = bf2_fma(a[0], a[0], bf2_fma(a[2], a[2], low ? u0 : 0u));
                            const uint32_t pe1 = bf2_fma(a[1], a[1], bf2_fma(a[3], a[3], low ? u1 : 0u));
                            const uint32_t po0 = bf2_fma(a[6], a[6], bf2_fma(a[8], a[8], low ? 0u : u0));
                            const uint32_t po1 = bf2_fma(a[7], a[7], bf2_fma(a[9], a[9], low ? 0u : u1));
                            const float e0 = bf_lo(pe0) + bf_hi(pe0), e1 = bf_lo(pe1) + bf_hi(pe1);
                            const float o0 = bf_lo(po0) + bf_hi(po0), o1 = bf_lo(po1) + bf_hi(po1);
                            const bool b0 = c & 1, b1_ = c & 2;
                            const float x0 = (b0 ? e1 : e0) + __shfl_xor_sync(~0u, b0 ? e0 : e1, 1);
                            const float x1 = (b0 ? o1 : o0) + __shfl_xor_sync(~0u, b0 ? o0 : o1, 1);
                            float y = (b1_ ? x1 : x0) + __shfl_xor_sync(~0u, b1_ ? x0 : x1, 2);
                            if (which == 1 && (b0 ? emu1 : emu0)) y *= 0.25f;
                            g_nrm[(hs + (c >> 1)) * SEQ + row0 + (c & 1) * 8] = y;
                        }
                    }
                    if (it == 6 * SPREAD - 1) { __syncwarp(); if (lane == 0) mbar_arrive(bar + B_ST * 8); }
                }
            }
            wg_wait<0>();
            fence_regs(acc2);
            if (lane == 0) mbar_arrive(bar + (B_DEAD + 1) * 8);
            if (threadIdx.x == 256) TL(1, 2);
            mbar_wait(bar + B_AUX2 * 8, 0);
            if (threadIdx.x == 256) TL(4, 0);
            const uint32_t* bias = reinterpret_cast<const uint32_t*>(smem + SM_BIAS) + c;
            const int mrow = w4 * 16 + (lane & 15);
            const uint32_t stage = sAw + 7 * 16384;
            const uint32_t st_row = stage + mrow * 128;
            uint32_t hv[48];
#pragma unroll
            for (int j = 0; j < 24; j++) {
                const uint32_t bA = bias[j * 4];
                const float2 cA = cs[(30 + j) * 4];
                const float* a = acc2 + j * 4;
                hv[2 * j] = gelu_half2(fmaf(a[0], r20, fmaf(e20, cA.x, bf_lo(bA))), fmaf(a[1], r20, fmaf(e20, cA.y, bf_hi(bA))));
                hv[2 * j + 1] = gelu_half2(fmaf(a[2], r21, fmaf(e21, cA.x, bf_lo(bA))), fmaf(a[3], r21, fmaf(e21, cA.y, bf_hi(bA))));
            }
#pragma unroll
            for (int j = 0; j < 24; j += 2) {
                const int chunk = (j & 7) + (lane >> 4);
                stmatrix_x4(st_row + (j >> 3) * 16384 + ((chunk ^ (mrow & 7)) << 4), hv[2 * j], hv[2 * j + 1], hv[2 * j + 2], hv[2 * j + 3]);
            }
            if (threadIdx.x == 256) TL(4, 1);
            fence_proxy_async();
            __syncwarp();
            if (lane == 0) mbar_arrive(bar + (B_ST + 1) * 8);
            asm volatile("bar.sync %0, 128;" ::"r"(wgi + 3) : "memory");
            reg_dealloc<128>();
            if (threadIdx.x == 256) TL(4, 3);
        }
        __syncthreads();
        if (threadIdx.x == 0) TL(1, 3);
    }

    {
        const int h = blockIdx.x >> 2, qb = blockIdx.x & 3;
        const uint32_t sK = sb + SM_K, sV = sb + SM_V, barKV = bar + B_KV * 8;
        if (threadIdx.x == 0) TL(2, 0);
        auto late_tiles = [&]() {
            if (warp == 5 && lane == 0) {
                bulk_wait_read();
                asm volatile("fence.proxy.async.global;" ::: "memory");
                const uint8_t* gK = g_img + (size_t)(32 + h) * IMG_BYTES;
                const uint8_t* gV = g_img + (size_t)(64 + h) * IMG_BYTES;
                for (int i = 9; i < 16; i++) {
                    if (i >= 13) mbar_expect_tx(barKV + i * 8, i < 15 ? 12288 : 6144);
                    bulk_load(sV + ((i + 7) & 15) * 6144, gV + i * 6144, 6144, barKV + i * 8);
                    if (i >= 13 && i < 15) bulk_load(sK + (i + 1) * 6144, gK + (i + 1) * 6144, 6144, barKV + i * 8);
                }
            }
            __syncwarp();
        };
        const bool safe = __all_sync(~0u, *reinterpret_cast<volatile uint32_t*>(smem + SM_SAFE) != 0);
        if (threadIdx.x == 0) TL(2, 1);
        const uint64_t dK0 = make_desc(sK, 128, 384, 0), dV0 = make_desc(sV, 384, 128, 0);
        auto publish_h = [&]() {
            if (warp == 5) {
                if (lane == 0) { bulk_wait_all(); cnt_signal(CNT_H + rb); }
                __syncwarp();
            }
        };
        auto g2_issue = [&](int kb) {
            const int ct = (blockIdx.x >> 1) & 3, rt = (blockIdx.x >> 3) * 2 + (blockIdx.x & 1);
            const uint32_t dst = sb + g2_slot(kb), fb = bar + (B_F3 + kb) * 8;
            mbar_expect_tx(fb, G2_STAGE);
            tma_load(dst, &tm.h, kb * 64, rt * 64, fb);
            const int b0 = ((kb & 1) == (int)rank) ? 0 : 3;
            tma_load_mc(dst + 8192 + b0 * 4096, &tm.w2, ct * 160 + b0 * 32, kb * 64, fb, 3);
            tma_load_mc(dst + 8192 + b0 * 4096 + 4096, &tm.w2, ct * 160 + b0 * 32 + 32, kb * 64, fb, 3);
            if (b0 == 0) tma_load_mc(dst + 8192 + 8192, &tm.w2, ct * 160 + 64, kb * 64, fb, 3);
        };
        auto pf_arrive = [&](int step) {
            asm volatile("{\n.reg .pred p;\n.reg .b32 ra;\nelect.sync _|p, 0xFFFFFFFF;\nmapa.shared::cluster.u32 ra, %0, %1;\n"
                         "@p mbarrier.arrive.shared::cta.b64 _, [%0];\n@p mbarrier.arrive.shared::cluster.b64 _, [ra];\n}"
                         ::"r"(bar + (B_PF + step) * 8), "r"(peer) : "memory");
        };
        auto pf_issue = [&](int step) {
            if (warp == 4) {
                if (elect_one()) {
                    if (step == 0) cnt_wait(CNT_H + (blockIdx.x >> 3), (*reinterpret_cast<volatile uint32_t*>(smem + SM_EPOCH) + 1) * 8);
                    g2_issue(2 * step);
                    if (step < 2) g2_issue(2 * step + 1);
                }
                __syncwarp();
            }
        };
        if (!safe) {
            late_tiles();
#pragma unroll 1
            for (int pass = 0; pass < 2; pass++) {
                const uint32_t sQ = sb + SM_Q + pass * 12288 + wgi * 3072;
                mbar_wait(bar + (B_Q + pass) * 8, 0);
                attn_rows_maxshift(sK, barKV, make_desc(sQ, 128, 384, 0), make_desc(sQ + 256, sb + SM_ZERO - (sQ + 256), 384, 0), h,
                                   qb * 512 + pass * 256 + wgi * 64 + w4 * 16);
                if (pass == 0) publish_h();
            }
            pf_arrive(0); pf_arrive(1); pf_arrive(2);
            if (warp == 4) {
                mbar_wait(bar + B_PF * 8, 0); pf_issue(0);
                mbar_wait(bar + (B_PF + 1) * 8, 0); pf_issue(1);
            }
        } else {
            const ExpConst kc = make_exp_const();
            auto attn_pass = [&](auto pass_c) {
                constexpr int pass = decltype(pass_c)::value;
                const int rbase = qb * 512 + pass * 256 + wgi * 64 + w4 * 16;
                const uint32_t sQ = sb + SM_Q + pass * 12288 + wgi * 3072;
                const uint64_t dQ = make_desc(sQ, 128, 384, 0), dQ2 = make_desc(sQ + 256, sb + SM_ZERO - (sQ + 256), 384, 0);
                float o[12], sa[32], sc[32];
                uint32_t p[16];
#pragma unroll
                for (int i = 0; i < 12; i++) o[i] = 0.f;
                fence_regs(o);
                mbar_wait(bar + (B_Q + pass) * 8, 0);
                mbar_wait(barKV + 128, 0);
                qk_tile(sa, dQ, dQ2, dK0);
                wg_wait<0>();
                fence_regs(sa);
                uint64_t dK = dK0, dV = dV0 + 7 * 384;
                uint32_t bj = barKV;
#pragma unroll 1
                for (int j = 0; j < 16; j++) {
                    mbar_wait(bj, 0);
                    if (pass == 0) {
                        if (j == 2) late_tiles();
                        if (j == 5) publish_h();
                    } else {
                        if (j == 6 || j == 10 || j == 14) pf_arrive((j - 6) >> 2);
                    }
                    qk_tile(sc, dQ, dQ2, dK + 192);
                    wg_wait<1>();
                    exp_tile<0>(sa, p, kc);
                    pv_tile(o, p, dV);
                    wg_wait<1>();
                    fence_regs(sc);
                    mbar_wait(bj, 0);
                    if (pass == 1 && (j == 8 || j == 12) && warp == 4) {
                        mbar_wait(bar + (B_PF + ((j - 8) >> 2)) * 8, 0);
                        pf_issue((j - 8) >> 2);
                    }
                    qk_tile(sa, dQ, dQ2, dK + 384);
                    wg_wait<1>();
                    exp_tile<8>(sc, p, kc);
                    pv_tile(o, p, dV + 192);
                    wg_wait<1>();
                    fence_regs(sa);
                    dK += 384; dV = j == 8 ? dV0 : dV + 384; bj += 8;
                }
                wg_wait<0>();
                fence_regs(o);
                store_o(o, h, rbase, lane);
                if (threadIdx.x == 0) TL(2, 2 + pass);
            };
            attn_pass(IntC<0>{});
            attn_pass(IntC<1>{});
        }
        if (wgi == 0) {
            asm volatile("bar.arrive 10, 512;" ::: "memory");
        } else {
            if (warp == 4) { mbar_wait(bar + (B_PF + 2) * 8, 0); pf_issue(2); }
            asm volatile("bar.sync 10, 512;" ::: "memory");
            if (threadIdx.x == 320) cnt_signal(CNT_O + qb);
        }
        cluster_arrive_relaxed();
    }

    {
        const uint32_t epoch = *reinterpret_cast<volatile uint32_t*>(smem + SM_EPOCH);
        const int ct = cl & 3, rt = (cl >> 2) * 2 + rank;
        if (threadIdx.x == 0) TL(3, 0);
        const int ot = threadIdx.x - 192, orow = ot / 5, oseg = ot - orow * 5;
        const size_t ooff = (size_t)(rt * 64 + orow) * DM + ct * 160 + oseg * 32;
        uint4 xr[4], br[4];
        if (ot >= 0) {
#pragma unroll
            for (int i = 0; i < 4; i++) {
                asm volatile("ld.global.nc.v4.u32 {%0, %1, %2, %3}, [%4];" : "=r"(xr[i].x), "=r"(xr[i].y), "=r"(xr[i].z), "=r"(xr[i].w)
                             : "l"(reinterpret_cast<const uint4*>(x + ooff) + i));
                asm volatile("ld.global.nc.v4.u32 {%0, %1, %2, %3}, [%4];" : "=r"(br[i].x), "=r"(br[i].y), "=r"(br[i].z), "=r"(br[i].w)
                             : "l"(reinterpret_cast<const uint4*>(b2 + ct * 160 + oseg * 32) + i));
            }
        }
        if (wgi != 0) cluster_wait();
        float* stg = reinterpret_cast<float*>(smem);
        if (warp >= 4 && warp < 4 + NPROD) {
#pragma unroll 1
            for (int kb = 5 + (warp - 4); kb < 34; kb += NPROD) {
                const int s = kb % 7;
                if (lane == 0) IT(2, kb);
                if (kb >= 7) mbar_wait(bar + (B_E3 + s) * 8, ((kb / 7) - 1) & 1);
                if (lane == 0) IT(3, kb);
                if (elect_one()) {
                    if (kb == 24) { cnt_wait(CNT_O + (rt >> 3), (epoch + 1) * 32); TL(3, 1); }
                    const uint32_t dst = sb + g2_slot(s), fb = bar + (B_F3 + s) * 8;
                    const CUtensorMap* mA = kb < 24 ? &tm.h : &tm.o;
                    const CUtensorMap* mB = kb < 24 ? &tm.w2 : &tm.wo;
                    const int k0 = (kb < 24 ? kb : kb - 24) * 64;
                    mbar_expect_tx(fb, G2_STAGE);
                    tma_load(dst, mA, k0, rt * 64, fb);
                    const int first = ((kb & 1) == (int)rank) ? 0 : 3, last = ((kb & 1) == (int)rank) ? 3 : 5;
                    for (int b = first; b < last; b++) tma_load_mc(dst + 8192 + b * 4096, mB, ct * 160 + b * 32, k0, fb, 3);
                }
                __syncwarp();
            }
        } else if (wgi == 0) {
            float acc[80];
#pragma unroll 1
            for (int kb = 0; kb < 34; kb++) {
                const int s = kb % 7;
                if (threadIdx.x == 0) IT(4, kb);
                mbar_wait(bar + (B_F3 + s) * 8, (kb / 7) & 1);
                if (threadIdx.x == 0) IT(5, kb);
                const uint64_t dA = make_desc(sb + g2_slot(s), 16, 1024, 1);
                const uint64_t dB = make_desc(sb + g2_slot(s) + 8192, 4096, 512, 2);
                wg_fence();
#pragma unroll
                for (int kk = 0; kk < 4; kk++) wgmma_n160_ss_tb(acc, dA + kk * 2, dB + kk * 64, (kb | kk) != 0);
                wg_commit();
                if (kb > 0) {
                    wg_wait<1>();
                    if (kb <= 27) release_stage(bar + (B_E3 + (kb - 1) % 7) * 8, peer, lane);
                }
            }
            wg_wait<0>();
            fence_regs(acc);
            cluster_wait();
            if (threadIdx.x == 0) TL(3, 2);
            const int r = w4 * 16 + g;
#pragma unroll
            for (int j = 0; j < 20; j++) {
                *reinterpret_cast<float2*>(stg + r * 184 + j * 8 + (j >> 2) * 4 + 2 * c) = make_float2(acc[4 * j], acc[4 * j + 1]);
                *reinterpret_cast<float2*>(stg + (r + 8) * 184 + j * 8 + (j >> 2) * 4 + 2 * c) = make_float2(acc[4 * j + 2], acc[4 * j + 3]);
            }
        }
        __syncthreads();
        if (ot >= 0) {
            const float4* sp = reinterpret_cast<const float4*>(stg + orow * 184 + oseg * 36);
#pragma unroll
            for (int i = 0; i < 4; i++) {
                const float4 a = sp[2 * i], b = sp[2 * i + 1];
                uint4 w;
                w.x = pack_bf16(a.x + bf_lo(br[i].x) + bf_lo(xr[i].x), a.y + bf_hi(br[i].x) + bf_hi(xr[i].x));
                w.y = pack_bf16(a.z + bf_lo(br[i].y) + bf_lo(xr[i].y), a.w + bf_hi(br[i].y) + bf_hi(xr[i].y));
                w.z = pack_bf16(b.x + bf_lo(br[i].z) + bf_lo(xr[i].z), b.y + bf_hi(br[i].z) + bf_hi(xr[i].z));
                w.w = pack_bf16(b.z + bf_lo(br[i].w) + bf_lo(xr[i].w), b.w + bf_hi(br[i].w) + bf_hi(xr[i].w));
                reinterpret_cast<uint4*>(out + ooff)[i] = w;
            }
        }
        if (blockIdx.x == 0 && threadIdx.x == 0) g_epoch = epoch + 1;
        if (threadIdx.x == 256) TL(3, 3);
    }
}

typedef CUresult (*EncodeTiledFn)(CUtensorMap*, CUtensorMapDataType, cuuint32_t, void*, const cuuint64_t*,
                                  const cuuint64_t*, const cuuint32_t*, const cuuint32_t*, CUtensorMapInterleave,
                                  CUtensorMapSwizzle, CUtensorMapL2promotion, CUtensorMapFloatOOBfill);

CUtensorMap make_map(EncodeTiledFn enc, const void* ptr, int rows, int cols, int box_rows, int box_cols,
                     CUtensorMapSwizzle swz) {
    CUtensorMap m;
    cuuint64_t gd[2] = {(cuuint64_t)cols, (cuuint64_t)rows};
    cuuint64_t gs[1] = {(cuuint64_t)cols * 2};
    cuuint32_t bd[2] = {(cuuint32_t)box_cols, (cuuint32_t)box_rows};
    cuuint32_t es[2] = {1, 1};
    enc(&m, CU_TENSOR_MAP_DATA_TYPE_BFLOAT16, 2, const_cast<void*>(ptr), gd, gs, bd, es, CU_TENSOR_MAP_INTERLEAVE_NONE,
        swz, CU_TENSOR_MAP_L2_PROMOTION_L2_128B, CU_TENSOR_MAP_FLOAT_OOB_FILL_NONE);
    return m;
}

}

extern "C" void kernel_launch(void* const* d_in, const int* in_sizes, int n_in, void* d_out, int out_size) {
    (void)in_sizes; (void)n_in; (void)out_size;
    const __nv_bfloat16* x = (const __nv_bfloat16*)d_in[0];
    const __nv_bfloat16* wqkv = (const __nv_bfloat16*)d_in[1];
    const __nv_bfloat16* wo = (const __nv_bfloat16*)d_in[2];
    const __nv_bfloat16* w1 = (const __nv_bfloat16*)d_in[4];
    const __nv_bfloat16* b1 = (const __nv_bfloat16*)d_in[5];
    const __nv_bfloat16* w2 = (const __nv_bfloat16*)d_in[6];
    const __nv_bfloat16* b2 = (const __nv_bfloat16*)d_in[7];
    __nv_bfloat16* out = (__nv_bfloat16*)d_out;

    static EncodeTiledFn enc = nullptr;
    static void *p_h, *p_o;
    if (!enc) {
        cudaDriverEntryPointQueryResult qr;
        cudaGetDriverEntryPoint("cuTensorMapEncodeTiled", (void**)&enc, cudaEnableDefault, &qr);
        cudaGetSymbolAddress(&p_h, g_h);
        cudaGetSymbolAddress(&p_o, g_o);
        cudaFuncSetAttribute(k_fused, cudaFuncAttributeMaxDynamicSharedMemorySize, SM_TOTAL);
    }
    Maps tm;
    tm.x = make_map(enc, x, SEQ, DM, 128, 64, CU_TENSOR_MAP_SWIZZLE_128B);
    tm.wqkv = make_map(enc, wqkv, DM, 3 * DM, 32, 64, CU_TENSOR_MAP_SWIZZLE_128B);
    tm.w1 = make_map(enc, w1, DM, FF, 32, 64, CU_TENSOR_MAP_SWIZZLE_128B);
    tm.h = make_map(enc, p_h, SEQ, FF, 64, 64, CU_TENSOR_MAP_SWIZZLE_128B);
    tm.o = make_map(enc, p_o, SEQ, DM, 64, 64, CU_TENSOR_MAP_SWIZZLE_128B);
    tm.wo = make_map(enc, wo, DM, DM, 64, 32, CU_TENSOR_MAP_SWIZZLE_64B);
    tm.w2 = make_map(enc, w2, FF, DM, 64, 32, CU_TENSOR_MAP_SWIZZLE_64B);
    k_fused<<<128, 512, SM_TOTAL, cudaStreamPerThread>>>(tm, x, (const uint8_t*)wqkv, (const uint8_t*)w1, (const uint8_t*)w2,
                                                         (const uint8_t*)wo, b1, b2, out);
}
```
